```python
import torch

def _softmax(x, axis=-1):
    return torch.softmax(x, dim=axis)
def _gelu(x):
    return torch.nn.functional.gelu(x, approximate="tanh")
def _silu(x):
    return torch.nn.functional.silu(x)
def _sigmoid(x):
    return torch.sigmoid(x)
def _layernorm(x, axis=-1, eps=1e-5):
    m = x.mean(dim=axis, keepdim=True)
    v = x.var(dim=axis, keepdim=True, unbiased=False)
    return (x - m) / torch.sqrt(v + eps)
def _scatter_add(tgt, idx, src, axis=0):
    return tgt.clone().index_add_(axis, idx, src)
def _segment_sum(src, seg, n):
    out = torch.zeros((n,) + src.shape[1:], dtype=src.dtype)
    return out.index_add_(0, seg, src)
def _pad(x, pw):
    flat = tuple(v for pair in reversed(pw) for v in pair)
    return torch.nn.functional.pad(x, flat)

kernel_name = 'concat_heads__ssm_conv_h3__linear_attn_block__prompt'

def setup_inputs():

    _w = (lambda a: (lambda t: t.to(torch.bfloat16) if t.is_floating_point() else t)(torch.as_tensor(a)))
    def _A_setup():
        B, S, D = 1, 2048, 1024
        ks = 4
        return {
            "q": _w((lambda *s: torch.randn(*s, dtype=torch.bfloat16) * 0.05)(B, S, D)),
            "k": _w((lambda *s: torch.randn(*s, dtype=torch.bfloat16) * 0.4)(B, S, D)),
            "v": _w((lambda *s: torch.randn(*s, dtype=torch.bfloat16) * 0.4)(B, S, D)),
            "shift_k": _w((lambda *s: torch.randn(*s, dtype=torch.bfloat16) * 0.4)(D, ks) * 0.5),
            "ssm_k": _w((lambda *s: torch.randn(*s, dtype=torch.bfloat16) * 1.6)(D, S) * (1.0 / S ** 0.5)),
            "ssm_D": _w((lambda *s: torch.randn(*s, dtype=torch.bfloat16) * 0.4)(D)),
        }
    _A_in = _A_setup()

    def _B_setup():
        B, S, D = 1, 2048, 1024
        return {
            "x": _w((lambda *s: torch.randn(*s, dtype=torch.bfloat16) * 0.05)(B, S, D)),
            "wqkv": _w((lambda *s: torch.randn(*s, dtype=torch.bfloat16) * 0.8)(D, 3 * D)),
            "wo": _w((lambda *s: torch.randn(*s, dtype=torch.bfloat16) * 0.05)(D, D)),
        }
    _B_in = _B_setup()

    return {
        "A_q": _A_in["q"],
        "A_k": _A_in["k"],
        "A_v": _A_in["v"],
        "A_shift_k": _A_in["shift_k"],
        "A_ssm_k": _A_in["ssm_k"],
        "A_ssm_D": _A_in["ssm_D"],
        "B_x": _B_in["x"],
        "B_wqkv": _B_in["wqkv"],
        "B_wo": _B_in["wo"],
    }

def reference(A_q, A_k, A_v, A_shift_k, A_ssm_k, A_ssm_D, B_x, B_wqkv, B_wo):
    def _A_ref(q, k, v, shift_k, ssm_k, ssm_D):
        B, S, D = q.shape
        ks = shift_k.shape[-1]
        k_pad = _pad(k, ((0, 0), (ks - 1, 0), (0, 0)))
        k_shift = torch.zeros_like(k)
        for t in range(ks):
            k_shift = k_shift + k_pad[:, t:t + S, :] * shift_k[:, ks - 1 - t][None, None, :]
        kv = k_shift * v
        L = 2 * S
        kv_pad = _pad(kv, ((0, 0), (0, S), (0, 0)))
        kf_pad = _pad(ssm_k, ((0, 0), (0, S)))
        kv_f = (lambda x, axes=(-2,-1): torch.fft.rfft2(x.float(), dim=axes))(kv_pad[:, None, :, :], axes=(1, 2))
        kf_f = (lambda x, axes=(-2,-1): torch.fft.rfft2(x.float(), dim=axes))(kf_pad[:, None, :], axes=(1, 2))
        kf_f = (lambda x, *d: x.permute(*d))(kf_f, 1, 2, 0)
        y_f = kv_f * kf_f[None, :, :, :]
        y = (lambda x, s, axes=(-2,-1): torch.fft.irfft2(x, s=s, dim=axes).to(torch.bfloat16))(y_f, (1, L), axes=(1, 2))[:, 0, :S, :]
        y = y + kv * ssm_D[None, None, :]
        return q * y

    def _B_ref(x, wqkv, wo):
        B, S, D = x.shape
        H = 32; Dh = D // H
        qkv = (lambda x, *d: x.permute(*d))((x @ wqkv).reshape(B, S, 3, H, Dh), 2, 0, 3, 1, 4)
        q, k, v = qkv[0], qkv[1], qkv[2]
        phi = lambda t: torch.where(t > 0, t + 1, torch.exp(t)) + 1e-6
        pq, pk = phi(q), phi(k)
        kv = torch.einsum("bhsd,bhse->bhde", pk, v)
        z = torch.einsum("bhsd->bhd", pk)
        num = torch.einsum("bhqd,bhde->bhqe", pq, kv)
        den = torch.einsum("bhqd,bhd->bhq", pq, z)[..., None] + 1e-6
        o = num / den
        return (lambda x, *d: x.permute(*d))(o, 0, 2, 1, 3).reshape(B, S, D) @ wo

    a = _A_ref(A_q, A_k, A_v, A_shift_k, A_ssm_k, A_ssm_D)
    b = _B_ref(B_x, B_wqkv, B_wo)
    return torch.concatenate([a, b], axis=-1)
```

```cpp
#include <cuda_runtime.h>
#include <cuda_bf16.h>
#include <cuda.h>
#include <stdint.h>

#define PARAM(name, value) constexpr int name = value
#define TUNE
namespace dflt {
PARAM(SK1, 2); PARAM(SK2, 3); PARAM(SK3, 2);
PARAM(NX, 0); PARAM(XPACE, 1); PARAM(MID, 3);
PARAM(STG_T0, 1300); PARAM(STG_DT, 540);
PARAM(Q_ST, 10);
PARAM(OA_END, 7400); PARAM(OA_MIN, 200); PARAM(OA_MAX, 450);
PARAM(PF_DT0, 200); PARAM(PF_DT1, 1060); PARAM(PF_DT2, 512); PARAM(PF_N1, 9);
}
#define PF_LIST 0x01, 0x11, 0x02, 0x12, 0x03, 0x13, 0x04, 0x14, 0x05, 0x15, 0x51, 0x06, 0x16, 0x20, 0x07, 0x17, 0x21, 0x22, 0x23, \
                0x40, 0x41, 0x42, 0x43, 0x44, 0x45, 0x46, 0x47, 0x30, 0x31, 0x32, 0x33, 0x57, 0x56
#define PF_N (31 + NX)
#define WAIT_BOUND 262144

namespace {
using namespace dflt;
TUNE

constexpr int S_LEN = 2048;
constexpr int DM    = 1024;
constexpr int NCTA  = 128;
constexpr int NTHREADS = 512;
constexpr int SLOT  = 32768;
constexpr int W_OFF = 3 * SLOT;
constexpr int M_OFF = 4 * SLOT;
constexpr int VT    = 16 * 1152;
constexpr int T_OFF = M_OFF + 43008;
constexpr int XS    = 4096 + 16;
constexpr int YX    = 2048 + 16;
constexpr int X_OFF = T_OFF + 8192 + 2176;
constexpr int H_OFF = X_OFF + 8 * XS;
constexpr int A_OFF = H_OFF + 4096;
constexpr int F_OFF = A_OFF + 8192;
constexpr int BAR_OFF = F_OFF + 2048;
constexpr int D_OFF = BAR_OFF + 384;
constexpr int SMEM_BYTES = D_OFF + 64 + 256;
constexpr int KB = 8704;
constexpr int KVB_OFF = M_OFF + 32768;
static_assert(H_OFF % 256 == 0 && X_OFF % 128 == 0 && SMEM_BYTES <= 232448, "layout");
constexpr int B_XF = 0, B_F0 = 3, B_FULL = 4, B_FULL2 = 25, B_KVL = 24, B_STG = 8, B_X = 12, B_Z = 13, B_H = 14, B_Q = 15, B_YR = 16,
              B_SK = 29, B_GO = 30, B_QE = 31,
              B_EMPTY = 32, B_KVB = 36, B_EMPTY2 = 37, B_SFREE = 41, B_HX = 44, B_XK = 46;
constexpr int KV_PER_HP = 2 * 1056;

__device__ __align__(1024) uint4 g_O[S_LEN * DM / 8];
__device__ __align__(128) float g_kv[16 * KV_PER_HP];
__device__ __align__(128) unsigned g_cnt[32 * 32];

#define OSTAMP(i) do {} while (0)
#define TSTAMP(k, i) do {} while (0)

__device__ __forceinline__ uint32_t cta_ids() {
  const uint32_t b = blockIdx.x, c = b >> 1, q = ((c - 36) * 37) >> 8;
  const uint32_t lo = (4 + c) << 12, mid = (((c - 4) & 7) << 8) + (((c - 4) >> 3) << 12), hi = ((c - 35) << 8) + q * (4096 - 7 * 256) + (4 << 12);
  uint32_t r;
  asm("{\n.reg .pred p, q;\nsetp.lt.u32 p, %4, 4;\nsetp.lt.u32 q, %4, 36;\nselp.u32 %0, %2, %3, q;\nselp.u32 %0, %1, %0, p;\n}" : "=&r"(r) : "r"(lo), "r"(mid), "r"(hi), "r"(c));
  return r + b;
}

#define ELECT "{\n.reg .pred e;\nelect.sync _|e, 0xffffffff;\n@e "
__device__ __forceinline__ uint32_t uni(uint32_t v) { return __shfl_sync(0xffffffffu, v, 0); }
__device__ __forceinline__ uint32_t fresh(uint32_t v) { asm volatile("" : "+r"(v)); return v; }
__device__ __forceinline__ uint32_t smem_u32(const void* p) { return (uint32_t)__cvta_generic_to_shared(p); }
__device__ __forceinline__ void mbar_init(uint32_t b, uint32_t c) { asm volatile(ELECT "mbarrier.init.shared::cta.b64 [%0], %1;\n}" :: "r"(b), "r"(c) : "memory"); }
__device__ __forceinline__ void mbar_expect_tx(uint32_t b, uint32_t bytes) { asm volatile(ELECT "mbarrier.arrive.expect_tx.shared::cta.b64 _, [%0], %1;\n}" :: "r"(b), "r"(bytes) : "memory"); }
__device__ __forceinline__ void mbar_arrive(uint32_t b) { asm volatile(ELECT "mbarrier.arrive.shared::cluster.b64 _, [%0];\n}" :: "r"(b) : "memory"); }
__device__ __forceinline__ void mbar_wait(uint32_t b, uint32_t ph) {
  asm volatile("{\n.reg .pred p;\n.reg .u32 n;\nmov.u32 n, 0;\n"
    "WAIT_LOOP:\nmbarrier.try_wait.parity.shared::cta.b64 p, [%0], %1;\n@p bra.uni WAIT_DONE;\n"
    "add.u32 n, n, 1;\nsetp.lt.u32 p, n, %2;\n@p bra.uni WAIT_LOOP;\nWAIT_DONE:\n}" :: "r"(b), "r"(ph), "n"(WAIT_BOUND) : "memory"); }
__device__ __forceinline__ void tma2d(uint32_t dst, const CUtensorMap* m, int c0, int c1, uint32_t bar) {
  asm volatile(ELECT "cp.async.bulk.tensor.2d.shared::cluster.global.mbarrier::complete_tx::bytes [%0], [%1, {%3, %4}], [%2];\n}"
    :: "r"(dst), "l"(m), "r"(bar), "r"(c0), "r"(c1) : "memory"); }
__device__ __forceinline__ void tma2d_mc(uint32_t dst, const CUtensorMap* m, int c0, int c1, uint32_t bar) {
  asm volatile(ELECT "cp.async.bulk.tensor.2d.shared::cluster.global.mbarrier::complete_tx::bytes.multicast::cluster [%0], [%1, {%3, %4}], [%2], %5;\n}"
    :: "r"(dst), "l"(m), "r"(bar), "r"(c0), "r"(c1), "h"((uint16_t)3) : "memory"); }
__device__ __forceinline__ void tma3d(uint32_t dst, const CUtensorMap* m, int c0, int c1, int c2, uint32_t bar) {
  asm volatile(ELECT "cp.async.bulk.tensor.3d.shared::cluster.global.mbarrier::complete_tx::bytes [%0], [%1, {%3, %4, %5}], [%2];\n}"
    :: "r"(dst), "l"(m), "r"(bar), "r"(c0), "r"(c1), "r"(c2) : "memory"); }
__device__ __forceinline__ void tma2d_store(const CUtensorMap* m, int c0, int c1, uint32_t src) {
  asm volatile(ELECT "cp.async.bulk.tensor.2d.global.shared::cta.bulk_group [%0, {%2, %3}], [%1];\n}"
    :: "l"(m), "r"(src), "r"(c0), "r"(c1) : "memory"); }
__device__ __forceinline__ void bulk_load(uint32_t dst, const void* src, uint32_t bytes, uint32_t bar) {
  asm volatile(ELECT "cp.async.bulk.shared::cluster.global.mbarrier::complete_tx::bytes [%0], [%1], %2, [%3];\n}"
    :: "r"(dst), "l"(src), "r"(bytes), "r"(bar) : "memory"); }
__device__ __forceinline__ void bulk_commit() { asm volatile("cp.async.bulk.commit_group;" ::: "memory"); }
__device__ __forceinline__ void bulk_wait_read() { asm volatile("cp.async.bulk.wait_group.read 0;" ::: "memory"); }
__device__ __forceinline__ void fence_async_smem() { asm volatile("fence.proxy.async.shared::cta;" ::: "memory"); }
__device__ __forceinline__ void bar_sync(int id, int n) { asm volatile("bar.sync %0, %1;" :: "r"(id), "r"(n) : "memory"); }
__device__ __forceinline__ void bar_arrive(int id, int n) { asm volatile("bar.arrive %0, %1;" :: "r"(id), "r"(n) : "memory"); }
__device__ __forceinline__ void wg_fence() { asm volatile("wgmma.fence.sync.aligned;" ::: "memory"); }
__device__ __forceinline__ void wg_commit() { asm volatile("wgmma.commit_group.sync.aligned;" ::: "memory"); }
template <int N> __device__ __forceinline__ void wg_wait() { asm volatile("wgmma.wait_group.sync.aligned %0;" :: "n"(N) : "memory"); }
constexpr uint32_t SB0 = 1024;
__host__ __device__ constexpr uint64_t cdesc(uint32_t off, uint32_t lbo, uint32_t sbo, uint32_t swz) {
  return (uint64_t)((SB0 + off) >> 4) | ((uint64_t)(lbo >> 4) << 16) | ((uint64_t)(sbo >> 4) << 32) | ((uint64_t)swz << 62); }
__device__ __forceinline__ uint64_t dofs(uint64_t d, uint32_t bytes) { return (d & 0xffffffff00000000ull) | (uint32_t)((uint32_t)d + (bytes >> 4)); }
__device__ __forceinline__ uint32_t mbar_try(uint32_t b, uint32_t ph) {
  uint32_t ok;
  asm volatile("{\n.reg .pred p;\nmbarrier.test_wait.parity.shared::cta.b64 p, [%1], %2;\nselp.u32 %0, 1, 0, p;\n}" : "=r"(ok) : "r"(b), "r"(ph) : "memory");
  return ok; }
__device__ __forceinline__ void arrive_at(uint32_t a, bool on) {
  asm volatile("{\n.reg .pred p;\nsetp.ne.b32 p, %1, 0;\n@p mbarrier.arrive.shared::cluster.b64 _, [%0];\n}" :: "r"(a), "r"((uint32_t)on) : "memory"); }
__device__ __forceinline__ void ldsm4(uint32_t* r, uint32_t a) {
  asm volatile("ldmatrix.sync.aligned.m8n8.x4.shared.b16 {%0,%1,%2,%3}, [%4];" : "=r"(r[0]), "=r"(r[1]), "=r"(r[2]), "=r"(r[3]) : "r"(a) : "memory"); }
__device__ __forceinline__ void ldsm4t(uint32_t* r, uint32_t a) {
  asm volatile("ldmatrix.sync.aligned.m8n8.x4.trans.shared.b16 {%0,%1,%2,%3}, [%4];" : "=r"(r[0]), "=r"(r[1]), "=r"(r[2]), "=r"(r[3]) : "r"(a) : "memory"); }
__device__ __forceinline__ void stsm4(uint32_t a, uint32_t r0, uint32_t r1, uint32_t r2, uint32_t r3) {
  asm volatile("stmatrix.sync.aligned.m8n8.x4.shared.b16 [%0], {%1,%2,%3,%4};" :: "r"(a), "r"(r0), "r"(r1), "r"(r2), "r"(r3) : "memory"); }
__device__ __forceinline__ void stsm4t(uint32_t a, uint32_t r0, uint32_t r1, uint32_t r2, uint32_t r3) {
  asm volatile("stmatrix.sync.aligned.m8n8.x4.trans.shared.b16 [%0], {%1,%2,%3,%4};" :: "r"(a), "r"(r0), "r"(r1), "r"(r2), "r"(r3) : "memory"); }
__device__ __forceinline__ uint32_t lds32(uint32_t a) { uint32_t v; asm volatile("ld.shared.b32 %0, [%1];" : "=r"(v) : "r"(a) : "memory"); return v; }
__device__ __forceinline__ void lds128(uint32_t* v, uint32_t a) { asm volatile("ld.shared.v4.b32 {%0,%1,%2,%3}, [%4];" : "=r"(v[0]), "=r"(v[1]), "=r"(v[2]), "=r"(v[3]) : "r"(a) : "memory"); }
__device__ __forceinline__ void sts32(uint32_t a, uint32_t v) { asm volatile("st.shared.b32 [%0], %1;" :: "r"(a), "r"(v) : "memory"); }
__device__ __forceinline__ void sts128(uint32_t a, uint32_t v0, uint32_t v1, uint32_t v2, uint32_t v3) {
  asm volatile("st.shared.v4.b32 [%0], {%1,%2,%3,%4};" :: "r"(a), "r"(v0), "r"(v1), "r"(v2), "r"(v3) : "memory"); }
__device__ __forceinline__ uint32_t pack_bf16(float lo, float hi) { uint32_t r; asm("cvt.rn.bf16x2.f32 %0, %1, %2;" : "=r"(r) : "f"(hi), "f"(lo)); return r; }
__device__ __forceinline__ void sched_fence(uint32_t& key) {
  asm volatile("{\n.reg .pred p;\nsetp.eq.u32 p, %0, 0;\nSF_LOOP:\n@p pmevent 1;\n@p bra.uni SF_LOOP;\n}" :: "r"(key) : "memory");
  key++;
}
template <int N> __device__ __forceinline__ void pinv(float* v) {
  #pragma unroll
  for (int i = 0; i < N; i++) asm volatile("" : "+f"(v[i]) :: "memory"); }
__device__ __forceinline__ uint32_t bmul2(uint32_t a, uint32_t b) { uint32_t r; asm("mul.rn.bf16x2 %0, %1, %2;" : "=r"(r) : "r"(a), "r"(b)); return r; }
__device__ __forceinline__ uint32_t badd2(uint32_t a, uint32_t b) { uint32_t r; asm("add.rn.bf16x2 %0, %1, %2;" : "=r"(r) : "r"(a), "r"(b)); return r; }
__device__ __forceinline__ void spin_until(const unsigned* p, unsigned target) {
  int n = 0;
  unsigned v;
  do { asm volatile("ld.relaxed.gpu.global.u32 %0, [%1];" : "=r"(v) : "l"(p) : "memory"); } while ((int)(v - target) < 0 && ++n < WAIT_BOUND);
  asm volatile("fence.acquire.gpu;" ::: "memory");
}
__device__ __forceinline__ void cluster_wait() { asm volatile("barrier.cluster.wait.aligned;" ::: "memory"); }
__device__ __forceinline__ void fence_gpu() { asm volatile("fence.release.gpu;" ::: "memory"); }
__device__ __forceinline__ void fence_async_global() { asm volatile("fence.proxy.async.global;" ::: "memory"); }
__device__ __forceinline__ void red_add(unsigned* p) { asm volatile(ELECT "red.relaxed.gpu.global.add.u32 [%0], 1;\n}" :: "l"(p) : "memory"); }
__device__ __forceinline__ float rcp_fast(float x) { float r; asm("rcp.approx.ftz.f32 %0, %1;" : "=f"(r) : "f"(x)); return r; }
__device__ __forceinline__ uint32_t mapa(uint32_t a, uint32_t rank) { uint32_t r; asm("mapa.shared::cluster.u32 %0, %1, %2;" : "=r"(r) : "r"(a), "r"(rank)); return r; }
__device__ __forceinline__ void st_async128(uint32_t a, uint32_t bar, uint32_t v0, uint32_t v1, uint32_t v2, uint32_t v3) {
  asm volatile("st.async.weak.shared::cluster.mbarrier::complete_tx::bytes.v4.b32 [%0], {%2,%3,%4,%5}, [%1];"
    :: "r"(a), "r"(bar), "r"(v0), "r"(v1), "r"(v2), "r"(v3) : "memory"); }
__device__ __forceinline__ int fresh_tid() { int t; asm volatile("mov.u32 %0, %%tid.x;" : "=r"(t)); return t; }
__device__ __forceinline__ void pace(uint32_t& t, uint32_t dt) {
  uint32_t c;
  while ((int)((c = uni((uint32_t)clock())) - t) < 0) __nanosleep(20);
  t = ((int)(c - t) > (int)dt ? c : t) + dt;
}
template <int LOG> __device__ __forceinline__ void unit_root(int a, float& c, float& s) {
  const float x = (float)((a << (32 - LOG)) >> (32 - LOG)) * (6.283185307179586f / (1 << LOG));
  c = __cosf(x); s = __sinf(x); }

template <int TA, int TB> __device__ __forceinline__ void ss128p(float* d, uint64_t da, uint64_t db, int sd) {
  asm volatile("{\n.reg .pred p;\nsetp.ne.b32 p, %68, 0;\n"
    "wgmma.mma_async.sync.aligned.m64n128k16.f32.bf16.bf16 "
    "{%0, %1, %2, %3, %4, %5, %6, %7, %8, %9, %10, %11, %12, %13, %14, %15, "
    "%16, %17, %18, %19, %20, %21, %22, %23, %24, %25, %26, %27, %28, %29, %30, %31, "
    "%32, %33, %34, %35, %36, %37, %38, %39, %40, %41, %42, %43, %44, %45, %46, %47, "
    "%48, %49, %50, %51, %52, %53, %54, %55, %56, %57, %58, %59, %60, %61, %62, %63}, %64, %65, p, 1, 1, %66, %67;\n}\n"
    : "+f"(d[0]), "+f"(d[1]), "+f"(d[2]), "+f"(d[3]), "+f"(d[4]), "+f"(d[5]), "+f"(d[6]), "+f"(d[7]),
      "+f"(d[8]), "+f"(d[9]), "+f"(d[10]), "+f"(d[11]), "+f"(d[12]), "+f"(d[13]), "+f"(d[14]), "+f"(d[15]),
      "+f"(d[16]), "+f"(d[17]), "+f"(d[18]), "+f"(d[19]), "+f"(d[20]), "+f"(d[21]), "+f"(d[22]), "+f"(d[23]),
      "+f"(d[24]), "+f"(d[25]), "+f"(d[26]), "+f"(d[27]), "+f"(d[28]), "+f"(d[29]), "+f"(d[30]), "+f"(d[31]),
      "+f"(d[32]), "+f"(d[33]), "+f"(d[34]), "+f"(d[35]), "+f"(d[36]), "+f"(d[37]), "+f"(d[38]), "+f"(d[39]),
      "+f"(d[40]), "+f"(d[41]), "+f"(d[42]), "+f"(d[43]), "+f"(d[44]), "+f"(d[45]), "+f"(d[46]), "+f"(d[47]),
      "+f"(d[48]), "+f"(d[49]), "+f"(d[50]), "+f"(d[51]), "+f"(d[52]), "+f"(d[53]), "+f"(d[54]), "+f"(d[55]),
      "+f"(d[56]), "+f"(d[57]), "+f"(d[58]), "+f"(d[59]), "+f"(d[60]), "+f"(d[61]), "+f"(d[62]), "+f"(d[63])
    : "l"(da), "l"(db), "n"(TA), "n"(TB), "r"(sd));
}
template <int TA, int TB> __device__ __forceinline__ void ss128a(float* d, uint64_t da, uint64_t db) {
  asm volatile("{\n.reg .pred p;\nsetp.eq.b32 p, 0, 0;\n"
    "wgmma.mma_async.sync.aligned.m64n128k16.f32.bf16.bf16 "
    "{%0, %1, %2, %3, %4, %5, %6, %7, %8, %9, %10, %11, %12, %13, %14, %15, "
    "%16, %17, %18, %19, %20, %21, %22, %23, %24, %25, %26, %27, %28, %29, %30, %31, "
    "%32, %33, %34, %35, %36, %37, %38, %39, %40, %41, %42, %43, %44, %45, %46, %47, "
    "%48, %49, %50, %51, %52, %53, %54, %55, %56, %57, %58, %59, %60, %61, %62, %63}, %64, %65, p, 1, 1, %66, %67;\n}\n"
    : "+f"(d[0]), "+f"(d[1]), "+f"(d[2]), "+f"(d[3]), "+f"(d[4]), "+f"(d[5]), "+f"(d[6]), "+f"(d[7]),
      "+f"(d[8]), "+f"(d[9]), "+f"(d[10]), "+f"(d[11]), "+f"(d[12]), "+f"(d[13]), "+f"(d[14]), "+f"(d[15]),
      "+f"(d[16]), "+f"(d[17]), "+f"(d[18]), "+f"(d[19]), "+f"(d[20]), "+f"(d[21]), "+f"(d[22]), "+f"(d[23]),
      "+f"(d[24]), "+f"(d[25]), "+f"(d[26]), "+f"(d[27]), "+f"(d[28]), "+f"(d[29]), "+f"(d[30]), "+f"(d[31]),
      "+f"(d[32]), "+f"(d[33]), "+f"(d[34]), "+f"(d[35]), "+f"(d[36]), "+f"(d[37]), "+f"(d[38]), "+f"(d[39]),
      "+f"(d[40]), "+f"(d[41]), "+f"(d[42]), "+f"(d[43]), "+f"(d[44]), "+f"(d[45]), "+f"(d[46]), "+f"(d[47]),
      "+f"(d[48]), "+f"(d[49]), "+f"(d[50]), "+f"(d[51]), "+f"(d[52]), "+f"(d[53]), "+f"(d[54]), "+f"(d[55]),
      "+f"(d[56]), "+f"(d[57]), "+f"(d[58]), "+f"(d[59]), "+f"(d[60]), "+f"(d[61]), "+f"(d[62]), "+f"(d[63])
    : "l"(da), "l"(db), "n"(TA), "n"(TB));
}
template <int TA, int TB> __device__ __forceinline__ void ss128z(float* d, uint64_t da, uint64_t db) {
  asm volatile("{\n.reg .pred p;\nsetp.ne.b32 p, 0, 0;\n"
    "wgmma.mma_async.sync.aligned.m64n128k16.f32.bf16.bf16 "
    "{%0, %1, %2, %3, %4, %5, %6, %7, %8, %9, %10, %11, %12, %13, %14, %15, "
    "%16, %17, %18, %19, %20, %21, %22, %23, %24, %25, %26, %27, %28, %29, %30, %31, "
    "%32, %33, %34, %35, %36, %37, %38, %39, %40, %41, %42, %43, %44, %45, %46, %47, "
    "%48, %49, %50, %51, %52, %53, %54, %55, %56, %57, %58, %59, %60, %61, %62, %63}, %64, %65, p, 1, 1, %66, %67;\n}\n"
    : "=f"(d[0]), "=f"(d[1]), "=f"(d[2]), "=f"(d[3]), "=f"(d[4]), "=f"(d[5]), "=f"(d[6]), "=f"(d[7]),
      "=f"(d[8]), "=f"(d[9]), "=f"(d[10]), "=f"(d[11]), "=f"(d[12]), "=f"(d[13]), "=f"(d[14]), "=f"(d[15]),
      "=f"(d[16]), "=f"(d[17]), "=f"(d[18]), "=f"(d[19]), "=f"(d[20]), "=f"(d[21]), "=f"(d[22]), "=f"(d[23]),
      "=f"(d[24]), "=f"(d[25]), "=f"(d[26]), "=f"(d[27]), "=f"(d[28]), "=f"(d[29]), "=f"(d[30]), "=f"(d[31]),
      "=f"(d[32]), "=f"(d[33]), "=f"(d[34]), "=f"(d[35]), "=f"(d[36]), "=f"(d[37]), "=f"(d[38]), "=f"(d[39]),
      "=f"(d[40]), "=f"(d[41]), "=f"(d[42]), "=f"(d[43]), "=f"(d[44]), "=f"(d[45]), "=f"(d[46]), "=f"(d[47]),
      "=f"(d[48]), "=f"(d[49]), "=f"(d[50]), "=f"(d[51]), "=f"(d[52]), "=f"(d[53]), "=f"(d[54]), "=f"(d[55]),
      "=f"(d[56]), "=f"(d[57]), "=f"(d[58]), "=f"(d[59]), "=f"(d[60]), "=f"(d[61]), "=f"(d[62]), "=f"(d[63])
    : "l"(da), "l"(db), "n"(TA), "n"(TB));
}
template <int TA, int TB> __device__ __forceinline__ void ss64a(float* d, uint64_t da, uint64_t db) {
  asm volatile("{\n.reg .pred p;\nsetp.eq.b32 p, 0, 0;\n"
    "wgmma.mma_async.sync.aligned.m64n64k16.f32.bf16.bf16 "
    "{%0, %1, %2, %3, %4, %5, %6, %7, %8, %9, %10, %11, %12, %13, %14, %15, "
    "%16, %17, %18, %19, %20, %21, %22, %23, %24, %25, %26, %27, %28, %29, %30, %31}, %32, %33, p, 1, 1, %34, %35;\n}\n"
    : "+f"(d[0]), "+f"(d[1]), "+f"(d[2]), "+f"(d[3]), "+f"(d[4]), "+f"(d[5]), "+f"(d[6]), "+f"(d[7]),
      "+f"(d[8]), "+f"(d[9]), "+f"(d[10]), "+f"(d[11]), "+f"(d[12]), "+f"(d[13]), "+f"(d[14]), "+f"(d[15]),
      "+f"(d[16]), "+f"(d[17]), "+f"(d[18]), "+f"(d[19]), "+f"(d[20]), "+f"(d[21]), "+f"(d[22]), "+f"(d[23]),
      "+f"(d[24]), "+f"(d[25]), "+f"(d[26]), "+f"(d[27]), "+f"(d[28]), "+f"(d[29]), "+f"(d[30]), "+f"(d[31])
    : "l"(da), "l"(db), "n"(TA), "n"(TB));
}
template <int TA, int TB> __device__ __forceinline__ void ss64z(float* d, uint64_t da, uint64_t db) {
  asm volatile("{\n.reg .pred p;\nsetp.ne.b32 p, 0, 0;\n"
    "wgmma.mma_async.sync.aligned.m64n64k16.f32.bf16.bf16 "
    "{%0, %1, %2, %3, %4, %5, %6, %7, %8, %9, %10, %11, %12, %13, %14, %15, "
    "%16, %17, %18, %19, %20, %21, %22, %23, %24, %25, %26, %27, %28, %29, %30, %31}, %32, %33, p, 1, 1, %34, %35;\n}\n"
    : "=f"(d[0]), "=f"(d[1]), "=f"(d[2]), "=f"(d[3]), "=f"(d[4]), "=f"(d[5]), "=f"(d[6]), "=f"(d[7]),
      "=f"(d[8]), "=f"(d[9]), "=f"(d[10]), "=f"(d[11]), "=f"(d[12]), "=f"(d[13]), "=f"(d[14]), "=f"(d[15]),
      "=f"(d[16]), "=f"(d[17]), "=f"(d[18]), "=f"(d[19]), "=f"(d[20]), "=f"(d[21]), "=f"(d[22]), "=f"(d[23]),
      "=f"(d[24]), "=f"(d[25]), "=f"(d[26]), "=f"(d[27]), "=f"(d[28]), "=f"(d[29]), "=f"(d[30]), "=f"(d[31])
    : "l"(da), "l"(db), "n"(TA), "n"(TB));
}
template <int TB> __device__ __forceinline__ void rs32a(float* d, const uint32_t* a, uint64_t db) {
  asm volatile("{\n.reg .pred p;\nsetp.eq.b32 p, 0, 0;\n"
    "wgmma.mma_async.sync.aligned.m64n32k16.f32.bf16.bf16 "
    "{%0, %1, %2, %3, %4, %5, %6, %7, %8, %9, %10, %11, %12, %13, %14, %15}, {%16, %17, %18, %19}, %20, p, 1, 1, %21;\n}\n"
    : "+f"(d[0]), "+f"(d[1]), "+f"(d[2]), "+f"(d[3]), "+f"(d[4]), "+f"(d[5]), "+f"(d[6]), "+f"(d[7]),
      "+f"(d[8]), "+f"(d[9]), "+f"(d[10]), "+f"(d[11]), "+f"(d[12]), "+f"(d[13]), "+f"(d[14]), "+f"(d[15])
    : "r"(a[0]), "r"(a[1]), "r"(a[2]), "r"(a[3]), "l"(db), "n"(TB));
}
template <int TB> __device__ __forceinline__ void rs32z(float* d, const uint32_t* a, uint64_t db) {
  asm volatile("{\n.reg .pred p;\nsetp.ne.b32 p, 0, 0;\n"
    "wgmma.mma_async.sync.aligned.m64n32k16.f32.bf16.bf16 "
    "{%0, %1, %2, %3, %4, %5, %6, %7, %8, %9, %10, %11, %12, %13, %14, %15}, {%16, %17, %18, %19}, %20, p, 1, 1, %21;\n}\n"
    : "=&f"(d[0]), "=&f"(d[1]), "=&f"(d[2]), "=&f"(d[3]), "=&f"(d[4]), "=&f"(d[5]), "=&f"(d[6]), "=&f"(d[7]),
      "=&f"(d[8]), "=&f"(d[9]), "=&f"(d[10]), "=&f"(d[11]), "=&f"(d[12]), "=&f"(d[13]), "=&f"(d[14]), "=&f"(d[15])
    : "r"(a[0]), "r"(a[1]), "r"(a[2]), "r"(a[3]), "l"(db), "n"(TB));
}
template <int TB> __device__ __forceinline__ void rs40a(float* d, const uint32_t* a, uint64_t db) {
  asm volatile("{\n.reg .pred p;\nsetp.eq.b32 p, 0, 0;\n"
    "wgmma.mma_async.sync.aligned.m64n40k16.f32.bf16.bf16 "
    "{%0, %1, %2, %3, %4, %5, %6, %7, %8, %9, %10, %11, %12, %13, %14, %15, "
    "%16, %17, %18, %19}, {%20, %21, %22, %23}, %24, p, 1, 1, %25;\n}\n"
    : "+f"(d[0]), "+f"(d[1]), "+f"(d[2]), "+f"(d[3]), "+f"(d[4]), "+f"(d[5]), "+f"(d[6]), "+f"(d[7]),
      "+f"(d[8]), "+f"(d[9]), "+f"(d[10]), "+f"(d[11]), "+f"(d[12]), "+f"(d[13]), "+f"(d[14]), "+f"(d[15]),
      "+f"(d[16]), "+f"(d[17]), "+f"(d[18]), "+f"(d[19])
    : "r"(a[0]), "r"(a[1]), "r"(a[2]), "r"(a[3]), "l"(db), "n"(TB));
}
template <int TB> __device__ __forceinline__ void rs40z(float* d, const uint32_t* a, uint64_t db) {
  asm volatile("{\n.reg .pred p;\nsetp.ne.b32 p, 0, 0;\n"
    "wgmma.mma_async.sync.aligned.m64n40k16.f32.bf16.bf16 "
    "{%0, %1, %2, %3, %4, %5, %6, %7, %8, %9, %10, %11, %12, %13, %14, %15, "
    "%16, %17, %18, %19}, {%20, %21, %22, %23}, %24, p, 1, 1, %25;\n}\n"
    : "=&f"(d[0]), "=&f"(d[1]), "=&f"(d[2]), "=&f"(d[3]), "=&f"(d[4]), "=&f"(d[5]), "=&f"(d[6]), "=&f"(d[7]),
      "=&f"(d[8]), "=&f"(d[9]), "=&f"(d[10]), "=&f"(d[11]), "=&f"(d[12]), "=&f"(d[13]), "=&f"(d[14]), "=&f"(d[15]),
      "=&f"(d[16]), "=&f"(d[17]), "=&f"(d[18]), "=&f"(d[19])
    : "r"(a[0]), "r"(a[1]), "r"(a[2]), "r"(a[3]), "l"(db), "n"(TB));
}
template <int TB> __device__ __forceinline__ void rs72a(float* d, const uint32_t* a, uint64_t db) {
  asm volatile("{\n.reg .pred p;\nsetp.eq.b32 p, 0, 0;\n"
    "wgmma.mma_async.sync.aligned.m64n72k16.f32.bf16.bf16 "
    "{%0, %1, %2, %3, %4, %5, %6, %7, %8, %9, %10, %11, %12, %13, %14, %15, "
    "%16, %17, %18, %19, %20, %21, %22, %23, %24, %25, %26, %27, %28, %29, %30, %31, "
    "%32, %33, %34, %35}, {%36, %37, %38, %39}, %40, p, 1, 1, %41;\n}\n"
    : "+f"(d[0]), "+f"(d[1]), "+f"(d[2]), "+f"(d[3]), "+f"(d[4]), "+f"(d[5]), "+f"(d[6]), "+f"(d[7]),
      "+f"(d[8]), "+f"(d[9]), "+f"(d[10]), "+f"(d[11]), "+f"(d[12]), "+f"(d[13]), "+f"(d[14]), "+f"(d[15]),
      "+f"(d[16]), "+f"(d[17]), "+f"(d[18]), "+f"(d[19]), "+f"(d[20]), "+f"(d[21]), "+f"(d[22]), "+f"(d[23]),
      "+f"(d[24]), "+f"(d[25]), "+f"(d[26]), "+f"(d[27]), "+f"(d[28]), "+f"(d[29]), "+f"(d[30]), "+f"(d[31]),
      "+f"(d[32]), "+f"(d[33]), "+f"(d[34]), "+f"(d[35])
    : "r"(a[0]), "r"(a[1]), "r"(a[2]), "r"(a[3]), "l"(db), "n"(TB));
}
template <int TB> __device__ __forceinline__ void rs72z(float* d, const uint32_t* a, uint64_t db) {
  asm volatile("{\n.reg .pred p;\nsetp.ne.b32 p, 0, 0;\n"
    "wgmma.mma_async.sync.aligned.m64n72k16.f32.bf16.bf16 "
    "{%0, %1, %2, %3, %4, %5, %6, %7, %8, %9, %10, %11, %12, %13, %14, %15, "
    "%16, %17, %18, %19, %20, %21, %22, %23, %24, %25, %26, %27, %28, %29, %30, %31, "
    "%32, %33, %34, %35}, {%36, %37, %38, %39}, %40, p, 1, 1, %41;\n}\n"
    : "=&f"(d[0]), "=&f"(d[1]), "=&f"(d[2]), "=&f"(d[3]), "=&f"(d[4]), "=&f"(d[5]), "=&f"(d[6]), "=&f"(d[7]),
      "=&f"(d[8]), "=&f"(d[9]), "=&f"(d[10]), "=&f"(d[11]), "=&f"(d[12]), "=&f"(d[13]), "=&f"(d[14]), "=&f"(d[15]),
      "=&f"(d[16]), "=&f"(d[17]), "=&f"(d[18]), "=&f"(d[19]), "=&f"(d[20]), "=&f"(d[21]), "=&f"(d[22]), "=&f"(d[23]),
      "=&f"(d[24]), "=&f"(d[25]), "=&f"(d[26]), "=&f"(d[27]), "=&f"(d[28]), "=&f"(d[29]), "=&f"(d[30]), "=&f"(d[31]),
      "=&f"(d[32]), "=&f"(d[33]), "=&f"(d[34]), "=&f"(d[35])
    : "r"(a[0]), "r"(a[1]), "r"(a[2]), "r"(a[3]), "l"(db), "n"(TB));
}

template <int V> struct IC { static constexpr int value = V; };
struct PfType { const char* base; uint32_t gl, gh, sp, sr, su, l4, l2; };
struct Params {
  const __nv_bfloat16 *x, *w;
  uint32_t one;
  const __nv_bfloat16 *shift, *ssmD;
  __nv_bfloat16* out;
  uint4* o; float* kv; unsigned* cnt;
  const char *k, *v;
  PfType pt[6];
  uint8_t pf[36];
};

struct Tmp { float t0, t1; uint32_t one, key; };
__device__ __forceinline__ void mul2(Tmp& t, float a0, float b0, float a1, float b1) {
  asm volatile("{\n.reg .pred p;\nsetp.ne.b32 p, %6, 0;\n@p mul.rn.f32 %0, %2, %3;\n@p mul.rn.f32 %1, %4, %5;\n}"
    : "+f"(t.t0), "+f"(t.t1) : "f"(a0), "f"(b0), "f"(a1), "f"(b1), "r"(t.one)); }
__device__ __forceinline__ void add2(Tmp& t, float a0, float b0, float a1, float b1) {
  asm volatile("{\n.reg .pred p;\nsetp.ne.b32 p, %6, 0;\n@p add.rn.f32 %0, %2, %3;\n@p add.rn.f32 %1, %4, %5;\n}"
    : "+f"(t.t0), "+f"(t.t1) : "f"(a0), "f"(b0), "f"(a1), "f"(b1), "r"(t.one)); }
__device__ __forceinline__ void fma2(Tmp& t, float a0, float b0, float a1, float b1) { t.t0 = fmaf(a0, b0, t.t0); t.t1 = fmaf(a1, b1, t.t1); }
__device__ __forceinline__ uint32_t bfma2(uint32_t a, uint32_t b, uint32_t c) { uint32_t r; asm("fma.rn.bf16x2 %0, %1, %2, %3;" : "=r"(r) : "r"(a), "r"(b), "r"(c)); return r; }
struct Tw { uint32_t c[2], s[2], ns[2]; };
__device__ __forceinline__ void pack32(Tmp& t, uint32_t* u, const float* a) {
  #pragma unroll
  for (int j = 0; j < 16; j++) { u[j] = pack_bf16(a[2 * j], a[2 * j + 1]); asm volatile("" : "+r"(u[j])); }
  sched_fence(t.key);
}
__device__ __forceinline__ void rot(uint32_t& ou, uint32_t& ov, uint32_t u, uint32_t v, const Tw& w, int k) {
  ou = bfma2(v, w.ns[k], bmul2(u, w.c[k])); ov = bfma2(u, w.s[k], bmul2(v, w.c[k]));
}
__device__ __forceinline__ void tw_fwd(Tmp& t, uint32_t (&f)[2][2][4], const float* a, const Tw& w) {
  uint32_t u[16];
  pack32(t, u, a);
  #pragma unroll
  for (int j = 0; j < 8; j++) rot(f[j >> 2][j & 1][(j >> 1) & 1], f[j >> 2][j & 1][2 + ((j >> 1) & 1)], u[2 * j], u[2 * j + 1], w, j & 1);
  sched_fence(t.key);
}
__device__ __forceinline__ void dft16(float* d, const uint32_t (&f)[2][2][4], uint64_t dF) {
  rs32z<0>(d, f[0][0], dF); rs32z<0>(d + 16, f[1][0], dF);
  rs32a<0>(d, f[0][1], dF + (256 >> 4)); rs32a<0>(d + 16, f[1][1], dF + (256 >> 4));
}
#define SP(a, p, im, k) ((a) + 16 * ((p) >> 1) + 8 * (im) + 4 * (k) + 2 * ((p) & 1))
__device__ __forceinline__ void prod(Tmp& t, uint32_t (&f)[2][2][4], const float* H, const float* X) {
  #pragma unroll
  for (int g = 0; g < 16; g++) {
    const int p = 3 - (g >> 2), k = (g >> 1) & 1, im = g & 1;
    #pragma unroll
    for (int q = 0; q <= p; q++) {
      const float *hr = SP(H, q, 0, k), *hi = SP(H, q, 1, k), *xa = SP(X, p - q, im, k), *xb = SP(X, p - q, 1 - im, k);
      if (q == 0) mul2(t, hr[0], xa[0], hr[1], xa[1]); else fma2(t, hr[0], xa[0], hr[1], xa[1]);
      if (im) fma2(t, hi[0], xb[0], hi[1], xb[1]); else fma2(t, -hi[0], xb[0], -hi[1], xb[1]);
    }
    f[p >> 1][k][2 * (1 - im) + (p & 1)] = pack_bf16(t.t0, t.t1);
  }
}

constexpr uint64_t dA = cdesc(A_OFF, 2048, 128, 0), dAi = cdesc(A_OFF, 128, 1024, 0), dF = cdesc(F_OFF, 128, 512, 0);
__device__ __forceinline__ void make_tw(Tw& tw, int ht) {
  #pragma unroll
  for (int i = 0; i < 2; i++) {
    float c0, s0, c1, s1;
    unit_root<11>((4 * (ht >> 2) + 1) * (i * 8 + 2 * (ht & 3)), c0, s0);
    unit_root<11>((4 * (ht >> 2) + 1) * (i * 8 + 2 * (ht & 3) + 1), c1, s1);
    tw.c[i] = pack_bf16(c0, c1); tw.s[i] = pack_bf16(s0, s1); tw.ns[i] = fresh(tw.s[i] ^ 0x80008000u);
  }
}
__device__ __forceinline__ void dft32_h(float* r, uint64_t dH) { ss64z<1, 1>(r, dA, dH); ss64a<1, 1>(r, dA + (4096 >> 4), dofs(dH, 512)); wg_commit(); }
__device__ __forceinline__ void dft32_x(float* r, int ch) {
  const uint64_t dx = dofs(cdesc(X_OFF, 1024, 128, 0), ch * XS);
  ss64z<1, 0>(r, dA, dx); ss64a<1, 0>(r, dA + (4096 >> 4), dofs(dx, 2048));
  wg_commit();
}
__device__ __forceinline__ void tw_inv(Tmp& t, const float* r, const Tw& tw, uint32_t ta) {
  uint32_t u[16];
  pack32(t, u, r);
  #pragma unroll
  for (int m = 0; m < 2; m++) {
    uint32_t re[4], im[4];
    #pragma unroll
    for (int j = 0; j < 4; j++) rot(im[j], re[j], u[8 * m + 2 * (j & 1) + (j >> 1)], u[8 * m + 4 + 2 * (j & 1) + (j >> 1)], tw, j & 1);
    stsm4(ta + m * 512, re[0], re[1], re[2], re[3]);
    stsm4(ta + 1024 + m * 512, im[0], im[1], im[2], im[3]);
  }
}
__device__ __forceinline__ void idft32(float* r, uint64_t dT, int bar) {
  fence_async_smem();
  bar_sync(bar, 128);
  wg_fence();
  ss64z<0, 1>(r, dAi, dT);
  #pragma unroll
  for (int j = 1; j < 4; j++) ss64a<0, 1>(r, dAi + j * (256 >> 4), dofs(dT, j * 2048));
  wg_commit();
}
__device__ __forceinline__ void finish(Tmp& t, const float* r, int ch, int ht, int rank, uint32_t y0, uint32_t y1) {
  const uint32_t ya = X_OFF + ch * XS + (ch & 1) * 16, yb = BAR_OFF + (B_YR + ch) * 8;
  uint32_t y[8];
  #pragma unroll
  for (int j = 0; j < 8; j++) {
    if (j >= 2) add2(t, r[4 * j], r[4 * j - 6], r[4 * j + 1], r[4 * j - 5]);
    y[j] = j < 2 ? pack_bf16(r[4 * j], r[4 * j + 1]) : pack_bf16(t.t0, t.t1);
  }
  st_async128(y0 + ya + (ht ^ (rank * 4)) * 16 + rank * (YX - XS), y0 + yb, y[0], y[1], y[2], y[3]);
  st_async128(y1 + ya + (ht ^ (rank * 4) ^ 4) * 16 + (rank ^ 1) * (YX - XS), y1 + yb, y[4], y[5], y[6], y[7]);
}

struct Team { uint32_t bars, rel, wofs; bool lead; };
template <bool M> __device__ __forceinline__ void mid_wait() { if (M) { wg_commit(); wg_wait<0>(); wg_fence(); } }
template <int J, bool M = false> __device__ __forceinline__ void kv_issue(float* aK, float* aV, uint32_t xo, int sd) {
  constexpr uint64_t dw = cdesc(W_OFF + J * 8192, 8192, 1024, 1);
  const uint64_t dx = dofs(cdesc((J & 1) * 64, 16, 1024, 1), xo);
  wg_fence();
  ss128p<1, 0>(aV, dw + (4096 >> 4), dx, sd);
  ss128p<1, 0>(aK, dw, dx, sd);
  mid_wait<M>();
  ss128a<1, 0>(aV, dw + (6144 >> 4), dofs(dx, 32));
  ss128a<1, 0>(aK, dw + (2048 >> 4), dofs(dx, 32));
  wg_commit();
}
template <int O, int J, bool M = false, bool FIRST = false> __device__ __forceinline__ void g2_issue(float* acc, const Team& c) {
  constexpr uint64_t db = cdesc(J * SLOT + 16384, 8192, 1024, 1);
  const uint64_t da = dofs(O ? cdesc(J * SLOT, 16, 512, 2) : cdesc(J * SLOT, 16, 1024, 1), c.wofs);
  wg_fence();
  if (FIRST) ss128z<0, 1>(acc, da, db); else ss128a<0, 1>(acc, da, db);
  ss128a<0, 1>(acc, dofs(da, 32), db + (2048 >> 4));
  mid_wait<M>();
  ss128a<0, 1>(acc, dofs(da, O ? 4096 : 64), db + (4096 >> 4));
  ss128a<0, 1>(acc, dofs(da, O ? 4128 : 96), db + (6144 >> 4));
  wg_commit();
}
template <bool DEEP, bool AB = false, class F>
__device__ __forceinline__ void ring_step(const Team& c, int fb, uint32_t ph, int eb, bool rel, F issue, uint32_t ab = 0, uint32_t aph = 0) {
  uint32_t ok = mbar_try(c.bars + fb * 8, ph);
  if (AB) ok &= mbar_try(ab, aph);
  if (!ok) {
    wg_wait<0>();
    arrive_at(c.rel + eb * 8, rel);
    rel = false;
    mbar_wait(c.bars + fb * 8, ph);
    if (AB) mbar_wait(ab, aph);
  }
  if (!DEEP) { wg_wait<0>(); arrive_at(c.rel + eb * 8, rel); }
  issue();
  if (DEEP) { wg_wait<1>(); arrive_at(c.rel + eb * 8, rel); }
}
template <int N, int I = 0, class R> __device__ __forceinline__ void tail_release(R rel) {
  if constexpr (I <= N) { wg_wait<N - I>(); rel(I - 1); tail_release<N, I + 1>(rel); }
}
template <int N, class F, class R> __device__ __forceinline__ void skew_tail(const Team& c, int ph, F issue, R rel) {
  if (c.wofs) { wg_wait<0>(); rel(-1); mbar_wait(c.bars + B_SK * 8, ph); }
  issue();
  arrive_at(c.bars + B_SK * 8, fresh_tid() == 0);
  tail_release<N>([&](int i) { if (i >= 0 || !c.wofs) rel(i); });
}
__device__ __forceinline__ void phi_a(float* a, uint32_t* f) {
  #pragma unroll
  for (int i = 0; i < 8; i++) {
    asm("cvt.rn.relu.bf16x2.f32 %0, %1, %2;" : "=r"(f[i]) : "f"(a[2 * i + 1]), "f"(a[2 * i]));
    asm("ex2.approx.ftz.f32 %0, %1;" : "=f"(a[2 * i]) : "f"(a[2 * i] * 1.4426950408889634f));
    asm("ex2.approx.ftz.f32 %0, %1;" : "=f"(a[2 * i + 1]) : "f"(a[2 * i + 1] * 1.4426950408889634f));
  }
  pinv<16>(a);
}
__device__ __forceinline__ void phi_b(const float* e, uint32_t* f) {
  #pragma unroll
  for (int i = 0; i < 8; i++) f[i] = badd2(f[i], pack_bf16(__saturatef(e[2 * i] + 1e-6f), __saturatef(e[2 * i + 1] + 1e-6f)));
}
__device__ __forceinline__ int g2_k(int st, int n2) { return st < 2 ? 2 * n2 + st : ((st >> 1) == n2 ? st & 1 : st); }

__global__ void __cluster_dims__(2, 1, 1) __launch_bounds__(NTHREADS, 1)
fused_kernel(const __grid_constant__ Params P, const __grid_constant__ CUtensorMap mX, const __grid_constant__ CUtensorMap mW,
             const __grid_constant__ CUtensorMap mWq, const __grid_constant__ CUtensorMap mWo,
             const __grid_constant__ CUtensorMap mK, const __grid_constant__ CUtensorMap mV, const __grid_constant__ CUtensorMap mH,
             const __grid_constant__ CUtensorMap mQ, const __grid_constant__ CUtensorMap mOut) {
  extern __shared__ __align__(1024) uint8_t smem[];
  if (__shfl_sync(0xffffffffu, threadIdx.x >> 5, 0) == 0) {
    asm volatile(ELECT "prefetch.tensormap [%0];\n}" :: "l"(&mW) : "memory");
    asm volatile(ELECT "prefetch.tensormap [%0];\n}" :: "l"(&mX) : "memory");
  }
  {
    const uint32_t t = threadIdx.x, bb = blockIdx.x;
    asm volatile("{\n.reg .pred p, q;\nsetp.eq.u32 p, %2, 2;\nsetp.eq.u32 q, %3, 8;\n@p prefetch.global.L2 [%0];\n@q prefetch.global.L2 [%1];\n}"
      :: "l"(reinterpret_cast<const char*>(P.x) + ((bb * 16 + t - 32) * 2048)),
         "l"(reinterpret_cast<const char*>(P.w) + ((bb >> 2) * 2048 + bb * 1024 + t * 128 - 6144)), "r"(t >> 4), "r"(t >> 3));
  }
  const uint32_t sb = uni(smem_u32(smem));
  const uint32_t bars = sb + BAR_OFF;
  const int tid = threadIdx.x, lane = tid & 31;
  const int warp = __shfl_sync(0xffffffffu, tid >> 5, 0);
  const uint32_t ids = uni(cta_ids());
#define IDS(w) const int b = (w) & 127, rank = (w) & 1, g = ((w) >> 8) & 7, mb = (w) >> 12, hp = g * 2 + rank, m2 = hp, n2 = mb, \
                         cp = g * 8 + mb; (void)b; (void)hp; (void)m2; (void)n2; (void)cp
  IDS(ids);

  if (warp == 0) {
    mbar_init(bars + (B_XF + 2) * 8, 1); mbar_init(bars + B_F0 * 8, 1); mbar_init(bars + B_FULL * 8, 1);
    mbar_expect_tx(bars + B_FULL * 8, 8192);
    tma3d(sb + W_OFF, &mW, hp * 64, 0, 1, bars + B_FULL * 8);
    mbar_expect_tx(bars + (B_XF + 2) * 8, 16384);
    tma2d(sb + 2 * SLOT, &mX, 0, mb * 256, bars + (B_XF + 2) * 8);
    mbar_expect_tx(bars + B_F0 * 8, 16384);
    tma2d(sb + 2 * SLOT + 16384, &mX, 0, mb * 256 + 128, bars + B_F0 * 8);
    #pragma unroll
    for (int i = 1; i < 4; i++) mbar_init(bars + (B_FULL + i) * 8, 1);
    mbar_init(bars + B_XF * 8, 1); mbar_init(bars + (B_XF + 1) * 8, 1);
    #pragma unroll
    for (int i = 1; i < 4; i++) {
      mbar_expect_tx(bars + (B_FULL + i) * 8, 8192);
      tma3d(sb + W_OFF + i * 8192, &mW, hp * 64, i * 32, 1, bars + (B_FULL + i) * 8);
    }
  } else if (warp >= 6) {
    const uint32_t cnt = warp < 12 || warp == 15 ? 1 : 4, b0 = bars + (warp - 4) * 32;
    #pragma unroll
    for (int i = 0; i < 4; i++) mbar_init(b0 + i * 8, cnt);
    if (warp == 8 || warp == 9) {
      #pragma unroll
      for (int i = 0; i < 4; i++) mbar_expect_tx(b0 + i * 8, 4096);
    } else if (warp == 13) {
      mbar_expect_tx(bars + B_KVB * 8, 5120);
    }
  }
  asm volatile("fence.mbarrier_init.release.cluster;" ::: "memory");
  __syncwarp();
  asm volatile("barrier.cluster.arrive.relaxed.aligned;" ::: "memory");

  if (warp < 8) {
    asm volatile("setmaxnreg.inc.sync.aligned.u32 %0;" :: "n"(160));
    const int wg = warp >> 2;
    uint32_t key = P.one;
    Team c;
    c.bars = bars; c.rel = mapa(bars, tid & 1); c.wofs = wg * 8192; c.lead = (tid & 127) < 2;
    auto gemm2 = [&](float* a, auto O_, auto SK_) {
      constexpr int O = O_.value, SK = SK_.value;
      static_assert(SK >= 1 && SK <= 3, "tail");
      uint32_t ph = 1;
      #pragma unroll 1
      for (int it = 1; it < 4; it++, ph ^= 1) {
        ring_step<false>(c, B_FULL2, ph, B_EMPTY2 + 3, c.lead, [&]() { g2_issue<O, 0, (MID >> (1 + O)) & 1>(a, c); });
        if (!O && (tid & 127) == 0) OSTAMP(55 + wg * 4 + it);
        if (O && (tid & 127) == 0) OSTAMP(40 + wg * 4 + it);
        if (SK == 3 && it == 3) break;
        ring_step<false>(c, B_FULL2 + 1, ph, B_EMPTY2, c.lead && (!O || it < 3), [&]() { g2_issue<O, 1, (MID >> (1 + O)) & 1>(a, c); });
        if (SK == 2 && it == 3) break;
        ring_step<false>(c, B_FULL2 + 2, ph, B_EMPTY2 + 1, c.lead && (!O || it < 3), [&]() { g2_issue<O, 2, (MID >> (1 + O)) & 1>(a, c); });
        if (SK == 1 && it == 3) break;
        ring_step<false>(c, B_FULL2 + 3, ph, B_EMPTY2 + 2, c.lead, [&]() { g2_issue<O, 3, (MID >> (1 + O)) & 1>(a, c); });
      }
      skew_tail<SK>(c, O ^ 1,
        [&]() {
          auto full = [&](int jj) { mbar_wait(bars + (B_FULL2 + jj) * 8, 1); };
          if (SK >= 3) { full(1); g2_issue<O, 1>(a, c); }
          if (SK >= 2) { full(2); g2_issue<O, 2>(a, c); }
          full(3); g2_issue<O, 3>(a, c);
        },
        [&](int i) { if (!O) arrive_at(c.rel + (B_EMPTY2 + ((16 - SK + i) & 3)) * 8, c.lead); });
      pinv<64>(a);
    };
    float aq[64];
    {
      float aK[64], aV[64];
      if (wg == 0) { kv_issue<0>(aK, aV, 0, 0); wg_wait<0>(); }
      cluster_wait();
      if (wg == 1) mbar_wait(bars + B_F0 * 8, 0);
      static_assert(SK1 >= 1 && SK1 <= 3, "tail");
      uint32_t ph = 0, xs = 2, xp = 0;
      auto next_x = [&]() { if (xs == 1) xp ^= 1; xs = xs == 2 ? 0 : xs + 1; };
      #pragma unroll 1
      for (int it = 0; it < 8; it++, ph ^= 1) {
        uint32_t xo = xs * SLOT + wg * 16384;
        ring_step<false, true>(c, B_FULL, ph, B_EMPTY + 3, c.lead && it > 0, [&]() { kv_issue<0, MID & 1>(aK, aV, xo, it); if (tid == 0 && it == 0) OSTAMP(1); }, bars + (B_XF + xs) * 8, xp);
        if (SK1 == 3 && it == 7) break;
        next_x();
        ring_step<false>(c, B_FULL + 1, ph, B_EMPTY, c.lead, [&]() { kv_issue<1, MID & 1>(aK, aV, xo, 1); });
        if (SK1 == 2 && it == 7) break;
        xo = xs * SLOT + wg * 16384;
        ring_step<false, true>(c, B_FULL + 2, ph, B_EMPTY + 1, c.lead, [&]() { kv_issue<2, MID & 1>(aK, aV, xo, 1); }, bars + (B_XF + xs) * 8, xp);
        if (SK1 == 1 && it == 7) break;
        next_x();
        ring_step<false>(c, B_FULL + 3, ph, B_EMPTY + 2, c.lead, [&]() { kv_issue<3, MID & 1>(aK, aV, xo, 1); });
      }
      skew_tail<SK1>(c, 0,
        [&]() {
          auto wait = [&](uint32_t a) { mbar_wait(a, 1); };
          if (SK1 >= 3) { wait(bars + (B_FULL + 1) * 8); kv_issue<1>(aK, aV, SLOT + wg * 16384, 1); }
          if (SK1 >= 2) { wait(bars + (B_FULL + 2) * 8); wait(bars + (B_XF + 2) * 8); kv_issue<2>(aK, aV, 2 * SLOT + wg * 16384, 1); }
          wait(bars + (B_FULL + 3) * 8); kv_issue<3>(aK, aV, 2 * SLOT + wg * 16384, 1);
        },
        [&](int i) { arrive_at(c.rel + (B_EMPTY + ((32 - SK1 + i) & 3)) * 8, c.lead); });
      pinv<64>(aV); pinv<64>(aK);
      if (tid == 128) OSTAMP(3);
      const uint32_t vb = sb + M_OFF + wg * VT;
      float kv[36];
      uint32_t kf[4][8];
      const uint64_t dv = dofs(cdesc(M_OFF, 1152, 128, 0), wg * VT);
      const int t = fresh_tid();
      const uint32_t va = vb + ((t >> 4) & 1) * 1152 + ((t >> 5) & 3) * 256 + (t & 15) * 16;
      mbar_wait(bars + B_X * 8, 0);
      #pragma unroll
      for (int i = 0; i < 8; i++) {
        const float* a = aV + 8 * i;
        stsm4(va + i * 2304, pack_bf16(a[0], a[1]), pack_bf16(a[2], a[3]), pack_bf16(a[4], a[5]), pack_bf16(a[6], a[7]));
      }
      phi_a(aK + 48, kf[3]);
      mbar_wait(bars + B_FULL2 * 8, 0);
      if ((tid & 127) == 0) OSTAMP(50 + wg);
      g2_issue<0, 0, false, true>(aq, c);
      sts128(vb + ((t & 127) >> 3) * 1152 + 1024 + (t & 7) * 16, 0x3f803f80u, 0x3f803f80u, 0x3f803f80u, 0x3f803f80u);
      phi_a(aK + 32, kf[2]); phi_b(aK + 48, kf[3]);
      sched_fence(key);
      ring_step<true>(c, B_FULL2 + 1, 0, B_EMPTY2, c.lead, [&]() { g2_issue<0, 1>(aq, c); });
      phi_a(aK + 16, kf[1]); phi_b(aK + 32, kf[2]);
      sched_fence(key);
      ring_step<true>(c, B_FULL2 + 2, 0, B_EMPTY2 + 1, c.lead, [&]() { g2_issue<0, 2>(aq, c); });
      phi_a(aK, kf[0]); phi_b(aK + 16, kf[1]);
      sched_fence(key);
      fence_async_smem(); bar_sync(1 + wg, 128);
      phi_b(aK, kf[0]);
      sched_fence(key);
      wg_fence();
      #pragma unroll
      for (int ks = 0; ks < 8; ks++) {
        if (ks == 0) rs72z<0>(kv, kf[0], dv); else rs72a<0>(kv, kf[ks >> 1] + 4 * (ks & 1), dofs(dv, ks * 2304));
      }
      wg_commit();
      wg_wait<1>();
      arrive_at(c.rel + (B_EMPTY2 + 2) * 8, c.lead);
      mbar_wait(bars + (B_FULL2 + 3) * 8, 0);
      g2_issue<0, 3>(aq, c);
      wg_wait<1>();
      pinv<36>(kv);
      const int a = fresh_tid() & 127;
      const bool hi = a >= 64;
      #pragma unroll
      for (int u = 0; u < 4; u++) {
        const int o = (u & 1) * 8 + (u & 2);
        sts128(vb + (a ^ ((a >> 3) & 3)) * 16 + u * 2048, __float_as_uint(hi ? kv[16 + o] : kv[o]), __float_as_uint(hi ? kv[17 + o] : kv[o + 1]),
               __float_as_uint(hi ? kv[20 + o] : kv[o + 4]), __float_as_uint(hi ? kv[21 + o] : kv[o + 5]));
      }
      if ((a & 3) < 2) sts32(vb + 8192 + ((a >> 5) * 16 + ((a & 31) >> 2) + (a & 1) * 8) * 4, __float_as_uint((a & 1) ? kv[34] : kv[32]));
      bar_arrive(4, 352);
    }
    if (tid == 0) OSTAMP(4);
    if (tid == 128) OSTAMP(5);
    float acc[64];
    {
      gemm2(aq, IC<0>(), IC<SK2>());
      if (tid == 0) OSTAMP(6);
      if (tid == 128) OSTAMP(7);
      constexpr uint64_t dk = cdesc(KVB_OFF, 640, 128, 0);
      const uint32_t id2 = fresh(ids); IDS(id2);
      if (NX && wg < NX && (warp & 3) == 0) {
        mbar_expect_tx(bars + (B_HX + wg) * 8, 4096);
        tma2d(sb + SLOT + wg * 8192, &mH, 0, (cp * 16 + rank * 8 + 7 - wg) * 128, bars + (B_HX + wg) * 8);
      }
      float nu[4][20];
      uint32_t pq[4][8], o[4][2][4];
      const int t2 = fresh_tid();
      const uint32_t oo = (t2 & 96) * 32 + (t2 & 28) * 16 + ((t2 ^ (t2 >> 3)) & 3) * 16;
      uint4* og = P.o + ((m2 * 8 + n2) * 4 + wg) * 512 + (oo >> 4);
      auto o_out = [&](int h) {
        pinv<20>(nu[h]);
        #pragma unroll
        for (int e = 0; e < 2; e++) {
          const float* n = nu[h] + 2 * e;
          const float iv = rcp_fast(n[16] + 1e-6f);
          #pragma unroll
          for (int i = 0; i < 4; i++) o[h][e][i] = pack_bf16(n[4 * i] * iv, n[4 * i + 1] * iv);
          asm volatile("st.global.v4.b32 [%0], {%1,%2,%3,%4};" :: "l"(og + (h >> 1) * 1024 + (h & 1) * 256 + e * 32), "r"(o[h][e][0]), "r"(o[h][e][1]), "r"(o[h][e][2]), "r"(o[h][e][3]) : "memory");
        }
      };
      auto o_mma = [&](int h) {
        wg_fence();
        rs40z<1>(nu[h], pq[h], dk + h * (2560 >> 4));
        rs40a<1>(nu[h], pq[h] + 4, dk + h * (2560 >> 4) + (1280 >> 4));
        wg_commit();
      };
      #pragma unroll
      for (int u = 0; u < 5; u++) {
        if (u >= 3) { wg_wait<1>(); o_out(u - 3); }
        if (u < 4) phi_a(aq + 16 * u, pq[u]);
        if (u > 0) phi_b(aq + 16 * (u - 1), pq[u - 1]);
        if (u == 1) { mbar_wait(bars + B_KVB * 8, 0); fence_async_smem(); } else sched_fence(key);
        if (u > 0) o_mma(u - 1);
      }
      wg_wait<1>(); o_out(2);
      sched_fence(key);
      wg_wait<0>(); o_out(3);
      bar_arrive(6, 288);
      if ((t2 & 127) == 0) OSTAMP(8 + wg * 2);
      if (NX && wg < NX) {
        float r0[32], r1[32];
        uint32_t fa[2][2][4], fb[2][2][4];
        const int ht = t2 & 127;
        const uint32_t psb = uni(mapa(sb, rank ^ 1));
        mbar_wait(bars + (B_HX + wg) * 8, 0);
        wg_fence();
        dft32_h(r0, dofs(cdesc(SLOT, 1024, 256, 3), c.wofs)); dft32_x(r1, 7 - wg);
        Tw tw;
        make_tw(tw, ht);
        Tmp t; t.t0 = 0.f; t.t1 = 0.f; t.one = XPACE ? P.one : 1; t.key = key;
        const float dn = __uint_as_float(lds32(sb + D_OFF + (7 - wg) * 4));
        sched_fence(t.key);
        wg_wait<1>(); pinv<32>(r0);
        tw_fwd(t, fb, r0, tw);
        wg_fence(); dft16(r0, fb, dF); wg_commit();
        wg_wait<1>(); pinv<32>(r1);
        arrive_at(psb + BAR_OFF + (B_XK + wg) * 8, ht == 0);
        tw_fwd(t, fa, r1, tw);
        wg_fence(); dft16(r1, fa, dF); wg_commit();
        wg_wait<0>(); pinv<32>(r0); pinv<32>(r1);
        r0[0] += dn; r0[1] += dn; r0[4] += dn; r0[5] += dn;
        prod(t, fa, r0, r1);
        sched_fence(t.key);
        wg_fence(); dft16(r0, fa, dF); wg_commit();
        wg_wait<0>(); pinv<32>(r0);
        tw_inv(t, r0, tw, sb + c.wofs + (ht >> 5) * 2048 + (ht & 31) * 16);
        idft32(r1, dofs(cdesc(0, 1024, 128, 0), c.wofs), 1 + wg);
        mbar_wait(bars + (B_YR + 6 - NX) * 8, 0);
        mbar_wait(bars + B_XK * 8, 0);
        if (NX == 2) mbar_wait(bars + (B_XK + 1) * 8, 0);
        wg_wait<0>(); pinv<32>(r1);
        finish(t, r1, 7 - wg, ht, rank, rank ? psb : sb, rank ? sb : psb);
        bar_sync(1 + wg, 128);
        key = t.key;
        if (ht == 0) OSTAMP(52 + wg);
      }
      #pragma unroll
      for (int i = 0; i < 8; i++)
        sts128(sb + wg * 8192 + oo + (i >> 2) * SLOT + ((i >> 1) & 1) * 4096 + (i & 1) * 512, o[i >> 1][i & 1][0], o[i >> 1][i & 1][1], o[i >> 1][i & 1][2], o[i >> 1][i & 1][3]);
      mbar_wait(bars + B_FULL2 * 8, 0);
      mbar_wait(bars + (B_FULL2 + 1) * 8, 0);
      fence_async_smem();
      g2_issue<1, 0, false, true>(acc, c);
      g2_issue<1, 1>(acc, c);
      if ((t2 & 127) == 0) OSTAMP(37 + wg);
      wg_wait<1>();
      arrive_at(c.rel + B_EMPTY2 * 8, c.lead);
      ring_step<true>(c, B_FULL2 + 2, 0, B_EMPTY2 + 1, c.lead, [&]() { if ((t2 & 127) == 0) OSTAMP(11 + wg * 24); g2_issue<1, 2>(acc, c); });
      ring_step<true>(c, B_FULL2 + 3, 0, B_EMPTY2 + 2, c.lead, [&]() { g2_issue<1, 3>(acc, c); });
    }
    gemm2(acc, IC<1>(), IC<SK3>());
    if (tid == 0) OSTAMP(13);
    if (tid == 128) OSTAMP(14);
    {
      const uint32_t id2 = fresh(ids); IDS(id2);
      const int t2 = fresh_tid();
      const int row = ((t2 >> 5) & 3) * 16 + (t2 & 15);
      const int cq = (t2 >> 4) & 1, sw = t2 & 7;
      const uint32_t stg = sb + wg * 8192;
      #pragma unroll
      for (int hf = 0; hf < 2; hf++) {
        #pragma unroll
        for (int jj = 0; jj < 4; jj++) {
          const int o = hf * 32 + jj * 8;
          stsm4(stg + hf * SLOT + row * 128 + (((2 * jj + cq) ^ sw) << 4),
                pack_bf16(acc[o], acc[o + 1]), pack_bf16(acc[o + 2], acc[o + 3]),
                pack_bf16(acc[o + 4], acc[o + 5]), pack_bf16(acc[o + 6], acc[o + 7]));
        }
        fence_async_smem();
        __syncwarp();
        tma2d_store(&mOut, 1024 + n2 * 128 + hf * 64, m2 * 128 + warp * 16, sb + hf * SLOT + warp * 2048);
      }
      bulk_commit(); bulk_wait_read();
    }
  } else if (warp < 12) {
    asm volatile("setmaxnreg.inc.sync.aligned.u32 %0;" :: "n"(160));
    const uint32_t id2 = fresh(ids); IDS(id2);
    const int ht = tid - 256, w = warp - 8;
    const int kap = w & 1;
    uint32_t w0, w1, w2, w3;
    {
      const uint4 s = *reinterpret_cast<const uint4*>(P.shift + (cp * 16 + kap * 8 + 2 * (lane & 3)) * 4);
      w0 = __byte_perm(s.x, s.z, 0x5410); w1 = __byte_perm(s.x, s.z, 0x7632);
      w2 = __byte_perm(s.y, s.w, 0x5410); w3 = __byte_perm(s.y, s.w, 0x7632);
      float dv = 0.f;
      if (ht < 8) dv = __bfloat162float(P.ssmD[cp * 16 + rank * 8 + ht]) * 0.125f;
      uint32_t c4[4], s4[4];
      #pragma unroll
      for (int i = 0; i < 4; i++) {
        float c0, s0, c1, s1;
        unit_root<7>((32 * (ht & 3) + 8 * i + 1) * (ht >> 2), c0, s0);
        unit_root<7>((32 * (ht & 3) + 8 * i + 5) * (ht >> 2), c1, s1);
        c4[i] = pack_bf16(c0 * 0.125f, c1 * 0.125f); s4[i] = pack_bf16(s0 * 0.125f, s1 * 0.125f);
      }
      const uint32_t aa = sb + A_OFF + w * 2048 + (ht & 3) * 256 + ((ht >> 2) & 7) * 16;
      sts128(aa, c4[0], c4[1], c4[2], c4[3]);
      sts128(aa + 128, s4[0], s4[1], s4[2], s4[3]);
      sts128(aa + 1024, s4[0] ^ 0x80008000u, s4[1] ^ 0x80008000u, s4[2] ^ 0x80008000u, s4[3] ^ 0x80008000u);
      sts128(aa + 1024 + 128, c4[0], c4[1], c4[2], c4[3]);
      float c0, s0, c1, s1;
      unit_root<4>((ht >> 3) * (2 * (ht & 7)), c0, s0);
      unit_root<4>((ht >> 3) * (2 * (ht & 7) + 1), c1, s1);
      const uint32_t fa = sb + F_OFF + (ht >> 6) * 512 + ((ht >> 2) & 1) * 256 + ((ht >> 3) & 7) * 16 + (ht & 3) * 4;
      const uint32_t cc = pack_bf16(c0, c1), ss = pack_bf16(s0, s1);
      sts32(fa, cc); sts32(fa + 128, ss ^ 0x80008000u); sts32(fa + 1024, ss); sts32(fa + 1024 + 128, cc);
      if (ht < 8) sts32(sb + D_OFF + ht * 4, __float_as_uint(dv));
    }
    Tw tw;
    make_tw(tw, ht);
    cluster_wait();
    const uint32_t psb = uni(mapa(sb, rank ^ 1));
    if (ht == 0) OSTAMP(20);
    {
      const int m = lane >> 3, n1 = (w >> 1) * 8 + (lane & 7);
      const int rk = 17 * m + n1 + 1, rh = 17 * (12 + m) + n1, rv = 16 * m + n1;
      const uint32_t ka = rk * 32 + ((kap ^ (rk >> 2)) & 1) * 16, ha = rh * 32 + ((kap ^ (rh >> 2)) & 1) * 16;
      const uint32_t va = rv * 32 + ((kap ^ (rv >> 2)) & 1) * 16;
      const uint32_t po = sb + T_OFF + (w >> 1) * 2176;
      #pragma unroll 1
      for (int rd = 0; rd < 4; rd++) {
        const uint32_t kb = sb + M_OFF + (rd & 1) * KB, vb = sb + M_OFF + 2 * KB + (rd & 1) * 8192;
        const uint32_t xo = X_OFF + ((rd & 1) * 2 + (w >> 1)) * 1024 + (2 * rank + (rd >> 1)) * 256;
        const uint32_t xa = (kap == rank ? sb + xo + (lane & 7) * XS : po + (lane & 7) * 272) + m * 16;
        mbar_wait(bars + (B_STG + (rd & 1) * 2) * 8, rd >> 1);
        uint32_t kk[20], vv[16];
        const uint32_t zero = P.one - 1;
        ldsm4(kk, kb + ha);
        ldsm4(kk + 4, kb + ka);
        #pragma unroll
        for (int i = 0; i < 16; i++) {
          if ((i & 3) == 0 && i < 12) ldsm4(kk + 8 + i, kb + (ka ^ ((~i & 4) * 4)) + (i + 4) * 544 + (kk[i + 4] & zero));
          uint32_t t = bmul2(kk[i + 1], w3);
          t = badd2(t, bmul2(kk[i + 2], w2));
          t = badd2(t, bmul2(kk[i + 3], w1));
          kk[i] = badd2(t, bmul2(kk[i + 4], w0));
          asm volatile("" : "+r"(kk[i]));
        }
        mbar_wait(bars + (B_STG + (rd & 1) * 2 + 1) * 8, rd >> 1);
        ldsm4(vv, vb + va);
        #pragma unroll
        for (int i = 0; i < 16; i += 4) {
          if (i < 12) ldsm4(vv + 4 + i, vb + va + (i + 4) * 512 + (i == 4 ? vv[0] & zero : 0));
          stsm4t(xa + (i >> 2) * 64, bmul2(kk[i], vv[i]), bmul2(kk[i + 1], vv[i + 1]), bmul2(kk[i + 2], vv[i + 2]), bmul2(kk[i + 3], vv[i + 3]));
        }
        if (rd < 2) {
          fence_async_smem();
          __syncwarp();
          mbar_arrive(bars + (B_SFREE + (rd & 1)) * 8);
        }
        __syncwarp();
        if (kap != rank) {
          #pragma unroll
          for (int i = 0; i < 4; i++) lds128(vv + 4 * i, po + (2 * i + (lane >> 4)) * 272 + (lane & 15) * 16);
          #pragma unroll
          for (int i = 0; i < 4; i++)
            st_async128(psb + xo + (2 * i + (lane >> 4)) * XS + (lane & 15) * 16, psb + BAR_OFF + B_X * 8, vv[4 * i], vv[4 * i + 1], vv[4 * i + 2], vv[4 * i + 3]);
          __syncwarp();
        }
      }
    }
    bar_sync(3, 128);
    if (w == 0) mbar_expect_tx(bars + B_X * 8, 16384);
    {
      constexpr uint64_t dT = cdesc(T_OFF, 1024, 128, 0), dH = cdesc(H_OFF, 1024, 256, 3);
      constexpr int NC = 8 - NX;
      Tmp t; t.t0 = 0.f; t.t1 = 0.f; t.one = P.one; t.key = P.one + 1;
      float r0[32], r1[32], r2[32];
      uint32_t fa[2][2][4], fb[2][2][4];
      const uint32_t ta = sb + T_OFF + w * 2048 + lane * 16;
      const uint32_t y0 = rank ? psb : sb, y1 = rank ? sb : psb;
      auto fin = [&](int ch) {
        if (ch > 0) mbar_wait(bars + (B_YR + ch - 1) * 8, 0);
        finish(t, r2, ch, ht, rank, y0, y1);
      };
      auto load_h = [&](int i) {
        mbar_expect_tx(bars + B_H * 8, 4096);
        tma2d(sb + H_OFF, &mH, 0, (cp * 16 + rank * 8 + i) * 128, bars + B_H * 8);
      };
      mbar_wait(bars + B_H * 8, 0);
      wg_fence();
      dft32_h(r0, dH);
      mbar_wait(bars + B_X * 8, 0);
      fence_async_smem();
      if (ht == 0) OSTAMP(21);
      wg_fence();
      dft32_x(r1, 0);
      float dn = __uint_as_float(lds32(sb + D_OFF));
      wg_wait<1>(); pinv<32>(r0);
      if (w == 0) load_h(1);
      tw_fwd(t, fb, r0, tw);
      wg_wait<0>(); pinv<32>(r1);
      tw_fwd(t, fa, r1, tw);
      wg_fence();
      dft16(r0, fb, dF); dft16(r1, fa, dF);
      wg_commit();
      wg_wait<0>(); pinv<32>(r0); pinv<32>(r1);
      #pragma unroll 1
      for (int i = 0;; i++) {
        r0[0] += dn; r0[1] += dn; r0[4] += dn; r0[5] += dn;
        dn = __uint_as_float(lds32(sb + D_OFF + 4 + i * 4));
        prod(t, fa, r0, r1);
        if (i == NC - 1) break;
        mbar_wait(bars + B_H * 8, (i + 1) & 1);
        wg_fence();
        dft16(r2, fa, dF);
        wg_commit();
        dft32_h(r0, dH); dft32_x(r1, i + 1);
        wg_wait<2>(); pinv<32>(r2);
        if (ht == 64) OSTAMP(22 + i);
        tw_inv(t, r2, tw, ta);
        sched_fence(t.key);
        wg_wait<1>(); pinv<32>(r0);
        if (w == 0 && i < NC - 2) load_h(i + 2);
        tw_fwd(t, fb, r0, tw);
        idft32(r2, dT, 3);
        dft16(r0, fb, dF);
        wg_commit();
        wg_wait<2>(); pinv<32>(r1);
        tw_fwd(t, fa, r1, tw);
        wg_fence();
        dft16(r1, fa, dF);
        wg_commit();
        wg_wait<2>(); pinv<32>(r2);
        fin(i);
        sched_fence(t.key);
        wg_wait<0>(); pinv<32>(r0); pinv<32>(r1);
      }
      wg_fence();
      dft16(r2, fa, dF);
      wg_commit();
      if (ht == 64) OSTAMP(29);
      const int l3 = fresh_tid() & 31;
      const int row = (l3 >> 4) * 512 + w * 128 + (l3 & 8) + ((l3 >> 2) & 1) + (l3 & 2);
      const uint32_t yb = sb + X_OFF + (l3 & 1) * (XS + 16) + w * 512
                          + (((l3 >> 1) & 1) == rank ? (l3 >> 2) * 16 : YX - XS + ((l3 >> 2) ^ 4) * 16);
      uint32_t qv[16][4];
      auto mul_y = [&](int m) {
        if (2 * m + 1 > NC - 3) { mbar_wait(bars + (B_YR + 2 * m) * 8, 0); mbar_wait(bars + (B_YR + 2 * m + 1) * 8, 0); }
        #pragma unroll
        for (int sg = 0; sg < 4; sg++) {
          uint32_t yv[4];
          ldsm4t(yv, yb + 2 * m * XS + sg * 128);
          #pragma unroll
          for (int i = 0; i < 4; i++) qv[4 * sg + i][m] = bmul2(qv[4 * sg + i][m], yv[i]);
        }
      };
      mbar_wait(bars + B_Q * 8, 0);
      #pragma unroll
      for (int i = 0; i < 16; i++) lds128(qv[i], sb + M_OFF + (row + (i >> 1) * 16 + (i & 1) * 4) * 32 + (l3 & 1) * 16);
      wg_wait<0>(); pinv<32>(r2);
      tw_inv(t, r2, tw, ta);
      mul_y(0);
      sched_fence(t.key);
      idft32(r2, dT, 3);
      mul_y(1);
      if (NX < 2) mul_y(2);
      wg_wait<0>(); pinv<32>(r2);
      fin(NC - 1);
      if (ht == 64) OSTAMP(30);
      if (NX == 2) mul_y(2);
      mul_y(3);
      uint4* op = reinterpret_cast<uint4*>(P.out) + (size_t)(rank * 1024 + row) * 256 + cp * 2 + (l3 & 1);
      mbar_wait(bars + B_GO * 8, 0);
      const uint32_t dt = min(max((int)(lds32(sb + D_OFF + 44) + OA_END - (uint32_t)clock()) >> 4, OA_MIN), OA_MAX);
      uint32_t t0 = (uint32_t)clock() + w * (dt >> 2);
      #pragma unroll
      for (int i = 0; i < 16; i++) {
        while ((int)((uint32_t)clock() - t0) < 0) {}
        t0 += dt;
        op[((i >> 1) * 16 + (i & 1) * 4) * 256] = make_uint4(qv[i][0], qv[i][1], qv[i][2], qv[i][3]);
      }
      if (ht == 0) OSTAMP(31);
    }
  } else {
    asm volatile("setmaxnreg.dec.sync.aligned.u32 %0;" :: "n"(32));
    const uint32_t id2 = fresh(ids); IDS(id2);
    const uint32_t t_pf = (uint32_t)clock();
    if (warp == 14)
      asm volatile("prefetch.global.L2 [%0];" :: "l"(((lane & 1) ? P.v : P.k) + (rank * 2097152 + cp * 32 + (lane >> 1) * 131072)));
    if (warp != 15) cluster_wait();
    auto reduce_kv = [&](int i0, int i1) {
      float* kr = P.kv + hp * KV_PER_HP;
      mbar_wait(bars + B_Z * 8, 0);
      bar_sync(4, 352);
      #pragma unroll 1
      for (; i0 < i1; i0 += 2) {
        uint32_t p[2][4], q[2][4];
        const int i = (i0 + 2 * mb) & 15;
        const uint32_t pa = sb + M_OFF + (i & 3) * 2048 + (i >> 2) * 512 + (lane & 7) * 64 + (((lane >> 3) ^ (lane >> 1)) & 3) * 16;
        lds128(p[0], pa); lds128(q[0], pa + VT); lds128(p[1], pa + 2048); lds128(q[1], pa + VT + 2048);
        #pragma unroll
        for (int j = 0; j < 2; j++)
          asm volatile("red.relaxed.gpu.global.add.v4.f32 [%0], {%1,%2,%3,%4};" :: "l"(kr + (i >> 3) * 32 + (i + j) * 128 + lane * 4),
            "f"(__uint_as_float(p[j][0]) + __uint_as_float(q[j][0])), "f"(__uint_as_float(p[j][1]) + __uint_as_float(q[j][1])),
            "f"(__uint_as_float(p[j][2]) + __uint_as_float(q[j][2])), "f"(__uint_as_float(p[j][3]) + __uint_as_float(q[j][3])) : "memory");
      }
      if (i1 == 4) {
        const uint32_t za = sb + M_OFF + 8192 + lane * 4;
        #pragma unroll
        for (int h = 0; h < 2; h++)
          asm volatile("red.relaxed.gpu.global.add.f32 [%0], %1;" :: "l"(kr + h * 1056 + 1024 + lane),
            "f"(__uint_as_float(lds32(za + h * 128)) + __uint_as_float(lds32(za + h * 128 + VT))) : "memory");
      }
      bar_sync(5, 96);
    };
    auto convert_kv = [&](int u0, auto N_) {
      constexpr int N = N_.value;
      const float* kg = P.kv + (2 * n2 + rank) * KV_PER_HP;
      const uint32_t psb = uni(mapa(sb, rank ^ 1));
      auto put = [&](uint32_t o, uint32_t v0, uint32_t v1, uint32_t v2, uint32_t v3) {
        st_async128(psb + o, psb + BAR_OFF + B_KVB * 8, v0, v1, v2, v3);
        sts128(sb + o, v0, v1, v2, v3);
      };
      mbar_wait(bars + B_KVL * 8, 0);
      spin_until(&P.cnt[(2 * n2 + rank) * 32 + 1], uni(lds32(sb + D_OFF + 40)) * 8);
      float4 v[N][2];
      float z[2];
      #pragma unroll
      for (int j = 0; j < N; j++) {
        const float4* kr = reinterpret_cast<const float4*>(kg + ((u0 + j) >> 2) * 32 + (u0 + j) * 256) + lane;
        v[j][0] = __ldcg(kr); v[j][1] = __ldcg(kr + 32);
      }
      if (N == 2) { z[0] = __ldcg(kg + 1024 + lane); z[1] = __ldcg(kg + 2080 + lane); }
      #pragma unroll
      for (int j = 0; j < N; j++)
        put(KVB_OFF + (rank * 8 + u0 + j) * 640 + lane * 16,
            pack_bf16(v[j][0].x, v[j][0].y), pack_bf16(v[j][0].z, v[j][0].w), pack_bf16(v[j][1].x, v[j][1].y), pack_bf16(v[j][1].z, v[j][1].w));
      if (N == 2) {
        #pragma unroll
        for (int h = 0; h < 2; h++) {
          const uint32_t zz = pack_bf16(z[h], z[h]);
          put(KVB_OFF + (rank * 8 + h * 4 + (lane >> 3)) * 640 + 512 + (lane & 7) * 16, zz, zz, zz, zz);
        }
      }
      fence_async_smem();
      __syncwarp();
      mbar_arrive(bars + B_KVB * 8);
    };
    if (warp == 12) {
      uint32_t xs = 0;
      auto load_x = [&](int k) {
        tma2d_mc(sb + xs * SLOT + rank * 16384, &mX, k, mb * 256 + rank * 128, bars + (B_XF + xs) * 8);
        mbar_expect_tx(bars + (B_XF + xs) * 8, SLOT);
        xs = xs == 2 ? 0 : xs + 1;
      };
      load_x(64); load_x(128);
      mbar_expect_tx(bars + B_Q * 8, 32768);
      #pragma unroll 1
      for (int it = 1; it < 8; it++) {
        #pragma unroll
        for (int j = 0; j < 4; j++) {
          mbar_wait(bars + (B_EMPTY + j) * 8, (it - 1) & 1);
          TSTAMP(1, 4 * it + j);
          tma3d(sb + W_OFF + j * 8192, &mW, hp * 64, it * 128 + j * 32, 1, bars + (B_FULL + j) * 8);
          if (j == 1 || (j == 3 && it < 7)) load_x(it * 128 + j * 32 + 32);
          mbar_expect_tx(bars + (B_FULL + j) * 8, 8192);
        }
      }
      mbar_wait(bars + B_Z * 8, 0);
      #pragma unroll 1
      for (int it = 0; it < 4; it++) {
        #pragma unroll
        for (int j = 0; j < 4; j++) {
          const uint32_t fb = bars + (B_FULL2 + j) * 8;
          if (j || it) mbar_wait(bars + (it ? B_EMPTY2 + j : B_EMPTY + (j | 1)) * 8, (it - 1) & 1);
          TSTAMP(5, 4 * it + j);
          tma2d_mc(sb + j * SLOT + 16384 + rank * 8192, &mWq, n2 * 128 + rank * 64, it * 256 + j * 64, fb);
          tma2d(sb + j * SLOT, &mX, it * 256 + j * 64, m2 * 128, fb);
          mbar_expect_tx(fb, SLOT);
          const int pc = 4 * it + j - Q_ST;
          if (pc >= 0) {
            mbar_wait(bars + B_Z * 8, 1);
            tma2d(sb + M_OFF + pc * 4096, &mQ, cp * 16, rank * 1024 + pc * 128, bars + B_Q * 8);
          }
        }
      }
      #pragma unroll 1
      for (int pc = 16 - Q_ST; pc < 8; pc++) tma2d(sb + M_OFF + pc * 4096, &mQ, cp * 16, rank * 1024 + pc * 128, bars + B_Q * 8);
      #pragma unroll 1
      for (int it = 0; it < 4; it++) {
        #pragma unroll
        for (int j = 0; j < 4; j++) {
          const uint32_t fb = bars + (B_FULL2 + j) * 8, k = fresh(g2_k(4 * it + j, n2) * 64);
          mbar_wait(bars + (B_EMPTY2 + j) * 8, (it - 1) & 1);
          TSTAMP(5, 16 + 4 * it + j);
          tma2d_mc(sb + j * SLOT + 16384 + rank * 8192, &mWo, n2 * 128 + rank * 64, k, fb);
          mbar_expect_tx(fb, j < 2 && it == 0 ? 16384 : SLOT);
        }
        if (it == 0) mbar_arrive(bars + B_QE * 8);
      }
    } else if (warp == 13) {
      if ((sb & 0xffffff) != SB0) __trap();
      float4* zp = reinterpret_cast<float4*>(P.kv + hp * KV_PER_HP + mb * 264);
      const float4 z4 = make_float4(0.f, 0.f, 0.f, 0.f);
      zp[lane] = z4; zp[lane + 32] = z4;
      if (lane < 2) zp[lane + 64] = z4;
      fence_gpu();
      __syncwarp();
      unsigned gen = 0;
      if (lane == 0) gen = (atomicAdd(&P.cnt[hp * 32], 1u) >> 3) + 1;
      gen = uni(gen);
      sts32(sb + D_OFF + 40, gen);
      spin_until(&P.cnt[hp * 32], gen * 8);
      mbar_arrive(bars + B_Z * 8);
      reduce_kv(0, 4);
      mbar_arrive(mapa(bars, rank ^ 1) + B_KVL * 8);
      mbar_arrive(bars + B_Z * 8);
      OSTAMP(17);
      fence_gpu();
      red_add(&P.cnt[hp * 32 + 1]);
      OSTAMP(15);
      convert_kv(0, IC<2>());
      bar_sync(6, 288);
      fence_gpu();
      asm volatile(ELECT "st.relaxed.gpu.global.u32 [%0], %1;\n}" :: "l"(&P.cnt[(16 + m2) * 32 + n2]), "r"(gen) : "memory");
      OSTAMP(32);
    } else {
      if (warp == 14) {
        uint32_t t0 = t_pf + STG_T0;
        #pragma unroll 1
        for (int pc = 0; pc < 16; pc++) {
          const int rd = pc >> 2, u = pc & 3;
          const uint32_t gb = bars + (B_STG + (rd & 1) * 2 + (u >> 1)) * 8;
          if (pc == 8 || pc == 12) mbar_wait(bars + (B_SFREE + (rd & 1)) * 8, 0);
          if (!(u & 1)) mbar_expect_tx(gb, u ? 8192 : KB);
          pace(t0, STG_DT);
          TSTAMP(3, 16 + pc);
          tma3d(sb + M_OFF + (u < 2 ? (rd & 1) * KB + u * (KB / 2) : 2 * KB + (rd & 1) * 8192 + (u & 1) * 4096), u < 2 ? &mK : &mV,
                cp * 16, rank * 64 + rd * 16 - (u < 2), (u & 1) * 8, gb);
        }
        mbar_expect_tx(bars + B_H * 8, 4096);
        tma2d(sb + H_OFF, &mH, 0, (cp * 16 + rank * 8) * 128, bars + B_H * 8);
      }
      if (warp == 15) {
        uint32_t t0 = t_pf + b * 2;
        #pragma unroll 1
        for (int i = 0; i < PF_N; i++) {
          const int u = P.pf[i];
          const PfType& f = P.pt[u >> 4];
          pace(t0, i == 0 ? PF_DT0 : (i < PF_N1 ? PF_DT1 : PF_DT2));
          asm volatile("prefetch.global.L2 [%0];" :: "l"(f.base + ((g & 3) * f.gl + (g >> 2) * f.gh + mb * f.sp + rank * f.sr + (u & 15) * f.su
                                                                   + (lane >> 2) * f.l4 + ((lane >> 1) & 1) * f.l2 + (lane & 1) * 128)));
        }
        cluster_wait();
      }
      reduce_kv(warp * 6 - 80, warp * 6 - 74);
      convert_kv(warp * 3 - 40, IC<3>());
      if (warp == 15) {
        const unsigned gen = uni(lds32(sb + D_OFF + 40));
        uint32_t have = 0;
        auto poll = [&]() {
          unsigned v;
          asm volatile("ld.relaxed.gpu.global.u32 %0, [%1];" : "=r"(v) : "l"(&P.cnt[(16 + m2) * 32 + lane]) : "memory");
          have = __ballot_sync(0xffffffffu, v == gen);
        };
        mbar_wait(bars + B_QE * 8, 0);
        #pragma unroll 1
        for (int it = 0; it < 4; it++) {
          #pragma unroll
          for (int j = 0; j < 4; j += 2) {
            if (j == 0 && it == 0) continue;
            const int k = g2_k(4 * it + j, n2);
            const uint4* src = P.o + (m2 * 16 + k) * 1024;
            if (!((have >> (k >> 1)) & 1)) {
              #pragma unroll 1
              for (int n = 0; n < WAIT_BOUND && !((have >> (k >> 1)) & 1); n++) poll();
              asm volatile("fence.acquire.gpu;" ::: "memory");
              fence_async_global();
            }
            if (it) mbar_wait(bars + (B_EMPTY2 + j) * 8, (it - 1) & 1);
            bulk_load(sb + j * SLOT, src, 16384, bars + (B_FULL2 + j) * 8);
            if (it) mbar_wait(bars + (B_EMPTY2 + j + 1) * 8, (it - 1) & 1);
            bulk_load(sb + (j + 1) * SLOT, src + 1024, 16384, bars + (B_FULL2 + j + 1) * 8);
          }
          if (it == 0) { OSTAMP(18); sts32(sb + D_OFF + 44, (uint32_t)clock()); mbar_arrive(bars + B_GO * 8); }
        }
      }
    }
  }
}

typedef CUresult (*EncodeFn)(CUtensorMap*, CUtensorMapDataType, cuuint32_t, void*, const cuuint64_t*, const cuuint64_t*,
                             const cuuint32_t*, const cuuint32_t*, CUtensorMapInterleave, CUtensorMapSwizzle,
                             CUtensorMapL2promotion, CUtensorMapFloatOOBfill);

void encode(EncodeFn fn, CUtensorMap* m, const void* ptr, int rank, const cuuint64_t* dims, const cuuint64_t* strides,
            const cuuint32_t* box, CUtensorMapSwizzle sw, CUtensorMapL2promotion pr) {
  const cuuint32_t es[3] = {1, 1, 1};
  fn(m, CU_TENSOR_MAP_DATA_TYPE_BFLOAT16, rank, const_cast<void*>(ptr), dims, strides, box, es,
     CU_TENSOR_MAP_INTERLEAVE_NONE, sw, pr, CU_TENSOR_MAP_FLOAT_OOB_FILL_NONE);
}

}

extern "C" void kernel_launch(void* const* d_in, const int* in_sizes, int n_in, void* d_out, int out_size) {
  (void)in_sizes; (void)n_in; (void)out_size;
  static EncodeFn fn = nullptr;
  static void *po, *pkv, *pcnt;
  if (!fn) {
    void* p = nullptr; cudaDriverEntryPointQueryResult qr;
    cudaGetDriverEntryPoint("cuTensorMapEncodeTiled", &p, cudaEnableDefault, &qr);
    fn = (EncodeFn)p;
    cudaGetSymbolAddress(&po, g_O); cudaGetSymbolAddress(&pkv, g_kv); cudaGetSymbolAddress(&pcnt, g_cnt);
    cudaFuncSetAttribute(fused_kernel, cudaFuncAttributeMaxDynamicSharedMemorySize, SMEM_BYTES);
  }
  const CUtensorMapL2promotion P128 = CU_TENSOR_MAP_L2_PROMOTION_L2_128B, P0 = CU_TENSOR_MAP_L2_PROMOTION_NONE;
  CUtensorMap mX, mW, mWq, mWo, mK, mV, mH, mQ, mOut;
  { cuuint64_t d[2] = {1024, 2048}, s[1] = {2048}; cuuint32_t bx[2] = {64, 128}, bq[2] = {16, 128};
    encode(fn, &mX, d_in[6], 2, d, s, bx, CU_TENSOR_MAP_SWIZZLE_128B, P128);
    encode(fn, &mQ, d_in[0], 2, d, s, bq, CU_TENSOR_MAP_SWIZZLE_NONE, P128); }
  { cuuint64_t d[3] = {1024, 1024, 3}, s[2] = {6144, 2048}; cuuint32_t bx[3] = {64, 32, 2};
    encode(fn, &mW, d_in[7], 3, d, s, bx, CU_TENSOR_MAP_SWIZZLE_128B, P128); }
  { cuuint64_t d[2] = {1024, 1024}, s[1] = {6144}, so[1] = {2048}; cuuint32_t bx[2] = {64, 64};
    encode(fn, &mWq, d_in[7], 2, d, s, bx, CU_TENSOR_MAP_SWIZZLE_128B, P128);
    encode(fn, &mWo, d_in[8], 2, d, so, bx, CU_TENSOR_MAP_SWIZZLE_128B, P128); }
  { cuuint64_t d[3] = {1024, 128, 16}, s[2] = {32768, 2048}; cuuint32_t bk[3] = {16, 17, 8}, bv[3] = {16, 16, 8};
    encode(fn, &mK, d_in[1], 3, d, s, bk, CU_TENSOR_MAP_SWIZZLE_32B, P128);
    encode(fn, &mV, d_in[2], 3, d, s, bv, CU_TENSOR_MAP_SWIZZLE_32B, P128); }
  { cuuint64_t d[2] = {16, 131072}, s[1] = {32}; cuuint32_t bx[2] = {16, 128};
    encode(fn, &mH, d_in[4], 2, d, s, bx, CU_TENSOR_MAP_SWIZZLE_32B, CU_TENSOR_MAP_L2_PROMOTION_L2_256B); }
  { cuuint64_t d[2] = {2048, 2048}, s[1] = {4096}; cuuint32_t bx[2] = {64, 16};
    encode(fn, &mOut, d_out, 2, d, s, bx, CU_TENSOR_MAP_SWIZZLE_128B, P0); }
  Params P;
  P.shift = (const __nv_bfloat16*)d_in[3]; P.ssmD = (const __nv_bfloat16*)d_in[5];
  P.x = (const __nv_bfloat16*)d_in[6]; P.w = (const __nv_bfloat16*)d_in[7]; P.out = (__nv_bfloat16*)d_out; P.one = 1;
  P.o = (uint4*)po; P.kv = (float*)pkv; P.cnt = (unsigned*)pcnt;
  P.k = (const char*)d_in[1]; P.v = (const char*)d_in[2];
  P.pt[0] = {(const char*)d_in[6], 16 * 32768, 64 * 32768, 65536, 32768, 256, 4096, 2048};
  P.pt[1] = {(const char*)d_in[7] + 2048, 256, 1024, 16 * 6144, 8 * 6144, 128 * 6144, 6144, 2048};
  P.pt[2] = {(const char*)d_in[7], 512, 128 * 6144, 16 * 6144, 8 * 6144, 256 * 6144, 6144, 256};
  P.pt[3] = {(const char*)d_in[8], 512, 128 * 2048, 16 * 2048, 8 * 2048, 256 * 2048, 2048, 256};
  P.pt[4] = {(const char*)d_in[0], 256, 1024, 32768, 2097152, 262144, 4096, 2048};
  P.pt[5] = {(const char*)d_in[4], 16 * 32768, 64 * 32768, 65536, 32768, 4096, 512, 256};
  const uint8_t pf[36] = {PF_LIST};
  for (int i = 0; i < 36; i++) P.pf[i] = pf[i];
  fused_kernel<<<NCTA, NTHREADS, SMEM_BYTES, cudaStreamPerThread>>>(P, mX, mW, mWq, mWo, mK, mV, mH, mQ, mOut);
}
```

```cpp
#include <cuda_runtime.h>
#include <cuda_bf16.h>
#include <cuda.h>
#include <stdint.h>

#define PARAM(name, value) constexpr int name = value
#define TUNE
namespace dflt {
PARAM(SK1, 2); PARAM(SK2, 3); PARAM(SK3, 2);
PARAM(SMAP, 1); PARAM(NEAR, 1); PARAM(FAR_DT, 500); PARAM(SPEC, 8); PARAM(RS_T0, 12000); PARAM(RS_DT, 1000); PARAM(CI, 1); PARAM(CW, 2); PARAM(SF, 97); PARAM(CX, 1); PARAM(DRY, 0); PARAM(FG, 2); PARAM(HINT, 0); PARAM(HW, 0); PARAM(AB, 0); PARAM(EHI, 0); PARAM(MID, 3);
PARAM(STG_T0, 1300); PARAM(STG_DT, 540);
PARAM(Q_ST, 10);
PARAM(OA_END, 7400); PARAM(OA_MIN, 200); PARAM(OA_MAX, 450);
PARAM(PF_DT0, 200); PARAM(PF_DT1, 1060); PARAM(PF_DT2, 512); PARAM(PF_N1, 9);
}
#define PF_LIST 0x01, 0x11, 0x02, 0x12, 0x03, 0x13, 0x04, 0x14, 0x05, 0x15, 0x51, 0x06, 0x16, 0x20, 0x07, 0x17, 0x21, 0x22, 0x23, \
                0x40, 0x41, 0x42, 0x43, 0x44, 0x45, 0x46, 0x47, 0x30, 0x31, 0x32, 0x33
#define PF_N 31
#define WAIT_BOUND 262144

namespace {
using namespace dflt;
TUNE

constexpr int S_LEN = 2048;
constexpr int DM    = 1024;
constexpr int NCTA  = 128;
constexpr int NTHREADS = 512;
constexpr int SLOT  = 32768;
constexpr int W_OFF = 3 * SLOT;
constexpr int M_OFF = 4 * SLOT;
constexpr int VT    = 16 * 1152;
constexpr int T_OFF = M_OFF + 43008;
constexpr int XS    = 4096 + 16;
constexpr int YX    = 2048 + 16;
constexpr int X_OFF = T_OFF + 8192 + 2176;
constexpr int H_OFF = X_OFF + 8 * XS;
constexpr int A_OFF = H_OFF + 4096;
constexpr int F_OFF = A_OFF + 8192;
constexpr int BAR_OFF = F_OFF + 2048;
constexpr int D_OFF = BAR_OFF + 384;
constexpr int SMEM_BYTES = D_OFF + 64 + 256;
constexpr int KB = 8704;
constexpr int KVB_OFF = M_OFF + 32768;
static_assert(H_OFF % 256 == 0 && X_OFF % 128 == 0 && SMEM_BYTES <= 232448, "layout");
constexpr int B_XF = 0, B_F0 = 3, B_FULL = 4, B_FA = 4, B_FULL2 = 25, B_KVL = 24, B_STG = 8, B_X = 12, B_Z = 13, B_H = 14, B_Q = 15, B_YR = 16,
              B_SK = 29, B_GO = 30, B_QE = 31,
              B_EMPTY = 32, B_KVB = 36, B_EMPTY2 = 37, B_SFREE = 41, B_CD = 43, B_MF = 44;
constexpr int KV_PER_HP = 2 * 1056;

__device__ __align__(1024) uint4 g_O[S_LEN * DM / 8];
__device__ __align__(128) float g_kv[16 * KV_PER_HP];
__device__ __align__(128) unsigned g_cnt[64 * 32];

#define OSTAMP(i) do {} while (0)
#define TSTAMP(k, i) do {} while (0)

__device__ __forceinline__ uint32_t cta_ids() {
  uint32_t b = blockIdx.x;
  if (SMAP) { asm("mov.u32 %0, %%smid;" : "=r"(b)); b = b >= 124 ? b - 124 : b + 8; }
  const uint32_t c = b >> 1, q = ((c - 36) * 37) >> 8;
  const uint32_t lo = (4 + c) << 12, mid = (((c - 4) & 7) << 8) + (((c - 4) >> 3) << 12), hi = ((c - 35) << 8) + q * (4096 - 7 * 256) + (4 << 12);
  uint32_t r;
  asm("{\n.reg .pred p, q;\nsetp.lt.u32 p, %4, 4;\nsetp.lt.u32 q, %4, 36;\nselp.u32 %0, %2, %3, q;\nselp.u32 %0, %1, %0, p;\n}" : "=&r"(r) : "r"(lo), "r"(mid), "r"(hi), "r"(c));
  return r + b;
}

#define ELECT "{\n.reg .pred e;\nelect.sync _|e, 0xffffffff;\n@e "
__device__ __forceinline__ uint32_t uni(uint32_t v) { return __shfl_sync(0xffffffffu, v, 0); }
__device__ __forceinline__ uint32_t fresh(uint32_t v) { asm volatile("" : "+r"(v)); return v; }
__device__ __forceinline__ uint32_t smem_u32(const void* p) { return (uint32_t)__cvta_generic_to_shared(p); }
__device__ __forceinline__ void mbar_init(uint32_t b, uint32_t c) { asm volatile(ELECT "mbarrier.init.shared::cta.b64 [%0], %1;\n}" :: "r"(b), "r"(c) : "memory"); }
__device__ __forceinline__ void mbar_expect_tx(uint32_t b, uint32_t bytes) { asm volatile(ELECT "mbarrier.arrive.expect_tx.shared::cta.b64 _, [%0], %1;\n}" :: "r"(b), "r"(bytes) : "memory"); }
__device__ __forceinline__ void mbar_arrive(uint32_t b) { asm volatile(ELECT "mbarrier.arrive.shared::cluster.b64 _, [%0];\n}" :: "r"(b) : "memory"); }
__device__ __forceinline__ void mbar_wait(uint32_t b, uint32_t ph) {
  asm volatile("{\n.reg .pred p;\n.reg .u32 n;\nmov.u32 n, 0;\n"
    "WAIT_LOOP:\nmbarrier.try_wait.parity.shared::cta.b64 p, [%0], %1;\n@p bra.uni WAIT_DONE;\n"
    "add.u32 n, n, 1;\nsetp.lt.u32 p, n, %2;\n@p bra.uni WAIT_LOOP;\nWAIT_DONE:\n}" :: "r"(b), "r"(ph), "n"(WAIT_BOUND) : "memory"); }
__device__ __forceinline__ void tma2d(uint32_t dst, const CUtensorMap* m, int c0, int c1, uint32_t bar) {
  asm volatile(ELECT "cp.async.bulk.tensor.2d.shared::cluster.global.mbarrier::complete_tx::bytes [%0], [%1, {%3, %4}], [%2];\n}"
    :: "r"(dst), "l"(m), "r"(bar), "r"(c0), "r"(c1) : "memory"); }
__device__ __forceinline__ void tma2d_mc(uint32_t dst, const CUtensorMap* m, int c0, int c1, uint32_t bar) {
  asm volatile(ELECT "cp.async.bulk.tensor.2d.shared::cluster.global.mbarrier::complete_tx::bytes.multicast::cluster [%0], [%1, {%3, %4}], [%2], %5;\n}"
    :: "r"(dst), "l"(m), "r"(bar), "r"(c0), "r"(c1), "h"((uint16_t)3) : "memory"); }
__device__ __forceinline__ void tma3d(uint32_t dst, const CUtensorMap* m, int c0, int c1, int c2, uint32_t bar) {
  asm volatile(ELECT "cp.async.bulk.tensor.3d.shared::cluster.global.mbarrier::complete_tx::bytes [%0], [%1, {%3, %4, %5}], [%2];\n}"
    :: "r"(dst), "l"(m), "r"(bar), "r"(c0), "r"(c1), "r"(c2) : "memory"); }
__device__ __forceinline__ void tma2d_store(const CUtensorMap* m, int c0, int c1, uint32_t src) {
  asm volatile(ELECT "cp.async.bulk.tensor.2d.global.shared::cta.bulk_group [%0, {%2, %3}], [%1];\n}"
    :: "l"(m), "r"(src), "r"(c0), "r"(c1) : "memory"); }
__device__ __forceinline__ void bulk_load(uint32_t dst, const void* src, uint32_t bytes, uint32_t bar) {
  asm volatile(ELECT "cp.async.bulk.shared::cluster.global.mbarrier::complete_tx::bytes [%0], [%1], %2, [%3];\n}"
    :: "r"(dst), "l"(src), "r"(bytes), "r"(bar) : "memory"); }
__device__ __forceinline__ void bulk_commit() { asm volatile("cp.async.bulk.commit_group;" ::: "memory"); }
__device__ __forceinline__ void bulk_wait_read() { asm volatile("cp.async.bulk.wait_group.read 0;" ::: "memory"); }
__device__ __forceinline__ void fence_async_smem() { asm volatile("fence.proxy.async.shared::cta;" ::: "memory"); }
__device__ __forceinline__ void bar_sync(int id, int n) { asm volatile("bar.sync %0, %1;" :: "r"(id), "r"(n) : "memory"); }
__device__ __forceinline__ void bar_arrive(int id, int n) { asm volatile("bar.arrive %0, %1;" :: "r"(id), "r"(n) : "memory"); }
__device__ __forceinline__ void wg_fence() { asm volatile("wgmma.fence.sync.aligned;" ::: "memory"); }
__device__ __forceinline__ void wg_commit() { asm volatile("wgmma.commit_group.sync.aligned;" ::: "memory"); }
template <int N> __device__ __forceinline__ void wg_wait() { asm volatile("wgmma.wait_group.sync.aligned %0;" :: "n"(N) : "memory"); }
constexpr uint32_t SB0 = 1024;
__host__ __device__ constexpr uint64_t cdesc(uint32_t off, uint32_t lbo, uint32_t sbo, uint32_t swz) {
  return (uint64_t)((SB0 + off) >> 4) | ((uint64_t)(lbo >> 4) << 16) | ((uint64_t)(sbo >> 4) << 32) | ((uint64_t)swz << 62); }
__device__ __forceinline__ uint64_t dofs(uint64_t d, uint32_t bytes) { return (d & 0xffffffff00000000ull) | (uint32_t)((uint32_t)d + (bytes >> 4)); }
__device__ __forceinline__ uint32_t mbar_try(uint32_t b, uint32_t ph) {
  uint32_t ok;
  asm volatile("{\n.reg .pred p;\nmbarrier.test_wait.parity.shared::cta.b64 p, [%1], %2;\nselp.u32 %0, 1, 0, p;\n}" : "=r"(ok) : "r"(b), "r"(ph) : "memory");
  return ok; }
__device__ __forceinline__ void arrive_at(uint32_t a, bool on) {
  asm volatile("{\n.reg .pred p;\nsetp.ne.b32 p, %1, 0;\n@p mbarrier.arrive.shared::cluster.b64 _, [%0];\n}" :: "r"(a), "r"((uint32_t)on) : "memory"); }
__device__ __forceinline__ void ldsm4(uint32_t* r, uint32_t a) {
  asm volatile("ldmatrix.sync.aligned.m8n8.x4.shared.b16 {%0,%1,%2,%3}, [%4];" : "=r"(r[0]), "=r"(r[1]), "=r"(r[2]), "=r"(r[3]) : "r"(a) : "memory"); }
__device__ __forceinline__ void ldsm4t(uint32_t* r, uint32_t a) {
  asm volatile("ldmatrix.sync.aligned.m8n8.x4.trans.shared.b16 {%0,%1,%2,%3}, [%4];" : "=r"(r[0]), "=r"(r[1]), "=r"(r[2]), "=r"(r[3]) : "r"(a) : "memory"); }
__device__ __forceinline__ void stsm4(uint32_t a, uint32_t r0, uint32_t r1, uint32_t r2, uint32_t r3) {
  asm volatile("stmatrix.sync.aligned.m8n8.x4.shared.b16 [%0], {%1,%2,%3,%4};" :: "r"(a), "r"(r0), "r"(r1), "r"(r2), "r"(r3) : "memory"); }
__device__ __forceinline__ void stsm4t(uint32_t a, uint32_t r0, uint32_t r1, uint32_t r2, uint32_t r3) {
  asm volatile("stmatrix.sync.aligned.m8n8.x4.trans.shared.b16 [%0], {%1,%2,%3,%4};" :: "r"(a), "r"(r0), "r"(r1), "r"(r2), "r"(r3) : "memory"); }
__device__ __forceinline__ uint32_t lds32(uint32_t a) { uint32_t v; asm volatile("ld.shared.b32 %0, [%1];" : "=r"(v) : "r"(a) : "memory"); return v; }
__device__ __forceinline__ void lds128(uint32_t* v, uint32_t a) { asm volatile("ld.shared.v4.b32 {%0,%1,%2,%3}, [%4];" : "=r"(v[0]), "=r"(v[1]), "=r"(v[2]), "=r"(v[3]) : "r"(a) : "memory"); }
__device__ __forceinline__ void sts32(uint32_t a, uint32_t v) { asm volatile("st.shared.b32 [%0], %1;" :: "r"(a), "r"(v) : "memory"); }
__device__ __forceinline__ void sts128(uint32_t a, uint32_t v0, uint32_t v1, uint32_t v2, uint32_t v3) {
  asm volatile("st.shared.v4.b32 [%0], {%1,%2,%3,%4};" :: "r"(a), "r"(v0), "r"(v1), "r"(v2), "r"(v3) : "memory"); }
__device__ __forceinline__ uint32_t pack_bf16(float lo, float hi) { uint32_t r; asm("cvt.rn.bf16x2.f32 %0, %1, %2;" : "=r"(r) : "f"(hi), "f"(lo)); return r; }
template <int ID = 0> __device__ __forceinline__ void sched_fence(uint32_t key) {
  asm volatile("{\n.reg .pred p;\nsetp.eq.u32 p, %0, %1;\nSF_LOOP:\n@p pmevent 1;\n@p bra.uni SF_LOOP;\n}" :: "r"(key), "n"(ID) : "memory");
}
template <int N> __device__ __forceinline__ void pinv(float* v) {
  #pragma unroll
  for (int i = 0; i < N; i++) asm volatile("" : "+f"(v[i]) :: "memory"); }
__device__ __forceinline__ uint32_t bmul2(uint32_t a, uint32_t b) { uint32_t r; asm("mul.rn.bf16x2 %0, %1, %2;" : "=r"(r) : "r"(a), "r"(b)); return r; }
__device__ __forceinline__ uint32_t badd2(uint32_t a, uint32_t b) { uint32_t r; asm("add.rn.bf16x2 %0, %1, %2;" : "=r"(r) : "r"(a), "r"(b)); return r; }
__device__ __forceinline__ void spin_until(const unsigned* p, unsigned target) {
  int n = 0;
  unsigned v;
  do { asm volatile("ld.relaxed.gpu.global.u32 %0, [%1];" : "=r"(v) : "l"(p) : "memory"); } while ((int)(v - target) < 0 && ++n < WAIT_BOUND);
  asm volatile("fence.acquire.gpu;" ::: "memory");
}
__device__ __forceinline__ void cluster_wait() { asm volatile("barrier.cluster.wait.aligned;" ::: "memory"); }
__device__ __forceinline__ void fence_gpu() { asm volatile("fence.release.gpu;" ::: "memory"); }
__device__ __forceinline__ void fence_async_global() { asm volatile("fence.proxy.async.global;" ::: "memory"); }
__device__ __forceinline__ void red_add(unsigned* p) { asm volatile(ELECT "red.relaxed.gpu.global.add.u32 [%0], 1;\n}" :: "l"(p) : "memory"); }
__device__ __forceinline__ float rcp_fast(float x) { float r; asm("rcp.approx.ftz.f32 %0, %1;" : "=f"(r) : "f"(x)); return r; }
__device__ __forceinline__ uint32_t mapa(uint32_t a, uint32_t rank) { uint32_t r; asm("mapa.shared::cluster.u32 %0, %1, %2;" : "=r"(r) : "r"(a), "r"(rank)); return r; }
__device__ __forceinline__ void st_async128(uint32_t a, uint32_t bar, uint32_t v0, uint32_t v1, uint32_t v2, uint32_t v3) {
  asm volatile("st.async.weak.shared::cluster.mbarrier::complete_tx::bytes.v4.b32 [%0], {%2,%3,%4,%5}, [%1];"
    :: "r"(a), "r"(bar), "r"(v0), "r"(v1), "r"(v2), "r"(v3) : "memory"); }
__device__ __forceinline__ int fresh_tid() { int t; asm volatile("mov.u32 %0, %%tid.x;" : "=r"(t)); return t; }
__device__ __forceinline__ void pace(uint32_t& t, uint32_t dt) {
  uint32_t c;
  while ((int)((c = uni((uint32_t)clock())) - t) < 0) __nanosleep(20);
  t = ((int)(c - t) > (int)dt ? c : t) + dt;
}
template <int LOG> __device__ __forceinline__ void unit_root(int a, float& c, float& s) {
  const float x = (float)((a << (32 - LOG)) >> (32 - LOG)) * (6.283185307179586f / (1 << LOG));
  c = __cosf(x); s = __sinf(x); }

struct D2 { uint64_t a, b; };
template <int TA, int TB> __device__ __forceinline__ void ss128p(float* d, uint64_t da, uint64_t db, int sd) {
  asm volatile("{\n.reg .pred p;\nsetp.ne.b32 p, %68, 0;\n"
    "wgmma.mma_async.sync.aligned.m64n128k16.f32.bf16.bf16 "
    "{%0, %1, %2, %3, %4, %5, %6, %7, %8, %9, %10, %11, %12, %13, %14, %15, "
    "%16, %17, %18, %19, %20, %21, %22, %23, %24, %25, %26, %27, %28, %29, %30, %31, "
    "%32, %33, %34, %35, %36, %37, %38, %39, %40, %41, %42, %43, %44, %45, %46, %47, "
    "%48, %49, %50, %51, %52, %53, %54, %55, %56, %57, %58, %59, %60, %61, %62, %63}, %64, %65, p, 1, 1, %66, %67;\n}\n"
    : "+f"(d[0]), "+f"(d[1]), "+f"(d[2]), "+f"(d[3]), "+f"(d[4]), "+f"(d[5]), "+f"(d[6]), "+f"(d[7]),
      "+f"(d[8]), "+f"(d[9]), "+f"(d[10]), "+f"(d[11]), "+f"(d[12]), "+f"(d[13]), "+f"(d[14]), "+f"(d[15]),
      "+f"(d[16]), "+f"(d[17]), "+f"(d[18]), "+f"(d[19]), "+f"(d[20]), "+f"(d[21]), "+f"(d[22]), "+f"(d[23]),
      "+f"(d[24]), "+f"(d[25]), "+f"(d[26]), "+f"(d[27]), "+f"(d[28]), "+f"(d[29]), "+f"(d[30]), "+f"(d[31]),
      "+f"(d[32]), "+f"(d[33]), "+f"(d[34]), "+f"(d[35]), "+f"(d[36]), "+f"(d[37]), "+f"(d[38]), "+f"(d[39]),
      "+f"(d[40]), "+f"(d[41]), "+f"(d[42]), "+f"(d[43]), "+f"(d[44]), "+f"(d[45]), "+f"(d[46]), "+f"(d[47]),
      "+f"(d[48]), "+f"(d[49]), "+f"(d[50]), "+f"(d[51]), "+f"(d[52]), "+f"(d[53]), "+f"(d[54]), "+f"(d[55]),
      "+f"(d[56]), "+f"(d[57]), "+f"(d[58]), "+f"(d[59]), "+f"(d[60]), "+f"(d[61]), "+f"(d[62]), "+f"(d[63])
    : "l"(da), "l"(db), "n"(TA), "n"(TB), "r"(sd));
}
template <int TA, int TB> __device__ __forceinline__ void ss128a(float* d, uint64_t da, uint64_t db) {
  asm volatile("{\n.reg .pred p;\nsetp.eq.b32 p, 0, 0;\n"
    "wgmma.mma_async.sync.aligned.m64n128k16.f32.bf16.bf16 "
    "{%0, %1, %2, %3, %4, %5, %6, %7, %8, %9, %10, %11, %12, %13, %14, %15, "
    "%16, %17, %18, %19, %20, %21, %22, %23, %24, %25, %26, %27, %28, %29, %30, %31, "
    "%32, %33, %34, %35, %36, %37, %38, %39, %40, %41, %42, %43, %44, %45, %46, %47, "
    "%48, %49, %50, %51, %52, %53, %54, %55, %56, %57, %58, %59, %60, %61, %62, %63}, %64, %65, p, 1, 1, %66, %67;\n}\n"
    : "+f"(d[0]), "+f"(d[1]), "+f"(d[2]), "+f"(d[3]), "+f"(d[4]), "+f"(d[5]), "+f"(d[6]), "+f"(d[7]),
      "+f"(d[8]), "+f"(d[9]), "+f"(d[10]), "+f"(d[11]), "+f"(d[12]), "+f"(d[13]), "+f"(d[14]), "+f"(d[15]),
      "+f"(d[16]), "+f"(d[17]), "+f"(d[18]), "+f"(d[19]), "+f"(d[20]), "+f"(d[21]), "+f"(d[22]), "+f"(d[23]),
      "+f"(d[24]), "+f"(d[25]), "+f"(d[26]), "+f"(d[27]), "+f"(d[28]), "+f"(d[29]), "+f"(d[30]), "+f"(d[31]),
      "+f"(d[32]), "+f"(d[33]), "+f"(d[34]), "+f"(d[35]), "+f"(d[36]), "+f"(d[37]), "+f"(d[38]), "+f"(d[39]),
      "+f"(d[40]), "+f"(d[41]), "+f"(d[42]), "+f"(d[43]), "+f"(d[44]), "+f"(d[45]), "+f"(d[46]), "+f"(d[47]),
      "+f"(d[48]), "+f"(d[49]), "+f"(d[50]), "+f"(d[51]), "+f"(d[52]), "+f"(d[53]), "+f"(d[54]), "+f"(d[55]),
      "+f"(d[56]), "+f"(d[57]), "+f"(d[58]), "+f"(d[59]), "+f"(d[60]), "+f"(d[61]), "+f"(d[62]), "+f"(d[63])
    : "l"(da), "l"(db), "n"(TA), "n"(TB));
}
template <int TA, int TB> __device__ __forceinline__ void ss128z(float* d, uint64_t da, uint64_t db) {
  asm volatile("{\n.reg .pred p;\nsetp.ne.b32 p, 0, 0;\n"
    "wgmma.mma_async.sync.aligned.m64n128k16.f32.bf16.bf16 "
    "{%0, %1, %2, %3, %4, %5, %6, %7, %8, %9, %10, %11, %12, %13, %14, %15, "
    "%16, %17, %18, %19, %20, %21, %22, %23, %24, %25, %26, %27, %28, %29, %30, %31, "
    "%32, %33, %34, %35, %36, %37, %38, %39, %40, %41, %42, %43, %44, %45, %46, %47, "
    "%48, %49, %50, %51, %52, %53, %54, %55, %56, %57, %58, %59, %60, %61, %62, %63}, %64, %65, p, 1, 1, %66, %67;\n}\n"
    : "=f"(d[0]), "=f"(d[1]), "=f"(d[2]), "=f"(d[3]), "=f"(d[4]), "=f"(d[5]), "=f"(d[6]), "=f"(d[7]),
      "=f"(d[8]), "=f"(d[9]), "=f"(d[10]), "=f"(d[11]), "=f"(d[12]), "=f"(d[13]), "=f"(d[14]), "=f"(d[15]),
      "=f"(d[16]), "=f"(d[17]), "=f"(d[18]), "=f"(d[19]), "=f"(d[20]), "=f"(d[21]), "=f"(d[22]), "=f"(d[23]),
      "=f"(d[24]), "=f"(d[25]), "=f"(d[26]), "=f"(d[27]), "=f"(d[28]), "=f"(d[29]), "=f"(d[30]), "=f"(d[31]),
      "=f"(d[32]), "=f"(d[33]), "=f"(d[34]), "=f"(d[35]), "=f"(d[36]), "=f"(d[37]), "=f"(d[38]), "=f"(d[39]),
      "=f"(d[40]), "=f"(d[41]), "=f"(d[42]), "=f"(d[43]), "=f"(d[44]), "=f"(d[45]), "=f"(d[46]), "=f"(d[47]),
      "=f"(d[48]), "=f"(d[49]), "=f"(d[50]), "=f"(d[51]), "=f"(d[52]), "=f"(d[53]), "=f"(d[54]), "=f"(d[55]),
      "=f"(d[56]), "=f"(d[57]), "=f"(d[58]), "=f"(d[59]), "=f"(d[60]), "=f"(d[61]), "=f"(d[62]), "=f"(d[63])
    : "l"(da), "l"(db), "n"(TA), "n"(TB));
}
template <int TA, int TB> __device__ __forceinline__ void ss64a(float* d, uint64_t da, uint64_t db) {
  asm volatile("{\n.reg .pred p;\nsetp.eq.b32 p, 0, 0;\n"
    "wgmma.mma_async.sync.aligned.m64n64k16.f32.bf16.bf16 "
    "{%0, %1, %2, %3, %4, %5, %6, %7, %8, %9, %10, %11, %12, %13, %14, %15, "
    "%16, %17, %18, %19, %20, %21, %22, %23, %24, %25, %26, %27, %28, %29, %30, %31}, %32, %33, p, 1, 1, %34, %35;\n}\n"
    : "+f"(d[0]), "+f"(d[1]), "+f"(d[2]), "+f"(d[3]), "+f"(d[4]), "+f"(d[5]), "+f"(d[6]), "+f"(d[7]),
      "+f"(d[8]), "+f"(d[9]), "+f"(d[10]), "+f"(d[11]), "+f"(d[12]), "+f"(d[13]), "+f"(d[14]), "+f"(d[15]),
      "+f"(d[16]), "+f"(d[17]), "+f"(d[18]), "+f"(d[19]), "+f"(d[20]), "+f"(d[21]), "+f"(d[22]), "+f"(d[23]),
      "+f"(d[24]), "+f"(d[25]), "+f"(d[26]), "+f"(d[27]), "+f"(d[28]), "+f"(d[29]), "+f"(d[30]), "+f"(d[31])
    : "l"(da), "l"(db), "n"(TA), "n"(TB));
}
template <int TA, int TB> __device__ __forceinline__ void ss64z(float* d, uint64_t da, uint64_t db) {
  asm volatile("{\n.reg .pred p;\nsetp.ne.b32 p, 0, 0;\n"
    "wgmma.mma_async.sync.aligned.m64n64k16.f32.bf16.bf16 "
    "{%0, %1, %2, %3, %4, %5, %6, %7, %8, %9, %10, %11, %12, %13, %14, %15, "
    "%16, %17, %18, %19, %20, %21, %22, %23, %24, %25, %26, %27, %28, %29, %30, %31}, %32, %33, p, 1, 1, %34, %35;\n}\n"
    : "=f"(d[0]), "=f"(d[1]), "=f"(d[2]), "=f"(d[3]), "=f"(d[4]), "=f"(d[5]), "=f"(d[6]), "=f"(d[7]),
      "=f"(d[8]), "=f"(d[9]), "=f"(d[10]), "=f"(d[11]), "=f"(d[12]), "=f"(d[13]), "=f"(d[14]), "=f"(d[15]),
      "=f"(d[16]), "=f"(d[17]), "=f"(d[18]), "=f"(d[19]), "=f"(d[20]), "=f"(d[21]), "=f"(d[22]), "=f"(d[23]),
      "=f"(d[24]), "=f"(d[25]), "=f"(d[26]), "=f"(d[27]), "=f"(d[28]), "=f"(d[29]), "=f"(d[30]), "=f"(d[31])
    : "l"(da), "l"(db), "n"(TA), "n"(TB));
}
__device__ __forceinline__ void ss64x4(float* d, const D2* c, int on) {
  asm volatile("{\n.reg .pred p, z, c;\nsetp.eq.b32 p, 0, 0;\nsetp.ne.b32 z, 0, 0;\nsetp.eq.b32 c, %40, 0;\n"
    "wgmma.mma_async.sync.aligned.m64n64k16.f32.bf16.bf16 "
    "{%0, %1, %2, %3, %4, %5, %6, %7, %8, %9, %10, %11, %12, %13, %14, %15, "
    "%16, %17, %18, %19, %20, %21, %22, %23, %24, %25, %26, %27, %28, %29, %30, %31}, %32, %33, z, 1, 1, 0, 1;\n"
    "wgmma.commit_group.sync.aligned;\n@c bra.uni X4_DONE;\n"
    "wgmma.mma_async.sync.aligned.m64n64k16.f32.bf16.bf16 "
    "{%0, %1, %2, %3, %4, %5, %6, %7, %8, %9, %10, %11, %12, %13, %14, %15, "
    "%16, %17, %18, %19, %20, %21, %22, %23, %24, %25, %26, %27, %28, %29, %30, %31}, %34, %35, p, 1, 1, 0, 1;\n"
    "wgmma.mma_async.sync.aligned.m64n64k16.f32.bf16.bf16 "
    "{%0, %1, %2, %3, %4, %5, %6, %7, %8, %9, %10, %11, %12, %13, %14, %15, "
    "%16, %17, %18, %19, %20, %21, %22, %23, %24, %25, %26, %27, %28, %29, %30, %31}, %36, %37, p, 1, 1, 0, 1;\n"
    "wgmma.mma_async.sync.aligned.m64n64k16.f32.bf16.bf16 "
    "{%0, %1, %2, %3, %4, %5, %6, %7, %8, %9, %10, %11, %12, %13, %14, %15, "
    "%16, %17, %18, %19, %20, %21, %22, %23, %24, %25, %26, %27, %28, %29, %30, %31}, %38, %39, p, 1, 1, 0, 1;\n"
    "wgmma.commit_group.sync.aligned;\nX4_DONE:\n}\n"
    : "=f"(d[0]), "=f"(d[1]), "=f"(d[2]), "=f"(d[3]), "=f"(d[4]), "=f"(d[5]), "=f"(d[6]), "=f"(d[7]),
      "=f"(d[8]), "=f"(d[9]), "=f"(d[10]), "=f"(d[11]), "=f"(d[12]), "=f"(d[13]), "=f"(d[14]), "=f"(d[15]),
      "=f"(d[16]), "=f"(d[17]), "=f"(d[18]), "=f"(d[19]), "=f"(d[20]), "=f"(d[21]), "=f"(d[22]), "=f"(d[23]),
      "=f"(d[24]), "=f"(d[25]), "=f"(d[26]), "=f"(d[27]), "=f"(d[28]), "=f"(d[29]), "=f"(d[30]), "=f"(d[31])
    : "l"(c[0].a), "l"(c[0].b), "l"(c[1].a), "l"(c[1].b), "l"(c[2].a), "l"(c[2].b), "l"(c[3].a), "l"(c[3].b), "r"(on));
}
template <int TB> __device__ __forceinline__ void rs32a(float* d, const uint32_t* a, uint64_t db) {
  asm volatile("{\n.reg .pred p;\nsetp.eq.b32 p, 0, 0;\n"
    "wgmma.mma_async.sync.aligned.m64n32k16.f32.bf16.bf16 "
    "{%0, %1, %2, %3, %4, %5, %6, %7, %8, %9, %10, %11, %12, %13, %14, %15}, {%16, %17, %18, %19}, %20, p, 1, 1, %21;\n}\n"
    : "+f"(d[0]), "+f"(d[1]), "+f"(d[2]), "+f"(d[3]), "+f"(d[4]), "+f"(d[5]), "+f"(d[6]), "+f"(d[7]),
      "+f"(d[8]), "+f"(d[9]), "+f"(d[10]), "+f"(d[11]), "+f"(d[12]), "+f"(d[13]), "+f"(d[14]), "+f"(d[15])
    : "r"(a[0]), "r"(a[1]), "r"(a[2]), "r"(a[3]), "l"(db), "n"(TB));
}
template <int TB> __device__ __forceinline__ void rs32z(float* d, const uint32_t* a, uint64_t db) {
  asm volatile("{\n.reg .pred p;\nsetp.ne.b32 p, 0, 0;\n"
    "wgmma.mma_async.sync.aligned.m64n32k16.f32.bf16.bf16 "
    "{%0, %1, %2, %3, %4, %5, %6, %7, %8, %9, %10, %11, %12, %13, %14, %15}, {%16, %17, %18, %19}, %20, p, 1, 1, %21;\n}\n"
    : "=&f"(d[0]), "=&f"(d[1]), "=&f"(d[2]), "=&f"(d[3]), "=&f"(d[4]), "=&f"(d[5]), "=&f"(d[6]), "=&f"(d[7]),
      "=&f"(d[8]), "=&f"(d[9]), "=&f"(d[10]), "=&f"(d[11]), "=&f"(d[12]), "=&f"(d[13]), "=&f"(d[14]), "=&f"(d[15])
    : "r"(a[0]), "r"(a[1]), "r"(a[2]), "r"(a[3]), "l"(db), "n"(TB));
}
template <int TB> __device__ __forceinline__ void rs40a(float* d, const uint32_t* a, uint64_t db) {
  asm volatile("{\n.reg .pred p;\nsetp.eq.b32 p, 0, 0;\n"
    "wgmma.mma_async.sync.aligned.m64n40k16.f32.bf16.bf16 "
    "{%0, %1, %2, %3, %4, %5, %6, %7, %8, %9, %10, %11, %12, %13, %14, %15, "
    "%16, %17, %18, %19}, {%20, %21, %22, %23}, %24, p, 1, 1, %25;\n}\n"
    : "+f"(d[0]), "+f"(d[1]), "+f"(d[2]), "+f"(d[3]), "+f"(d[4]), "+f"(d[5]), "+f"(d[6]), "+f"(d[7]),
      "+f"(d[8]), "+f"(d[9]), "+f"(d[10]), "+f"(d[11]), "+f"(d[12]), "+f"(d[13]), "+f"(d[14]), "+f"(d[15]),
      "+f"(d[16]), "+f"(d[17]), "+f"(d[18]), "+f"(d[19])
    : "r"(a[0]), "r"(a[1]), "r"(a[2]), "r"(a[3]), "l"(db), "n"(TB));
}
template <int TB> __device__ __forceinline__ void rs40z(float* d, const uint32_t* a, uint64_t db) {
  asm volatile("{\n.reg .pred p;\nsetp.ne.b32 p, 0, 0;\n"
    "wgmma.mma_async.sync.aligned.m64n40k16.f32.bf16.bf16 "
    "{%0, %1, %2, %3, %4, %5, %6, %7, %8, %9, %10, %11, %12, %13, %14, %15, "
    "%16, %17, %18, %19}, {%20, %21, %22, %23}, %24, p, 1, 1, %25;\n}\n"
    : "=&f"(d[0]), "=&f"(d[1]), "=&f"(d[2]), "=&f"(d[3]), "=&f"(d[4]), "=&f"(d[5]), "=&f"(d[6]), "=&f"(d[7]),
      "=&f"(d[8]), "=&f"(d[9]), "=&f"(d[10]), "=&f"(d[11]), "=&f"(d[12]), "=&f"(d[13]), "=&f"(d[14]), "=&f"(d[15]),
      "=&f"(d[16]), "=&f"(d[17]), "=&f"(d[18]), "=&f"(d[19])
    : "r"(a[0]), "r"(a[1]), "r"(a[2]), "r"(a[3]), "l"(db), "n"(TB));
}
template <int TB> __device__ __forceinline__ void rs72a(float* d, const uint32_t* a, uint64_t db) {
  asm volatile("{\n.reg .pred p;\nsetp.eq.b32 p, 0, 0;\n"
    "wgmma.mma_async.sync.aligned.m64n72k16.f32.bf16.bf16 "
    "{%0, %1, %2, %3, %4, %5, %6, %7, %8, %9, %10, %11, %12, %13, %14, %15, "
    "%16, %17, %18, %19, %20, %21, %22, %23, %24, %25, %26, %27, %28, %29, %30, %31, "
    "%32, %33, %34, %35}, {%36, %37, %38, %39}, %40, p, 1, 1, %41;\n}\n"
    : "+f"(d[0]), "+f"(d[1]), "+f"(d[2]), "+f"(d[3]), "+f"(d[4]), "+f"(d[5]), "+f"(d[6]), "+f"(d[7]),
      "+f"(d[8]), "+f"(d[9]), "+f"(d[10]), "+f"(d[11]), "+f"(d[12]), "+f"(d[13]), "+f"(d[14]), "+f"(d[15]),
      "+f"(d[16]), "+f"(d[17]), "+f"(d[18]), "+f"(d[19]), "+f"(d[20]), "+f"(d[21]), "+f"(d[22]), "+f"(d[23]),
      "+f"(d[24]), "+f"(d[25]), "+f"(d[26]), "+f"(d[27]), "+f"(d[28]), "+f"(d[29]), "+f"(d[30]), "+f"(d[31]),
      "+f"(d[32]), "+f"(d[33]), "+f"(d[34]), "+f"(d[35])
    : "r"(a[0]), "r"(a[1]), "r"(a[2]), "r"(a[3]), "l"(db), "n"(TB));
}
template <int TB> __device__ __forceinline__ void rs72z(float* d, const uint32_t* a, uint64_t db) {
  asm volatile("{\n.reg .pred p;\nsetp.ne.b32 p, 0, 0;\n"
    "wgmma.mma_async.sync.aligned.m64n72k16.f32.bf16.bf16 "
    "{%0, %1, %2, %3, %4, %5, %6, %7, %8, %9, %10, %11, %12, %13, %14, %15, "
    "%16, %17, %18, %19, %20, %21, %22, %23, %24, %25, %26, %27, %28, %29, %30, %31, "
    "%32, %33, %34, %35}, {%36, %37, %38, %39}, %40, p, 1, 1, %41;\n}\n"
    : "=&f"(d[0]), "=&f"(d[1]), "=&f"(d[2]), "=&f"(d[3]), "=&f"(d[4]), "=&f"(d[5]), "=&f"(d[6]), "=&f"(d[7]),
      "=&f"(d[8]), "=&f"(d[9]), "=&f"(d[10]), "=&f"(d[11]), "=&f"(d[12]), "=&f"(d[13]), "=&f"(d[14]), "=&f"(d[15]),
      "=&f"(d[16]), "=&f"(d[17]), "=&f"(d[18]), "=&f"(d[19]), "=&f"(d[20]), "=&f"(d[21]), "=&f"(d[22]), "=&f"(d[23]),
      "=&f"(d[24]), "=&f"(d[25]), "=&f"(d[26]), "=&f"(d[27]), "=&f"(d[28]), "=&f"(d[29]), "=&f"(d[30]), "=&f"(d[31]),
      "=&f"(d[32]), "=&f"(d[33]), "=&f"(d[34]), "=&f"(d[35])
    : "r"(a[0]), "r"(a[1]), "r"(a[2]), "r"(a[3]), "l"(db), "n"(TB));
}

template <int V> struct IC { static constexpr int value = V; };
struct PfType { const char* base; uint32_t gl, gh, sp, sr, su, l4, l2; };
struct Params {
  const __nv_bfloat16 *x, *w;
  uint32_t one;
  const __nv_bfloat16 *shift, *ssmD;
  __nv_bfloat16* out;
  uint4* o; float* kv; unsigned* cnt;
  const char *k, *v;
  PfType pt[6];
  uint8_t pf[32];
  uint64_t cd[18];
};

struct Tmp { float t0, t1; };
__device__ __forceinline__ void mul2(Tmp& t, float a0, float b0, float a1, float b1) {
  asm volatile("@p_one mul.rn.f32 %0, %2, %3;\n@p_one mul.rn.f32 %1, %4, %5;" : "+f"(t.t0), "+f"(t.t1) : "f"(a0), "f"(b0), "f"(a1), "f"(b1)); }
__device__ __forceinline__ void add2(Tmp& t, float a0, float b0, float a1, float b1) {
  asm volatile("@p_one add.rn.f32 %0, %2, %3;\n@p_one add.rn.f32 %1, %4, %5;" : "+f"(t.t0), "+f"(t.t1) : "f"(a0), "f"(b0), "f"(a1), "f"(b1)); }
__device__ __forceinline__ void fma2(Tmp& t, float a0, float b0, float a1, float b1) { t.t0 = fmaf(a0, b0, t.t0); t.t1 = fmaf(a1, b1, t.t1); }
__device__ __forceinline__ uint32_t bfma2(uint32_t a, uint32_t b, uint32_t c) { uint32_t r; asm("fma.rn.bf16x2 %0, %1, %2, %3;" : "=r"(r) : "r"(a), "r"(b), "r"(c)); return r; }
struct Tw { uint32_t c[2], s[2], ns[2]; };
__device__ __forceinline__ void rot(uint32_t& u, uint32_t& v, const Tw& w, int k) {
  asm("{\n.reg .b32 a, b;\nmul.rn.bf16x2 a, %0, %2;\nmul.rn.bf16x2 b, %0, %3;\nfma.rn.bf16x2 %0, %1, %4, a;\nfma.rn.bf16x2 %1, %1, %2, b;\n}"
    : "+r"(u), "+r"(v) : "r"(w.c[k]), "r"(w.s[k]), "r"(w.ns[k]));
}
__device__ __forceinline__ void pack_fwd(uint32_t (&f)[2][2][4], const float* a) {
  #pragma unroll
  for (int j = 0; j < 16; j++) f[j >> 3][(j >> 1) & 1][2 * (j & 1) + ((j >> 2) & 1)] = fresh(pack_bf16(a[2 * j], a[2 * j + 1]));
}
__device__ __forceinline__ void rot_fwd(uint32_t (&f)[2][2][4], const Tw& w) {
  #pragma unroll
  for (int j = 0; j < 8; j++) rot(f[j >> 2][j & 1][(j >> 1) & 1], f[j >> 2][j & 1][2 + ((j >> 1) & 1)], w, j & 1);
}
__device__ __forceinline__ void add_skip(float* h, float d) {
  asm volatile("add.rn.f32 %0, %0, %4;\nadd.rn.f32 %1, %1, %4;\nadd.rn.f32 %2, %2, %4;\nadd.rn.f32 %3, %3, %4;" : "+f"(h[0]), "+f"(h[1]), "+f"(h[4]), "+f"(h[5]) : "f"(d)); }
__device__ __forceinline__ void dft16h(float* d, const uint32_t (&f)[2][4], const D2& dF) { rs32z<0>(d, f[0], dF.a); rs32a<0>(d, f[1], dF.b); }
#define SP(h, p, im, k) (((p) >> 1 ? hi : lo) + 16 * (h) + 8 * (im) + 4 * (k) + 2 * ((p) & 1))
template <int PH, int G0 = 0, int G1 = 8> __device__ __forceinline__ void prod(Tmp& t, uint32_t (&f)[2][4], const float* lo, const float* hi) {
  #pragma unroll
  for (int g = G0; g < G1; g++) {
    const int p = 2 * PH + 1 - (g >> 2), k = (g >> 1) & 1, im = g & 1;
    #pragma unroll
    for (int q = 0; q <= p; q++) {
      const float *hr = SP(1, q, 0, k), *hi_ = SP(1, q, 1, k), *xa = SP(0, p - q, im, k), *xb = SP(0, p - q, 1 - im, k);
      if (q == 0) mul2(t, hr[0], xa[0], hr[1], xa[1]); else fma2(t, hr[0], xa[0], hr[1], xa[1]);
      if (im) fma2(t, hi_[0], xb[0], hi_[1], xb[1]); else fma2(t, -hi_[0], xb[0], -hi_[1], xb[1]);
    }
    f[k][2 * (1 - im) + (p & 1)] = pack_bf16(t.t0, t.t1);
  }
}

constexpr uint64_t dA = cdesc(A_OFF, 2048, 128, 0), dAi = cdesc(A_OFF, 128, 1024, 0), dF0 = cdesc(F_OFF, 128, 512, 0),
                   dT0 = cdesc(T_OFF, 1024, 128, 0), dH0 = cdesc(H_OFF, 1024, 256, 3), dX0 = cdesc(X_OFF, 1024, 128, 0);
#define CONV_DESC dF0, dF0 + 16, dAi, dT0, dAi + 16, dT0 + 128, dAi + 32, dT0 + 256, dAi + 48, dT0 + 384, dA, dH0, dA + 256, dH0 + 32, dA, dX0, dA + 256, dX0 + 128
__device__ __forceinline__ void make_tw(Tw& tw, int ht) {
  #pragma unroll
  for (int i = 0; i < 2; i++) {
    float c0, s0, c1, s1;
    unit_root<11>((4 * (ht >> 2) + 1) * (i * 8 + 2 * (ht & 3)), c0, s0);
    unit_root<11>((4 * (ht >> 2) + 1) * (i * 8 + 2 * (ht & 3) + 1), c1, s1);
    tw.c[i] = pack_bf16(c0, c1); tw.s[i] = pack_bf16(s0, s1); tw.ns[i] = fresh(tw.s[i] ^ 0x80008000u);
  }
}
template <bool COMMIT = true> __device__ __forceinline__ void dft32_h(float* r, const D2* d) {
  ss64z<1, 1>(r, d[0].a, d[0].b); ss64a<1, 1>(r, d[1].a, d[1].b);
  if (COMMIT) wg_commit();
}
template <bool COMMIT = true> __device__ __forceinline__ void dft32_x(float* r, D2* d) {
  ss64z<1, 0>(r, d[0].a, d[0].b); ss64a<1, 0>(r, d[1].a, d[1].b);
  if (COMMIT) wg_commit();
  d[0].b = dofs(d[0].b, XS); d[1].b = dofs(d[1].b, XS);
}
__device__ __forceinline__ void pack_inv(uint32_t (&u)[2][2][4], const float* r) {
  #pragma unroll
  for (int j = 0; j < 16; j++) u[j >> 3][(j >> 2) & 1][2 * (j & 1) + ((j >> 1) & 1)] = fresh(pack_bf16(r[2 * j], r[2 * j + 1]));
}
__device__ __forceinline__ void rot_inv(uint32_t (&u)[2][2][4], const Tw& tw, uint32_t ta) {
  #pragma unroll
  for (int m = 0; m < 2; m++) {
    #pragma unroll
    for (int j = 0; j < 4; j++) rot(u[m][0][j], u[m][1][j], tw, j & 1);
    stsm4(ta + m * 512, u[m][1][0], u[m][1][1], u[m][1][2], u[m][1][3]);
    stsm4(ta + 1024 + m * 512, u[m][0][0], u[m][0][1], u[m][0][2], u[m][0][3]);
  }
}
__device__ __forceinline__ void idft32(float* r, const D2* d) {
  wg_fence();
  ss64z<0, 1>(r, d[0].a, d[0].b);
  #pragma unroll
  for (int j = 1; j < 4; j++) ss64a<0, 1>(r, d[j].a, d[j].b);
  wg_commit();
}
__device__ __forceinline__ void finish(Tmp& t, const float* r, int ch, int ht, int rank, uint32_t y0, uint32_t y1) {
  const uint32_t ya = X_OFF + ch * XS + (ch & 1) * 16, yb = BAR_OFF + (B_YR + ch) * 8;
  uint32_t y[8];
  #pragma unroll
  for (int j = 0; j < 8; j++) {
    if (j >= 2) add2(t, r[4 * j], r[4 * j - 6], r[4 * j + 1], r[4 * j - 5]);
    y[j] = j < 2 ? pack_bf16(r[4 * j], r[4 * j + 1]) : pack_bf16(t.t0, t.t1);
  }
  st_async128(y0 + ya + (ht ^ (rank * 4)) * 16 + rank * (YX - XS), y0 + yb, y[0], y[1], y[2], y[3]);
  st_async128(y1 + ya + (ht ^ (rank * 4) ^ 4) * 16 + (rank ^ 1) * (YX - XS), y1 + yb, y[4], y[5], y[6], y[7]);
}

struct Team { uint32_t bars, rel, wofs; bool lead; };
template <bool M> __device__ __forceinline__ void mid_wait() { if (M) { wg_commit(); wg_wait<0>(); wg_fence(); } }
template <int J, bool M = false> __device__ __forceinline__ void kv_issue(float* aK, float* aV, uint32_t xo, int sd) {
  constexpr uint64_t dw = cdesc(W_OFF + J * 8192, 8192, 1024, 1);
  const uint64_t dx = dofs(cdesc((J & 1) * 64, 16, 1024, 1), xo);
  wg_fence();
  ss128p<1, 0>(aV, dw + (4096 >> 4), dx, sd);
  ss128p<1, 0>(aK, dw, dx, sd);
  mid_wait<M>();
  ss128a<1, 0>(aV, dw + (6144 >> 4), dofs(dx, 32));
  ss128a<1, 0>(aK, dw + (2048 >> 4), dofs(dx, 32));
  wg_commit();
}
template <int O, int J, bool M = false, bool FIRST = false> __device__ __forceinline__ void g2_issue(float* acc, const Team& c) {
  constexpr uint64_t db = cdesc(J * SLOT + 16384, 8192, 1024, 1);
  const uint64_t da = dofs(O ? cdesc(J * SLOT, 16, 512, 2) : cdesc(J * SLOT, 16, 1024, 1), c.wofs);
  wg_fence();
  if (FIRST) ss128z<0, 1>(acc, da, db); else ss128a<0, 1>(acc, da, db);
  ss128a<0, 1>(acc, dofs(da, 32), db + (2048 >> 4));
  mid_wait<M>();
  ss128a<0, 1>(acc, dofs(da, O ? 4096 : 64), db + (4096 >> 4));
  ss128a<0, 1>(acc, dofs(da, O ? 4128 : 96), db + (6144 >> 4));
  wg_commit();
}
template <bool DEEP, bool AB = false, class F>
__device__ __forceinline__ void ring_step(const Team& c, int fb, uint32_t ph, int eb, bool rel, F issue, uint32_t ab = 0, uint32_t aph = 0) {
  uint32_t ok = mbar_try(c.bars + fb * 8, ph);
  if (AB) ok &= mbar_try(ab, aph);
  if (!ok) {
    wg_wait<0>();
    arrive_at(c.rel + eb * 8, rel);
    rel = false;
    mbar_wait(c.bars + fb * 8, ph);
    if (AB) mbar_wait(ab, aph);
  }
  if (!DEEP) { wg_wait<0>(); arrive_at(c.rel + eb * 8, rel); }
  issue();
  if (DEEP) { wg_wait<1>(); arrive_at(c.rel + eb * 8, rel); }
}
template <int N, int I = 0, class R> __device__ __forceinline__ void tail_release(R rel) {
  if constexpr (I <= N) { wg_wait<N - I>(); rel(I - 1); tail_release<N, I + 1>(rel); }
}
template <int N, class F, class R> __device__ __forceinline__ void skew_tail(const Team& c, int ph, F issue, R rel) {
  if (c.wofs) { wg_wait<0>(); rel(-1); mbar_wait(c.bars + B_SK * 8, ph); }
  issue();
  arrive_at(c.bars + B_SK * 8, fresh_tid() == 0);
  tail_release<N>([&](int i) { if (i >= 0 || !c.wofs) rel(i); });
}
__device__ __forceinline__ void phi_a(float* a, uint32_t* f) {
  #pragma unroll
  for (int i = 0; i < 8; i++) {
    asm("cvt.rn.relu.bf16x2.f32 %0, %1, %2;" : "=r"(f[i]) : "f"(a[2 * i + 1]), "f"(a[2 * i]));
    asm("ex2.approx.ftz.f32 %0, %1;" : "=f"(a[2 * i]) : "f"(a[2 * i] * 1.4426950408889634f));
    asm("ex2.approx.ftz.f32 %0, %1;" : "=f"(a[2 * i + 1]) : "f"(a[2 * i + 1] * 1.4426950408889634f));
  }
  pinv<16>(a);
}
__device__ __forceinline__ void phi_b(const float* e, uint32_t* f) {
  #pragma unroll
  for (int i = 0; i < 8; i++) f[i] = badd2(f[i], pack_bf16(__saturatef(e[2 * i] + 1e-6f), __saturatef(e[2 * i + 1] + 1e-6f)));
}
__device__ __forceinline__ int g2_k(int st, int n2) { return st < 2 ? 2 * n2 + st : ((st >> 1) == n2 ? st & 1 : st); }

__global__ void __cluster_dims__(2, 1, 1) __launch_bounds__(NTHREADS, 1)
fused_kernel(const __grid_constant__ Params P, const __grid_constant__ CUtensorMap mX, const __grid_constant__ CUtensorMap mW,
             const __grid_constant__ CUtensorMap mWq, const __grid_constant__ CUtensorMap mWo,
             const __grid_constant__ CUtensorMap mK, const __grid_constant__ CUtensorMap mV, const __grid_constant__ CUtensorMap mH,
             const __grid_constant__ CUtensorMap mQ, const __grid_constant__ CUtensorMap mOut, const __grid_constant__ CUtensorMap mOutA) {
  extern __shared__ __align__(1024) uint8_t smem[];
  asm volatile(".reg .pred p_one;");
  if (__shfl_sync(0xffffffffu, threadIdx.x >> 5, 0) == 0) {
    asm volatile(ELECT "prefetch.tensormap [%0];\n}" :: "l"(&mW) : "memory");
    asm volatile(ELECT "prefetch.tensormap [%0];\n}" :: "l"(&mX) : "memory");
  }
  {
    const uint32_t t = threadIdx.x, bb = blockIdx.x;
    asm volatile("{\n.reg .pred p, q;\nsetp.eq.u32 p, %2, 2;\nsetp.eq.u32 q, %3, 8;\n@p prefetch.global.L2 [%0];\n@q prefetch.global.L2 [%1];\n}"
      :: "l"(reinterpret_cast<const char*>(P.x) + ((bb * 16 + t - 32) * 2048)),
         "l"(reinterpret_cast<const char*>(P.w) + ((bb >> 2) * 2048 + bb * 1024 + t * 128 - 6144)), "r"(t >> 4), "r"(t >> 3));
  }
  const uint32_t sb = uni(smem_u32(smem));
  const uint32_t bars = sb + BAR_OFF;
  const int tid = threadIdx.x, lane = tid & 31;
  const int warp = __shfl_sync(0xffffffffu, tid >> 5, 0);
  const uint32_t ids = uni(cta_ids());
#define IDS(w) const int b = (w) & 127, rank = (w) & 1, g = ((w) >> 8) & 7, mb = (w) >> 12, hp = g * 2 + rank, m2 = hp, n2 = mb, \
                         cp = g * 8 + mb; (void)b; (void)hp; (void)m2; (void)n2; (void)cp
  IDS(ids);

  if (warp == 0) {
    mbar_init(bars + (B_XF + 2) * 8, 1); mbar_init(bars + B_F0 * 8, 1); mbar_init(bars + B_FULL * 8, 1);
    mbar_expect_tx(bars + B_FULL * 8, 8192);
    tma3d(sb + W_OFF, &mW, hp * 64, 0, 1, bars + B_FULL * 8);
    mbar_expect_tx(bars + (B_XF + 2) * 8, 16384);
    tma2d(sb + 2 * SLOT, &mX, 0, mb * 256, bars + (B_XF + 2) * 8);
    mbar_expect_tx(bars + B_F0 * 8, 16384);
    tma2d(sb + 2 * SLOT + 16384, &mX, 0, mb * 256 + 128, bars + B_F0 * 8);
    #pragma unroll
    for (int i = 1; i < 4; i++) mbar_init(bars + (B_FULL + i) * 8, 1);
    mbar_init(bars + B_XF * 8, 1); mbar_init(bars + (B_XF + 1) * 8, 1);
    #pragma unroll
    for (int i = 1; i < 4; i++) {
      mbar_expect_tx(bars + (B_FULL + i) * 8, 8192);
      tma3d(sb + W_OFF + i * 8192, &mW, hp * 64, i * 32, 1, bars + (B_FULL + i) * 8);
    }
  } else if (warp >= 6) {
    const uint32_t cnt = warp < 12 || warp == 15 ? 1 : 4, b0 = bars + (warp - 4) * 32;
    #pragma unroll
    for (int i = 0; i < 4; i++) mbar_init(b0 + i * 8, i == 3 && warp == 15 ? 4 : cnt);
    if (warp == 8 || warp == 9) {
      #pragma unroll
      for (int i = 0; i < 4; i++) mbar_expect_tx(b0 + i * 8, 4096);
    } else if (warp == 13) {
      mbar_expect_tx(bars + B_KVB * 8, 5120);
    }
  }
  asm volatile("fence.mbarrier_init.release.cluster;" ::: "memory");
  __syncwarp();
  asm volatile("barrier.cluster.arrive.relaxed.aligned;" ::: "memory");

  if (warp < 8) {
    asm volatile("setmaxnreg.inc.sync.aligned.u32 %0;" :: "n"(160));
    const int wg = warp >> 2;
    Team c;
    c.bars = bars; c.rel = mapa(bars, tid & 1); c.wofs = wg * 8192; c.lead = (tid & 127) < 2;
    uint32_t key = P.one;
    auto gemm2 = [&](float* a, auto O_, auto SK_) {
      constexpr int O = O_.value, SK = SK_.value;
      static_assert(SK >= 1 && SK <= 3, "tail");
      uint32_t ph = 1;
      const uint32_t ab = bars + B_FA * 8 + wg * 32;
      #pragma unroll 1
      for (int it = 1; it < 4; it++, ph ^= 1) {
        ring_step<false, O>(c, B_FULL2, ph, B_EMPTY2 + 3, c.lead, [&]() { g2_issue<O, 0, (MID >> (1 + O)) & 1>(a, c); }, ab, ph);
        if (!O && (tid & 127) == 0) OSTAMP(55 + wg * 4 + it);
        if (O && (tid & 127) == 0) OSTAMP(40 + wg * 4 + it);
        if (SK == 3 && it == 3) break;
        ring_step<false, O>(c, B_FULL2 + 1, ph, B_EMPTY2, c.lead && (!O || it < 3), [&]() { g2_issue<O, 1, (MID >> (1 + O)) & 1>(a, c); }, ab + 8, ph);
        if (SK == 2 && it == 3) break;
        ring_step<false, O>(c, B_FULL2 + 2, ph, B_EMPTY2 + 1, c.lead && (!O || it < 3), [&]() { g2_issue<O, 2, (MID >> (1 + O)) & 1>(a, c); }, ab + 16, ph);
        if (SK == 1 && it == 3) break;
        ring_step<false, O>(c, B_FULL2 + 3, ph, B_EMPTY2 + 2, c.lead, [&]() { g2_issue<O, 3, (MID >> (1 + O)) & 1>(a, c); }, ab + 24, ph);
      }
      skew_tail<SK>(c, O ^ 1,
        [&]() {
          auto full = [&](int jj) { mbar_wait(bars + (B_FULL2 + jj) * 8, 1); if (O) mbar_wait(ab + jj * 8, 1); };
          if (SK >= 3) { full(1); g2_issue<O, 1>(a, c); }
          if (SK >= 2) { full(2); g2_issue<O, 2>(a, c); }
          full(3); g2_issue<O, 3>(a, c);
        },
        [&](int i) { if (!O) arrive_at(c.rel + (B_EMPTY2 + ((16 - SK + i) & 3)) * 8, c.lead); });
      pinv<64>(a);
    };
    float aq[64];
    {
      float aK[64], aV[64];
      if (wg == 0) { kv_issue<0>(aK, aV, 0, 0); wg_wait<0>(); }
      cluster_wait();
      if (wg == 1) mbar_wait(bars + B_F0 * 8, 0);
      static_assert(SK1 >= 1 && SK1 <= 3, "tail");
      uint32_t ph = 0, xs = 2, xp = 0;
      auto next_x = [&]() { if (xs == 1) xp ^= 1; xs = xs == 2 ? 0 : xs + 1; };
      #pragma unroll 1
      for (int it = 0; it < 8; it++, ph ^= 1) {
        uint32_t xo = xs * SLOT + wg * 16384;
        ring_step<false, true>(c, B_FULL, ph, B_EMPTY + 3, c.lead && it > 0, [&]() { kv_issue<0, MID & 1>(aK, aV, xo, it); if (tid == 0 && it == 0) OSTAMP(1); }, bars + (B_XF + xs) * 8, xp);
        if (SK1 == 3 && it == 7) break;
        next_x();
        ring_step<false>(c, B_FULL + 1, ph, B_EMPTY, c.lead, [&]() { kv_issue<1, MID & 1>(aK, aV, xo, 1); });
        if (SK1 == 2 && it == 7) break;
        xo = xs * SLOT + wg * 16384;
        ring_step<false, true>(c, B_FULL + 2, ph, B_EMPTY + 1, c.lead, [&]() { kv_issue<2, MID & 1>(aK, aV, xo, 1); }, bars + (B_XF + xs) * 8, xp);
        if (SK1 == 1 && it == 7) break;
        next_x();
        ring_step<false>(c, B_FULL + 3, ph, B_EMPTY + 2, c.lead, [&]() { kv_issue<3, MID & 1>(aK, aV, xo, 1); });
      }
      skew_tail<SK1>(c, 0,
        [&]() {
          auto wait = [&](uint32_t a) { mbar_wait(a, 1); };
          if (SK1 >= 3) { wait(bars + (B_FULL + 1) * 8); kv_issue<1>(aK, aV, SLOT + wg * 16384, 1); }
          if (SK1 >= 2) { wait(bars + (B_FULL + 2) * 8); wait(bars + (B_XF + 2) * 8); kv_issue<2>(aK, aV, 2 * SLOT + wg * 16384, 1); }
          wait(bars + (B_FULL + 3) * 8); kv_issue<3>(aK, aV, 2 * SLOT + wg * 16384, 1);
        },
        [&](int i) { arrive_at(c.rel + (B_EMPTY + ((32 - SK1 + i) & 3)) * 8, c.lead); });
      pinv<64>(aV); pinv<64>(aK);
      if (tid == 128) OSTAMP(3);
      const uint32_t vb = sb + M_OFF + wg * VT;
      float kv[36];
      uint32_t kf[4][8];
      const uint64_t dv = dofs(cdesc(M_OFF, 1152, 128, 0), wg * VT);
      const int t = fresh_tid();
      const uint32_t va = vb + ((t >> 4) & 1) * 1152 + ((t >> 5) & 3) * 256 + (t & 15) * 16;
      mbar_wait(bars + B_X * 8, 0);
      #pragma unroll
      for (int i = 0; i < 8; i++) {
        const float* a = aV + 8 * i;
        stsm4(va + i * 2304, pack_bf16(a[0], a[1]), pack_bf16(a[2], a[3]), pack_bf16(a[4], a[5]), pack_bf16(a[6], a[7]));
      }
      phi_a(aK + 48, kf[3]);
      mbar_wait(bars + B_FULL2 * 8, 0);
      if ((tid & 127) == 0) OSTAMP(50 + wg);
      g2_issue<0, 0, false, true>(aq, c);
      sts128(vb + ((t & 127) >> 3) * 1152 + 1024 + (t & 7) * 16, 0x3f803f80u, 0x3f803f80u, 0x3f803f80u, 0x3f803f80u);
      phi_a(aK + 32, kf[2]); phi_b(aK + 48, kf[3]);
      sched_fence(key++);
      ring_step<true>(c, B_FULL2 + 1, 0, B_EMPTY2, c.lead, [&]() { g2_issue<0, 1>(aq, c); });
      phi_a(aK + 16, kf[1]); phi_b(aK + 32, kf[2]);
      sched_fence(key++);
      ring_step<true>(c, B_FULL2 + 2, 0, B_EMPTY2 + 1, c.lead, [&]() { g2_issue<0, 2>(aq, c); });
      phi_a(aK, kf[0]); phi_b(aK + 16, kf[1]);
      sched_fence(key++);
      fence_async_smem(); bar_sync(1 + wg, 128);
      phi_b(aK, kf[0]);
      sched_fence(key++);
      wg_fence();
      #pragma unroll
      for (int ks = 0; ks < 8; ks++) {
        if (ks == 0) rs72z<0>(kv, kf[0], dv); else rs72a<0>(kv, kf[ks >> 1] + 4 * (ks & 1), dofs(dv, ks * 2304));
      }
      wg_commit();
      wg_wait<1>();
      arrive_at(c.rel + (B_EMPTY2 + 2) * 8, c.lead);
      mbar_wait(bars + (B_FULL2 + 3) * 8, 0);
      g2_issue<0, 3>(aq, c);
      wg_wait<1>();
      pinv<36>(kv);
      const int a = fresh_tid() & 127;
      const bool hi = a >= 64;
      #pragma unroll
      for (int u = 0; u < 4; u++) {
        const int o = (u & 1) * 8 + (u & 2);
        sts128(vb + (a ^ ((a >> 3) & 3)) * 16 + u * 2048, __float_as_uint(hi ? kv[16 + o] : kv[o]), __float_as_uint(hi ? kv[17 + o] : kv[o + 1]),
               __float_as_uint(hi ? kv[20 + o] : kv[o + 4]), __float_as_uint(hi ? kv[21 + o] : kv[o + 5]));
      }
      if ((a & 3) < 2) sts32(vb + 8192 + ((a >> 5) * 16 + ((a & 31) >> 2) + (a & 1) * 8) * 4, __float_as_uint((a & 1) ? kv[34] : kv[32]));
      bar_arrive(4, 352);
    }
    if (tid == 0) OSTAMP(4);
    if (tid == 128) OSTAMP(5);
    float acc[64];
    {
      gemm2(aq, IC<0>(), IC<SK2>());
      if (tid == 0) OSTAMP(6);
      if (tid == 128) OSTAMP(7);
      constexpr uint64_t dk = cdesc(KVB_OFF, 640, 128, 0);
      const uint32_t id2 = fresh(ids); IDS(id2);
      float nu[4][20];
      uint32_t gen, far;
      uint32_t pq[4][8], o[4][2][4];
      const int t2 = fresh_tid();
      const uint32_t oo = (t2 & 96) * 32 + (t2 & 28) * 16 + ((t2 ^ (t2 >> 3)) & 3) * 16;
      uint4* og = P.o + ((m2 * 8 + n2) * 4 + wg) * 512 + (oo >> 4);
      auto o_put = [&](int h, int e) {
        if (AB & 8) return;
        asm volatile("st.global.v4.b32 [%0], {%1,%2,%3,%4};" :: "l"(og + (h >> 1) * 1024 + (h & 1) * 256 + e * 32),
          "r"(o[h][e][0]), "r"(o[h][e][1]), "r"(o[h][e][2]), "r"(o[h][e][3]) : "memory");
      };
      auto o_out = [&](int h) {
        pinv<20>(nu[h]);
        #pragma unroll
        for (int e = 0; e < 2; e++) {
          const float* n = nu[h] + 2 * e;
          const float iv = rcp_fast(n[16] + 1e-6f);
          #pragma unroll
          for (int i = 0; i < 4; i++) o[h][e][i] = pack_bf16(n[4 * i] * iv, n[4 * i + 1] * iv);
          o_put(h, e);
        }
      };
      auto o_mma = [&](int h) {
        wg_fence();
        rs40z<1>(nu[h], pq[h], dk + h * (2560 >> 4));
        rs40a<1>(nu[h], pq[h] + 4, dk + h * (2560 >> 4) + (1280 >> 4));
        wg_commit();
      };
#define QSTAMP(i) do { if ((t2 & 127) == 0) TSTAMP(6, wg * 16 + (i)); } while (0)
      QSTAMP(0);
      #pragma unroll
      for (int u = 0; u < 5; u++) {
        if (u >= 3) { wg_wait<1>(); QSTAMP(2 * u + 1); o_out(u - 3); }
        if (u < 4) phi_a(aq + 16 * u, pq[u]);
        if (u > 0) phi_b(aq + 16 * (u - 1), pq[u - 1]);
        if (u == 1) { QSTAMP(2); if (!(AB & 16)) mbar_wait(bars + B_KVB * 8, 0); QSTAMP(3); gen = lds32(sb + D_OFF + 40); far = lds32(sb + D_OFF + 48); fence_async_smem(); } else sched_fence(key++);
        QSTAMP(u ? 2 * u + 2 : 1);
        if (u > 0) o_mma(u - 1);
        if (u == 1) QSTAMP(5);
      }
      wg_wait<1>(); QSTAMP(11); o_out(2);
      sched_fence(key++);
      wg_wait<0>(); QSTAMP(12); o_out(3);
      QSTAMP(13);
      asm volatile(ELECT "st.relaxed.gpu.global.u32 [%0], %1;\n}" :: "l"(&P.cnt[(32 + m2 * 2 + wg) * 32 + n2 * 4 + (warp & 3)]), "r"(gen) : "memory");
      bar_arrive(6, 288);
      if ((t2 & 127) == 0) OSTAMP(8 + wg * 2);
      #pragma unroll
      for (int i = 0; i < 8; i++)
        sts128(sb + wg * 8192 + oo + (i >> 2) * SLOT + ((i >> 1) & 1) * 4096 + (i & 1) * 512, o[i >> 1][i & 1][0], o[i >> 1][i & 1][1], o[i >> 1][i & 1][2], o[i >> 1][i & 1][3]);
      mbar_wait(bars + B_FULL2 * 8, 0);
      mbar_wait(bars + (B_FULL2 + 1) * 8, 0);
      QSTAMP(14);
      fence_async_smem();
      QSTAMP(15);
      g2_issue<1, 0, false, true>(acc, c);
      g2_issue<1, 1>(acc, c);
      if ((t2 & 127) == 0) OSTAMP(37 + wg);
      wg_wait<1>();
      arrive_at(c.rel + B_EMPTY2 * 8, c.lead);
      const uint32_t ab = bars + B_FA * 8 + wg * 32;
      const int k2 = g2_k(2, n2);
      const bool doubt = NEAR == 2 || (uni(far) >> (k2 >> 1)) & 1;
      auto look = [&](int j) {
        if (doubt) {
          const uint32_t a = sb + (2 + j) * SLOT + wg * 8192 + (t2 & 96) * 32;
          if (__any_sync(0xffffffffu, lds32(a + (t2 & 16) * 256 + (t2 & 15) * 64 + (t2 & 30) * 2) == ~0u)) {
            const uint4* src = P.o + (m2 * 16 + k2 + j) * 1024 + wg * 512 + (t2 & 96) * 2 + (t2 & 31);
            if ((t2 & 31) == 0) OSTAMP(34);
            #pragma unroll 1
            for (int i = 0; i < 4; i++) {
              uint32_t v[4];
              int n = 0;
              do asm volatile("ld.relaxed.gpu.global.v4.u32 {%0,%1,%2,%3}, [%4];" : "=r"(v[0]), "=r"(v[1]), "=r"(v[2]), "=r"(v[3]) : "l"(src + (i & 1) * 32 + (i >> 1) * 256) : "memory");
              while (__any_sync(0xffffffffu, v[0] == ~0u) && ++n < 64);
              sts128(a + (t2 & 31) * 16 + (i & 1) * 512 + (i >> 1) * 4096, v[0], v[1], v[2], v[3]);
            }
            fence_async_smem();
            __syncwarp();
          }
        }
      };
      ring_step<true, true>(c, B_FULL2 + 2, 0, B_EMPTY2 + 1, c.lead, [&]() { look(0); if ((t2 & 127) == 0) OSTAMP(11 + wg * 24); g2_issue<1, 2>(acc, c); }, ab + 16, 0);
      ring_step<true, true>(c, B_FULL2 + 3, 0, B_EMPTY2 + 2, c.lead, [&]() { look(1); g2_issue<1, 3>(acc, c); }, ab + 24, 0);
    }
    gemm2(acc, IC<1>(), IC<SK3>());
    if (tid == 0) OSTAMP(13);
    if (tid == 128) OSTAMP(14);
    {
      const uint32_t id2 = fresh(ids); IDS(id2);
      const int t2 = fresh_tid();
      const int row = ((t2 >> 5) & 3) * 16 + (t2 & 15);
      const int cq = (t2 >> 4) & 1, sw = t2 & 7;
      const uint32_t stg = sb + (EHI ? T_OFF : 0) + wg * 8192;
      constexpr uint32_t HS = EHI ? 16384 : SLOT;
      if (EHI) mbar_wait(bars + B_CD * 8, 0);
      #pragma unroll 1
      for (int pass = 0;; pass++) {
      const bool bad = acc[0] != acc[0] || acc[2] != acc[2];
      #pragma unroll
      for (int hf = 0; hf < 2; hf++) {
        #pragma unroll
        for (int jj = 0; jj < 4; jj++) {
          const int o = hf * 32 + jj * 8;
          stsm4(stg + hf * HS + row * 128 + (((2 * jj + cq) ^ sw) << 4),
                pack_bf16(acc[o], acc[o + 1]), pack_bf16(acc[o + 2], acc[o + 3]),
                pack_bf16(acc[o + 4], acc[o + 5]), pack_bf16(acc[o + 6], acc[o + 7]));
        }
        fence_async_smem();
        __syncwarp();
        if (!(AB & 1) && !((AB & 32) && wg == 0)) tma2d_store(&mOut, 1024 + n2 * 128 + hf * 64, m2 * 128 + warp * 16, sb + (EHI ? T_OFF : 0) + hf * HS + warp * 2048);
      }
      bulk_commit();
      uint32_t redo;
      asm volatile("{\n.reg .pred p, q;\nsetp.ne.b32 p, %1, 0;\nbar.red.or.pred q, %2, 128, p;\nselp.u32 %0, 1, 0, q;\n}" : "=r"(redo) : "r"((uint32_t)bad), "r"(1 + wg) : "memory");
      if (!uni(redo) || pass) break;
      if ((t2 & 127) == 0) OSTAMP(48 + wg);
      asm volatile("cp.async.bulk.wait_group 0;" ::: "memory");
      spin_until(&P.cnt[(16 + m2) * 32 + (t2 & 7)], lds32(sb + D_OFF + 40));
      fence_async_global();
      const uint32_t ab = bars + B_FA * 8 + wg * 32;
      #pragma unroll 1
      for (int k = 0; k < 16; k++) {
        bar_sync(1 + wg, 128);
        if ((warp & 3) == 0) {
          mbar_expect_tx(ab, 24576);
          bulk_load(sb + c.wofs, P.o + (m2 * 16 + k) * 1024 + wg * 512, 8192, ab);
          tma2d(sb + SLOT + c.wofs, &mWo, n2 * 128, k * 64, ab);
          tma2d(sb + 2 * SLOT + c.wofs, &mWo, n2 * 128 + 64, k * 64, ab);
        }
        mbar_wait(ab, k & 1);
        const uint64_t da = dofs(cdesc(0, 16, 512, 2), c.wofs), db = dofs(cdesc(SLOT, SLOT, 1024, 1), c.wofs);
        wg_fence();
        ss128p<0, 1>(acc, da, db, k);
        ss128a<0, 1>(acc, dofs(da, 32), dofs(db, 2048));
        ss128a<0, 1>(acc, dofs(da, 4096), dofs(db, 4096));
        ss128a<0, 1>(acc, dofs(da, 4128), dofs(db, 6144));
        wg_commit();
        wg_wait<0>(); pinv<64>(acc);
      }
      }
      bulk_wait_read();
    }
  } else if (warp < 12) {
    asm volatile("setmaxnreg.inc.sync.aligned.u32 %0;" :: "n"(160));
    const uint32_t id2 = fresh(ids); IDS(id2);
    const int ht = tid - 256, w = warp - 8;
    const int kap = w & 1;
    uint32_t w0, w1, w2, w3;
    {
      const uint4 s = *reinterpret_cast<const uint4*>(P.shift + (cp * 16 + kap * 8 + 2 * (lane & 3)) * 4);
      w0 = __byte_perm(s.x, s.z, 0x5410); w1 = __byte_perm(s.x, s.z, 0x7632);
      w2 = __byte_perm(s.y, s.w, 0x5410); w3 = __byte_perm(s.y, s.w, 0x7632);
      float dv = 0.f;
      if (ht < 8) dv = __bfloat162float(P.ssmD[cp * 16 + rank * 8 + ht]) * 0.125f;
      uint32_t c4[4], s4[4];
      #pragma unroll
      for (int i = 0; i < 4; i++) {
        float c0, s0, c1, s1;
        unit_root<7>((32 * (ht & 3) + 8 * i + 1) * (ht >> 2), c0, s0);
        unit_root<7>((32 * (ht & 3) + 8 * i + 5) * (ht >> 2), c1, s1);
        c4[i] = pack_bf16(c0 * 0.125f, c1 * 0.125f); s4[i] = pack_bf16(s0 * 0.125f, s1 * 0.125f);
      }
      const uint32_t aa = sb + A_OFF + w * 2048 + (ht & 3) * 256 + ((ht >> 2) & 7) * 16;
      sts128(aa, c4[0], c4[1], c4[2], c4[3]);
      sts128(aa + 128, s4[0], s4[1], s4[2], s4[3]);
      sts128(aa + 1024, s4[0] ^ 0x80008000u, s4[1] ^ 0x80008000u, s4[2] ^ 0x80008000u, s4[3] ^ 0x80008000u);
      sts128(aa + 1024 + 128, c4[0], c4[1], c4[2], c4[3]);
      float c0, s0, c1, s1;
      unit_root<4>((ht >> 3) * (2 * (ht & 7)), c0, s0);
      unit_root<4>((ht >> 3) * (2 * (ht & 7) + 1), c1, s1);
      const uint32_t fa = sb + F_OFF + (ht >> 6) * 512 + ((ht >> 2) & 1) * 256 + ((ht >> 3) & 7) * 16 + (ht & 3) * 4;
      const uint32_t cc = pack_bf16(c0, c1), ss = pack_bf16(s0, s1);
      sts32(fa, cc); sts32(fa + 128, ss ^ 0x80008000u); sts32(fa + 1024, ss); sts32(fa + 1024 + 128, cc);
      if (ht < 8) sts32(sb + D_OFF + ht * 4, __float_as_uint(dv));
    }
    Tw tw;
    make_tw(tw, ht);
    D2 cd[9];
    {
      const uint64_t v = P.cd[min(lane, 17)];
      #pragma unroll
      for (int i = 0; i < 9; i++) { cd[i].a = __shfl_sync(0xffffffffu, v, 2 * i); cd[i].b = __shfl_sync(0xffffffffu, v, 2 * i + 1); }
    }
    const D2 &dF = cd[0], *dT = cd + 1, *dH = cd + 5;
    D2* dX = cd + 7;
#define CFENCE(n) sched_fence<n>((uint32_t)dF.a)
    cluster_wait();
    const uint32_t psb = uni(mapa(sb, rank ^ 1));
    if (ht == 0) OSTAMP(20);
    {
      const int m = lane >> 3, n1 = (w >> 1) * 8 + (lane & 7);
      const int rk = 17 * m + n1 + 1, rh = 17 * (12 + m) + n1, rv = 16 * m + n1;
      const uint32_t ka = rk * 32 + ((kap ^ (rk >> 2)) & 1) * 16, ha = rh * 32 + ((kap ^ (rh >> 2)) & 1) * 16;
      const uint32_t va = rv * 32 + ((kap ^ (rv >> 2)) & 1) * 16;
      const uint32_t po = sb + T_OFF + (w >> 1) * 2176;
      #pragma unroll 1
      for (int rd = 0; rd < 4; rd++) {
        const uint32_t kb = sb + M_OFF + (rd & 1) * KB, vb = sb + M_OFF + 2 * KB + (rd & 1) * 8192;
        const uint32_t xo = X_OFF + ((rd & 1) * 2 + (w >> 1)) * 1024 + (2 * rank + (rd >> 1)) * 256;
        const uint32_t xa = (kap == rank ? sb + xo + (lane & 7) * XS : po + (lane & 7) * 272) + m * 16;
        mbar_wait(bars + (B_STG + (rd & 1) * 2) * 8, rd >> 1);
        uint32_t kk[20], vv[16];
        const uint32_t zero = P.one - 1;
        ldsm4(kk, kb + ha);
        ldsm4(kk + 4, kb + ka);
        #pragma unroll
        for (int i = 0; i < 16; i++) {
          if ((i & 3) == 0 && i < 12) ldsm4(kk + 8 + i, kb + (ka ^ ((~i & 4) * 4)) + (i + 4) * 544 + (kk[i + 4] & zero));
          uint32_t t = bmul2(kk[i + 1], w3);
          t = badd2(t, bmul2(kk[i + 2], w2));
          t = badd2(t, bmul2(kk[i + 3], w1));
          kk[i] = badd2(t, bmul2(kk[i + 4], w0));
          asm volatile("" : "+r"(kk[i]));
        }
        mbar_wait(bars + (B_STG + (rd & 1) * 2 + 1) * 8, rd >> 1);
        ldsm4(vv, vb + va);
        #pragma unroll
        for (int i = 0; i < 16; i += 4) {
          if (i < 12) ldsm4(vv + 4 + i, vb + va + (i + 4) * 512 + (i == 4 ? vv[0] & zero : 0));
          stsm4t(xa + (i >> 2) * 64, bmul2(kk[i], vv[i]), bmul2(kk[i + 1], vv[i + 1]), bmul2(kk[i + 2], vv[i + 2]), bmul2(kk[i + 3], vv[i + 3]));
        }
        if (rd < 2) {
          fence_async_smem();
          __syncwarp();
          mbar_arrive(bars + (B_SFREE + (rd & 1)) * 8);
        }
        __syncwarp();
        if (kap != rank) {
          #pragma unroll
          for (int i = 0; i < 4; i++) lds128(vv + 4 * i, po + (2 * i + (lane >> 4)) * 272 + (lane & 15) * 16);
          #pragma unroll
          for (int i = 0; i < 4; i++)
            st_async128(psb + xo + (2 * i + (lane >> 4)) * XS + (lane & 15) * 16, psb + BAR_OFF + B_X * 8, vv[4 * i], vv[4 * i + 1], vv[4 * i + 2], vv[4 * i + 3]);
          __syncwarp();
        }
      }
    }
    bar_sync(3, 128);
    if (w == 0) mbar_expect_tx(bars + B_X * 8, 16384);
    {
      constexpr int NC = 8;
      Tmp t; t.t0 = 0.f; t.t1 = 0.f;
      asm volatile("setp.ne.b32 p_one, %0, 0;" :: "r"(lds32(sb + F_OFF)));
      float ra[32], lo[32], hi[32];
      uint32_t fa[2][2][4], fb[2][2][4];
      const uint32_t ta = sb + T_OFF + w * 2048 + lane * 16;
      const uint32_t y0 = rank ? psb : sb, y1 = rank ? sb : psb;
      auto fin = [&](int ch) {
        if (ch > 0) mbar_wait(bars + (B_YR + ch - 1) * 8, 0);
        finish(t, ra, ch, ht, rank, y0, y1);
      };
      auto load_h = [&](int i) {
        mbar_expect_tx(bars + B_H * 8, 4096);
        tma2d(sb + H_OFF, &mH, 0, (cp * 16 + rank * 8 + i) * 128, bars + B_H * 8);
      };
      auto skip = [&](int i) {
        const float dn = __uint_as_float(lds32(sb + D_OFF + i * 4));
        return dn;
      };
      mbar_wait(bars + B_H * 8, 0);
      wg_fence();
      dft32_h(lo, dH);
      mbar_wait(bars + B_X * 8, 0);
      fence_async_smem();
      if (ht == 0) OSTAMP(21);
      wg_fence();
      dft32_x(hi, dX);
      float dn = skip(0);
      wg_wait<1>(); pinv<32>(lo);
      if (w == 0) load_h(1);
      pack_fwd(fa, lo); CFENCE(0); rot_fwd(fa, tw); CFENCE(1);
      wg_wait<0>(); pinv<32>(hi);
      pack_fwd(fb, hi); CFENCE(2); rot_fwd(fb, tw); CFENCE(3);
      wg_fence();
      dft16h(hi, fb[1], dF); dft16h(hi + 16, fa[1], dF); dft16h(lo, fb[0], dF); dft16h(lo + 16, fa[0], dF);
      wg_commit();
      wg_wait<0>(); pinv<32>(lo); pinv<32>(hi);
#define CSTAMP(n) do {} while (0)
      #pragma unroll 1
      for (int i = 0;; i++) {
        CSTAMP(0);
        add_skip(lo + 16, dn);
        prod<1, 0, FG>(t, fa[1], lo, hi);
        CFENCE(4);
        CSTAMP(1);
        fence_async_smem();
        bar_sync(3, 128);
        CSTAMP(2);
        float rg[32];
        if (DRY) idft32(rg, dT); else { wg_fence(); ss64x4(rg, dT, i); }
        CFENCE(5);
        CSTAMP(3);
        const uint32_t yr = bars + (i < 2 ? B_X : B_YR + i - 2) * 8;
        const uint32_t oky = mbar_try(yr, 0);
        dn = skip(i + 1);
        prod<1, FG, 8>(t, fa[1], lo, hi);
        pinv<32>(lo);
        if (!oky) mbar_wait(yr, 0);
        CSTAMP(4);
        wg_wait<0>(); pinv<32>(rg);
        if (i > 0) finish(t, rg, i - 1, ht, rank, y0, y1);
        if (i == NC - 1) break;
        CSTAMP(5);
        wg_fence();
        dft32_x<false>(hi, dX);
        if (HINT & 1) { asm volatile("@!p_one mov.b32 %0, %1;" : "+f"(t.t1) : "f"(rg[0])); if (SF & 16) CFENCE(6); wg_fence(); }
        dft16h(ra + 16, fa[1], dF);
        wg_commit();
        CFENCE(7);
        CSTAMP(6);
        const uint32_t okh = mbar_try(bars + B_H * 8, (i + 1) & 1);
        prod<0>(t, fa[0], lo, lo);
        if ((AB & 128) && i == 4) mbar_wait(bars + B_GO * 8, 0);
        if (!okh) mbar_wait(bars + B_H * 8, (i + 1) & 1);
        CSTAMP(7);
        wg_fence();
        dft32_h<false>(lo, dH);
        if (HINT & 2) { asm volatile("@!p_one mov.b32 %0, %1;" : "+f"(t.t0) : "f"(rg[31])); if (SF & 8) CFENCE(8); wg_fence(); }
        dft16h(ra, fa[0], dF);
        wg_commit();
        wg_wait<1>(); pinv<32>(hi);
        if (ht == 64) OSTAMP(22 + i);
        CSTAMP(8);
        pack_fwd(fb, hi); CFENCE(9); rot_fwd(fb, tw); CFENCE(10);
        CSTAMP(9);
        wg_wait<0>(); pinv<32>(lo); pinv<32>(ra);
        CSTAMP(10);
        if (w == HW && i < NC - 2) load_h(i + 2);
        pack_fwd(fa, lo);
        if (SF & 32) CFENCE(11);
        wg_fence();
        dft16h(hi, fb[1], dF); dft16h(lo, fb[0], dF);
        wg_commit();
        CFENCE(12);
        rot_fwd(fa, tw);
        uint32_t u[2][2][4];
        if (CX) { CFENCE(13); pack_inv(u, ra); }
        if (SF & 64) CFENCE(14);
        CSTAMP(11);
        wg_fence();
        dft16h(hi + 16, fa[1], dF); dft16h(lo + 16, fa[0], dF);
        wg_commit();
        CFENCE(15);
        CSTAMP(12);
        if (!CX) { pack_inv(u, ra); CFENCE(13); }
        rot_inv(u, tw, ta);
        CSTAMP(13);
        if (SF & 1) CFENCE(16);
        wg_wait<0>(); pinv<32>(lo); pinv<32>(hi);
        CSTAMP(14);
      }
      wg_fence();
      dft16h(hi + 16, fa[1], dF);
      wg_commit();
      CFENCE(17);
      prod<0>(t, fa[0], lo, lo);
      CFENCE(18);
      wg_fence();
      dft16h(hi, fa[0], dF);
      wg_commit();
      if (ht == 64) OSTAMP(29);
      wg_wait<0>(); pinv<32>(hi);
      pack_inv(fb, hi); CFENCE(19); rot_inv(fb, tw, ta);
      fence_async_smem();
      bar_sync(3, 128);
      idft32(ra, dT);
      const int l3 = fresh_tid() & 31;
      uint32_t qa = sb + M_OFF + ((l3 >> 4) * 512 + w * 128 + (l3 & 8) + ((l3 >> 2) & 1) + (l3 & 2)) * 32 + (l3 & 1) * 16;
      uint32_t yb = sb + X_OFF + (l3 & 1) * (XS + 16) + w * 512
                    + (((l3 >> 1) & 1) == rank ? (l3 >> 2) * 16 : YX - XS + ((l3 >> 2) ^ 4) * 16);
      mbar_wait(bars + B_Q * 8, 0);
      wg_wait<0>(); pinv<32>(ra);
      fin(NC - 1);
      if (ht == 64) OSTAMP(30);
      uint32_t t0 = 0, dt = 0;
      #pragma unroll 1
      for (int sg = 0; sg < 4; sg++, qa += 1024, yb += 128) {
        uint32_t qv[4][4], yv[4][4];
        #pragma unroll
        for (int i = 0; i < 4; i++) lds128(qv[i], qa + (i >> 1) * 512 + (i & 1) * 128);
        #pragma unroll
        for (int m = 0; m < 4; m++) {
          if (m == 3 && sg == 0) mbar_wait(bars + (B_YR + NC - 1) * 8, 0);
          ldsm4t(yv[m], yb + 2 * m * XS);
        }
        #pragma unroll
        for (int i = 0; i < 4; i++)
          sts128(qa + (i >> 1) * 512 + (i & 1) * 128, bmul2(qv[i][0], yv[0][i]), bmul2(qv[i][1], yv[1][i]), bmul2(qv[i][2], yv[2][i]), bmul2(qv[i][3], yv[3][i]));
        if (sg == 3) mbar_arrive(bars + B_CD * 8);
        fence_async_smem();
        __syncwarp();
        if (sg == 0) {
          mbar_wait(bars + B_GO * 8, 0);
          t0 = uni((uint32_t)clock());
          dt = uni(min(max((int)(lds32(sb + D_OFF + 44) + OA_END - t0) >> 2, 4 * OA_MIN), 4 * OA_MAX));
          t0 += w * (dt >> 2);
        }
        pace(t0, dt);
        #pragma unroll
        for (int hf = 0; hf < 2; hf++) {
          const int r = w * 128 + sg * 32 + hf * 512;
          if (!(AB & 2)) tma2d_store(&mOutA, cp * 16, rank * 1024 + r, sb + M_OFF + r * 32);
        }
      }
      bulk_commit(); bulk_wait_read();
      if (ht == 0) OSTAMP(31);
    }
  } else {
    asm volatile("setmaxnreg.dec.sync.aligned.u32 %0;" :: "n"(32));
    const uint32_t id2 = fresh(ids); IDS(id2);
    const uint32_t t_pf = (uint32_t)clock();
    if (warp == 14)
      asm volatile("prefetch.global.L2 [%0];" :: "l"(((lane & 1) ? P.v : P.k) + (rank * 2097152 + cp * 32 + (lane >> 1) * 131072)));
    if (warp != 15) cluster_wait();
    auto reduce_kv = [&](int i0, int i1) {
      float* kr = P.kv + hp * KV_PER_HP;
      mbar_wait(bars + B_Z * 8, 0);
      bar_sync(4, 352);
      #pragma unroll 1
      for (; i0 < i1; i0 += 2) {
        uint32_t p[2][4], q[2][4];
        const int i = (i0 + 2 * mb) & 15;
        const uint32_t pa = sb + M_OFF + (i & 3) * 2048 + (i >> 2) * 512 + (lane & 7) * 64 + (((lane >> 3) ^ (lane >> 1)) & 3) * 16;
        lds128(p[0], pa); lds128(q[0], pa + VT); lds128(p[1], pa + 2048); lds128(q[1], pa + VT + 2048);
        #pragma unroll
        for (int j = 0; j < 2; j++)
          asm volatile("red.relaxed.gpu.global.add.v4.f32 [%0], {%1,%2,%3,%4};" :: "l"(kr + (i >> 3) * 32 + (i + j) * 128 + lane * 4),
            "f"(__uint_as_float(p[j][0]) + __uint_as_float(q[j][0])), "f"(__uint_as_float(p[j][1]) + __uint_as_float(q[j][1])),
            "f"(__uint_as_float(p[j][2]) + __uint_as_float(q[j][2])), "f"(__uint_as_float(p[j][3]) + __uint_as_float(q[j][3])) : "memory");
      }
      if (i1 == 4) {
        const uint32_t za = sb + M_OFF + 8192 + lane * 4;
        #pragma unroll
        for (int h = 0; h < 2; h++)
          asm volatile("red.relaxed.gpu.global.add.f32 [%0], %1;" :: "l"(kr + h * 1056 + 1024 + lane),
            "f"(__uint_as_float(lds32(za + h * 128)) + __uint_as_float(lds32(za + h * 128 + VT))) : "memory");
      }
      bar_sync(5, 96);
    };
    auto convert_kv = [&](int u0, auto N_) {
      constexpr int N = N_.value;
      const float* kg = P.kv + (2 * n2 + rank) * KV_PER_HP;
      const uint32_t psb = uni(mapa(sb, rank ^ 1));
      auto put = [&](uint32_t o, uint32_t v0, uint32_t v1, uint32_t v2, uint32_t v3) {
        st_async128(psb + o, psb + BAR_OFF + B_KVB * 8, v0, v1, v2, v3);
        sts128(sb + o, v0, v1, v2, v3);
      };
      mbar_wait(bars + B_KVL * 8, 0);
      spin_until(&P.cnt[(2 * n2 + rank) * 32 + 1], uni(lds32(sb + D_OFF + 40)) * 8);
      float4 v[N][2];
      float z[2];
      #pragma unroll
      for (int j = 0; j < N; j++) {
        const float4* kr = reinterpret_cast<const float4*>(kg + ((u0 + j) >> 2) * 32 + (u0 + j) * 256) + lane;
        v[j][0] = __ldcg(kr); v[j][1] = __ldcg(kr + 32);
      }
      if (N == 2) { z[0] = __ldcg(kg + 1024 + lane); z[1] = __ldcg(kg + 2080 + lane); }
      #pragma unroll
      for (int j = 0; j < N; j++)
        put(KVB_OFF + (rank * 8 + u0 + j) * 640 + lane * 16,
            pack_bf16(v[j][0].x, v[j][0].y), pack_bf16(v[j][0].z, v[j][0].w), pack_bf16(v[j][1].x, v[j][1].y), pack_bf16(v[j][1].z, v[j][1].w));
      if (N == 2) {
        #pragma unroll
        for (int h = 0; h < 2; h++) {
          const uint32_t zz = pack_bf16(z[h], z[h]);
          put(KVB_OFF + (rank * 8 + h * 4 + (lane >> 3)) * 640 + 512 + (lane & 7) * 16, zz, zz, zz, zz);
        }
      }
      fence_async_smem();
      __syncwarp();
      mbar_arrive(bars + B_KVB * 8);
    };
    if (warp == 12) {
      uint32_t xs = 0;
      auto load_x = [&](int k) {
        tma2d_mc(sb + xs * SLOT + rank * 16384, &mX, k, mb * 256 + rank * 128, bars + (B_XF + xs) * 8);
        mbar_expect_tx(bars + (B_XF + xs) * 8, SLOT);
        xs = xs == 2 ? 0 : xs + 1;
      };
      load_x(64); load_x(128);
      mbar_expect_tx(bars + B_Q * 8, 32768);
      #pragma unroll 1
      for (int it = 1; it < 8; it++) {
        #pragma unroll
        for (int j = 0; j < 4; j++) {
          mbar_wait(bars + (B_EMPTY + j) * 8, (it - 1) & 1);
          TSTAMP(1, 4 * it + j);
          tma3d(sb + W_OFF + j * 8192, &mW, hp * 64, it * 128 + j * 32, 1, bars + (B_FULL + j) * 8);
          if (j == 1 || (j == 3 && it < 7)) load_x(it * 128 + j * 32 + 32);
          mbar_expect_tx(bars + (B_FULL + j) * 8, 8192);
        }
      }
      #pragma unroll 1
      for (int it = 0; it < 4; it++) {
        #pragma unroll
        for (int j = 0; j < 4; j++) {
          const uint32_t fb = bars + (B_FULL2 + j) * 8;
          if (j || it) mbar_wait(bars + (it ? B_EMPTY2 + j : B_EMPTY + (j | 1)) * 8, (it - 1) & 1);
          TSTAMP(5, 4 * it + j);
          tma2d_mc(sb + j * SLOT + 16384 + rank * 8192, &mWq, n2 * 128 + rank * 64, it * 256 + j * 64, fb);
          tma2d(sb + j * SLOT, &mX, it * 256 + j * 64, m2 * 128, fb);
          mbar_expect_tx(fb, SLOT);
          const int pc = 4 * it + j - Q_ST;
          if (pc >= 0) {
            mbar_wait(bars + B_MF * 8, 0);
            tma2d(sb + M_OFF + pc * 4096, &mQ, cp * 16, rank * 1024 + pc * 128, bars + B_Q * 8);
          }
        }
      }
      #pragma unroll 1
      for (int pc = 16 - Q_ST; pc < 8; pc++) tma2d(sb + M_OFF + pc * 4096, &mQ, cp * 16, rank * 1024 + pc * 128, bars + B_Q * 8);
      #pragma unroll 1
      for (int it = 0; it < 4; it++) {
        #pragma unroll
        for (int j = 0; j < 4; j++) {
          const uint32_t fb = bars + (B_FULL2 + j) * 8, k = fresh(g2_k(4 * it + j, n2) * 64);
          mbar_wait(bars + (B_EMPTY2 + j) * 8, (it - 1) & 1);
          TSTAMP(5, 16 + 4 * it + j);
          tma2d_mc(sb + j * SLOT + 16384 + rank * 8192, &mWo, n2 * 128 + rank * 64, k, fb);
          mbar_expect_tx(fb, 16384);
        }
        if (it == 0) mbar_arrive(bars + B_QE * 8);
      }
    } else if (warp == 13) {
      if ((sb & 0xffffff) != SB0) __trap();
      float4* zp = reinterpret_cast<float4*>(P.kv + hp * KV_PER_HP + mb * 264);
      const float4 z4 = make_float4(0.f, 0.f, 0.f, 0.f);
      zp[lane] = z4; zp[lane + 32] = z4;
      if (lane < 2) zp[lane + 64] = z4;
      if (lane == 0) P.cnt[hp * 32 + 8 + mb] = t_pf;
      if (SPEC) {
        uint4* op = P.o + m2 * 16384 + mb * (SPEC * 256) + lane;
        uint32_t t0 = t_pf + RS_T0 + mb * (RS_DT / 8);
        #pragma unroll 1
        for (int i = 0; i < 8; i++) {
          while ((int)((uint32_t)clock() - t0) < 0) __nanosleep(100);
          t0 += RS_DT;
          #pragma unroll
          for (int j = 0; j < SPEC; j++) op[(i * SPEC + j) * 32] = make_uint4(~0u, ~0u, ~0u, ~0u);
        }
      }
      fence_gpu();
      __syncwarp();
      unsigned gen = 0;
      if (lane == 0) gen = (atomicAdd(&P.cnt[hp * 32], 1u) >> 3) + 1;
      gen = uni(gen);
      sts32(sb + D_OFF + 40, gen);
      spin_until(&P.cnt[hp * 32], gen * 8);
      sts32(sb + D_OFF + 48, __ballot_sync(0xffffffffu, NEAR && __ldcg(&P.cnt[hp * 32 + 8 + (lane & 7)]) - t_pf + 4096 >= 8192));
      mbar_arrive(bars + B_Z * 8);
      reduce_kv(0, 4);
      mbar_arrive(mapa(bars, rank ^ 1) + B_KVL * 8);
      mbar_arrive(bars + B_MF * 8);
      OSTAMP(17);
      fence_gpu();
      red_add(&P.cnt[hp * 32 + 1]);
      OSTAMP(15);
      convert_kv(0, IC<2>());
      bar_sync(6, 288);
      fence_gpu();
      asm volatile(ELECT "st.relaxed.gpu.global.u32 [%0], %1;\n}" :: "l"(&P.cnt[(16 + m2) * 32 + n2]), "r"(gen) : "memory");
      OSTAMP(32);
    } else {
      if (warp == 14) {
        uint32_t t0 = t_pf + STG_T0;
        #pragma unroll 1
        for (int pc = 0; pc < 16; pc++) {
          const int rd = pc >> 2, u = pc & 3;
          const uint32_t gb = bars + (B_STG + (rd & 1) * 2 + (u >> 1)) * 8;
          if (pc == 8 || pc == 12) mbar_wait(bars + (B_SFREE + (rd & 1)) * 8, 0);
          if (!(u & 1)) mbar_expect_tx(gb, u ? 8192 : KB);
          pace(t0, STG_DT);
          TSTAMP(3, 16 + pc);
          tma3d(sb + M_OFF + (u < 2 ? (rd & 1) * KB + u * (KB / 2) : 2 * KB + (rd & 1) * 8192 + (u & 1) * 4096), u < 2 ? &mK : &mV,
                cp * 16, rank * 64 + rd * 16 - (u < 2), (u & 1) * 8, gb);
        }
        mbar_expect_tx(bars + B_H * 8, 4096);
        tma2d(sb + H_OFF, &mH, 0, (cp * 16 + rank * 8) * 128, bars + B_H * 8);
      }
      if (warp == 15) {
        uint32_t t0 = t_pf + b * 2;
        #pragma unroll 1
        for (int i = 0; i < PF_N; i++) {
          const int u = P.pf[i];
          const PfType& f = P.pt[u >> 4];
          pace(t0, i == 0 ? PF_DT0 : (i < PF_N1 ? PF_DT1 : PF_DT2));
          asm volatile("prefetch.global.L2 [%0];" :: "l"(f.base + ((g & 3) * f.gl + (g >> 2) * f.gh + mb * f.sp + rank * f.sr + (u & 15) * f.su
                                                                   + (lane >> 2) * f.l4 + ((lane >> 1) & 1) * f.l2 + (lane & 1) * 128)));
        }
        cluster_wait();
      }
      reduce_kv(warp * 6 - 80, warp * 6 - 74);
      convert_kv(warp * 3 - 40, IC<3>());
      {
        const int wg = 15 - warp;
        const unsigned gen = uni(lds32(sb + D_OFF + 40));
        const uint32_t ab = bars + B_FA * 8 + wg * 32, far = uni(lds32(sb + D_OFF + 48));
        const unsigned* fp = &P.cnt[SPEC ? (32 + m2 * 2 + wg) * 32 + lane : (16 + m2) * 32 + (lane >> 2)];
        uint32_t miss = ~0u, safe = t_pf;
        auto poll = [&]() {
          unsigned v;
          asm volatile("ld.relaxed.gpu.global.u32 %0, [%1];" : "=r"(v) : "l"(fp) : "memory");
          miss = __ballot_sync(0xffffffffu, v != gen);
        };
        mbar_arrive(ab); mbar_arrive(ab + 8);
        mbar_wait(bars + B_QE * 8, 0);
        #pragma unroll 1
        for (int st = 2; st < 16; st += 2) {
          const int k = g2_k(st, n2), j = st & 3;
          const uint4* src = P.o + (m2 * 16 + k) * 1024 + wg * 512;
          const uint32_t eb = bars + (B_EMPTY2 + j) * 8, ph = ((st >> 2) - 1) & 1, dst = sb + j * SLOT + wg * 8192;
          if (!(AB & 4) && ((miss >> (2 * k)) & 15)) {
            #pragma unroll 1
            for (int n = 0; n < WAIT_BOUND && ((miss >> (2 * k)) & 15); n++) poll();
            if (!SPEC) asm volatile("fence.acquire.gpu;" ::: "memory");
            fence_async_global();
            safe = (uint32_t)clock() + FAR_DT;
          }
          if (st >= 4) {
            if ((far >> (k >> 1)) & 1) while ((int)(uni((uint32_t)clock()) - safe) < 0) {}
            mbar_wait(eb, ph);
          }
          bulk_load(dst, src, 8192, ab + j * 8);
          mbar_expect_tx(ab + j * 8, 8192);
          if (st >= 4) mbar_wait(eb + 8, ph);
          bulk_load(dst + SLOT, src + 1024, 8192, ab + j * 8 + 8);
          mbar_expect_tx(ab + j * 8 + 8, 8192);
          if (st == 2) { OSTAMP(18 + wg * 15); if (wg) { sts32(sb + D_OFF + 44, (uint32_t)clock()); mbar_arrive(bars + B_GO * 8); } }
        }
      }
    }
  }
}

typedef CUresult (*EncodeFn)(CUtensorMap*, CUtensorMapDataType, cuuint32_t, void*, const cuuint64_t*, const cuuint64_t*,
                             const cuuint32_t*, const cuuint32_t*, CUtensorMapInterleave, CUtensorMapSwizzle,
                             CUtensorMapL2promotion, CUtensorMapFloatOOBfill);

void encode(EncodeFn fn, CUtensorMap* m, const void* ptr, int rank, const cuuint64_t* dims, const cuuint64_t* strides,
            const cuuint32_t* box, CUtensorMapSwizzle sw, CUtensorMapL2promotion pr) {
  const cuuint32_t es[3] = {1, 1, 1};
  fn(m, CU_TENSOR_MAP_DATA_TYPE_BFLOAT16, rank, const_cast<void*>(ptr), dims, strides, box, es,
     CU_TENSOR_MAP_INTERLEAVE_NONE, sw, pr, CU_TENSOR_MAP_FLOAT_OOB_FILL_NONE);
}

}

extern "C" void kernel_launch(void* const* d_in, const int* in_sizes, int n_in, void* d_out, int out_size) {
  (void)in_sizes; (void)n_in; (void)out_size;
  static EncodeFn fn = nullptr;
  static void *po, *pkv, *pcnt;
  if (!fn) {
    void* p = nullptr; cudaDriverEntryPointQueryResult qr;
    cudaGetDriverEntryPoint("cuTensorMapEncodeTiled", &p, cudaEnableDefault, &qr);
    fn = (EncodeFn)p;
    cudaGetSymbolAddress(&po, g_O); cudaGetSymbolAddress(&pkv, g_kv); cudaGetSymbolAddress(&pcnt, g_cnt);
    cudaFuncSetAttribute(fused_kernel, cudaFuncAttributeMaxDynamicSharedMemorySize, SMEM_BYTES);
  }
  const CUtensorMapL2promotion P128 = CU_TENSOR_MAP_L2_PROMOTION_L2_128B, P0 = CU_TENSOR_MAP_L2_PROMOTION_NONE;
  CUtensorMap mX, mW, mWq, mWo, mK, mV, mH, mQ, mOut, mOutA;
  { cuuint64_t d[2] = {1024, 2048}, s[1] = {2048}; cuuint32_t bx[2] = {64, 128}, bq[2] = {16, 128};
    encode(fn, &mX, d_in[6], 2, d, s, bx, CU_TENSOR_MAP_SWIZZLE_128B, P128);
    encode(fn, &mQ, d_in[0], 2, d, s, bq, CU_TENSOR_MAP_SWIZZLE_NONE, P128); }
  { cuuint64_t d[3] = {1024, 1024, 3}, s[2] = {6144, 2048}; cuuint32_t bx[3] = {64, 32, 2};
    encode(fn, &mW, d_in[7], 3, d, s, bx, CU_TENSOR_MAP_SWIZZLE_128B, P128); }
  { cuuint64_t d[2] = {1024, 1024}, s[1] = {6144}, so[1] = {2048}; cuuint32_t bx[2] = {64, 64};
    encode(fn, &mWq, d_in[7], 2, d, s, bx, CU_TENSOR_MAP_SWIZZLE_128B, P128);
    encode(fn, &mWo, d_in[8], 2, d, so, bx, CU_TENSOR_MAP_SWIZZLE_128B, P128); }
  { cuuint64_t d[3] = {1024, 128, 16}, s[2] = {32768, 2048}; cuuint32_t bk[3] = {16, 17, 8}, bv[3] = {16, 16, 8};
    encode(fn, &mK, d_in[1], 3, d, s, bk, CU_TENSOR_MAP_SWIZZLE_32B, P128);
    encode(fn, &mV, d_in[2], 3, d, s, bv, CU_TENSOR_MAP_SWIZZLE_32B, P128); }
  { cuuint64_t d[2] = {16, 131072}, s[1] = {32}; cuuint32_t bx[2] = {16, 128};
    encode(fn, &mH, d_in[4], 2, d, s, bx, CU_TENSOR_MAP_SWIZZLE_32B, CU_TENSOR_MAP_L2_PROMOTION_L2_256B); }
  { cuuint64_t d[2] = {2048, 2048}, s[1] = {4096}; cuuint32_t bx[2] = {64, 16}, ba[2] = {16, 32};
    encode(fn, &mOut, d_out, 2, d, s, bx, CU_TENSOR_MAP_SWIZZLE_128B, P0);
    encode(fn, &mOutA, d_out, 2, d, s, ba, CU_TENSOR_MAP_SWIZZLE_NONE, P0); }
  Params P;
  P.shift = (const __nv_bfloat16*)d_in[3]; P.ssmD = (const __nv_bfloat16*)d_in[5];
  P.x = (const __nv_bfloat16*)d_in[6]; P.w = (const __nv_bfloat16*)d_in[7]; P.out = (__nv_bfloat16*)d_out; P.one = 1;
  P.o = (uint4*)po; P.kv = (float*)pkv; P.cnt = (unsigned*)pcnt;
  P.k = (const char*)d_in[1]; P.v = (const char*)d_in[2];
  P.pt[0] = {(const char*)d_in[6], 16 * 32768, 64 * 32768, 65536, 32768, 256, 4096, 2048};
  P.pt[1] = {(const char*)d_in[7] + 2048, 256, 1024, 16 * 6144, 8 * 6144, 128 * 6144, 6144, 2048};
  P.pt[2] = {(const char*)d_in[7], 512, 128 * 6144, 16 * 6144, 8 * 6144, 256 * 6144, 6144, 256};
  P.pt[3] = {(const char*)d_in[8], 512, 128 * 2048, 16 * 2048, 8 * 2048, 256 * 2048, 2048, 256};
  P.pt[4] = {(const char*)d_in[0], 256, 1024, 32768, 2097152, 262144, 4096, 2048};
  P.pt[5] = {(const char*)d_in[4], 16 * 32768, 64 * 32768, 65536, 32768, 4096, 512, 256};
  const uint8_t pf[32] = {PF_LIST};
  for (int i = 0; i < 32; i++) P.pf[i] = pf[i];
  const uint64_t cd[18] = {CONV_DESC};
  for (int i = 0; i < 18; i++) P.cd[i] = cd[i];
  fused_kernel<<<NCTA, NTHREADS, SMEM_BYTES, cudaStreamPerThread>>>(P, mX, mW, mWq, mWo, mK, mV, mH, mQ, mOut, mOutA);
}
```

```cpp
#include <cuda_runtime.h>
#include <cuda_bf16.h>
#include <cuda.h>
#include <stdint.h>

#define PARAM(name, value) constexpr int name = value
#define TUNE
namespace dflt {
PARAM(SK1, 2); PARAM(SK2, 3); PARAM(SK3, 2);
PARAM(OWNL, 1); PARAM(OCP, 1); PARAM(SMAP, 1); PARAM(NEAR, 1); PARAM(FAR_DT, 500); PARAM(SPEC, 8); PARAM(RS_T0, 12000); PARAM(RS_DT, 1000); PARAM(CI, 1); PARAM(CW, 2); PARAM(SF, 97); PARAM(CX, 1); PARAM(DRY, 0); PARAM(FG, 2); PARAM(HINT, 0); PARAM(HW, 0); PARAM(AB, 0); PARAM(EHI, 0); PARAM(MID, 3);
PARAM(STG_T0, 1300); PARAM(STG_DT, 540);
PARAM(Q_ST, 10);
PARAM(OA_END, 7400); PARAM(OA_MIN, 200); PARAM(OA_MAX, 450);
PARAM(PF_DT0, 200); PARAM(PF_DT1, 1060); PARAM(PF_DT2, 512); PARAM(PF_N1, 9);
}
#define PF_LIST 0x01, 0x11, 0x02, 0x12, 0x03, 0x13, 0x04, 0x14, 0x05, 0x15, 0x51, 0x06, 0x16, 0x20, 0x07, 0x17, 0x21, 0x22, 0x23, \
                0x40, 0x41, 0x42, 0x43, 0x44, 0x45, 0x46, 0x47, 0x30, 0x31, 0x32, 0x33
#define PF_N 31
#define WAIT_BOUND 262144

namespace {
using namespace dflt;
TUNE

constexpr int S_LEN = 2048;
constexpr int DM    = 1024;
constexpr int NCTA  = 128;
constexpr int NTHREADS = 512;
constexpr int SLOT  = 32768;
constexpr int W_OFF = 3 * SLOT;
constexpr int M_OFF = 4 * SLOT;
constexpr int VT    = 16 * 1152;
constexpr int T_OFF = M_OFF + 43008;
constexpr int XS    = 4096 + 16;
constexpr int YX    = 2048 + 16;
constexpr int X_OFF = T_OFF + 8192 + 2176;
constexpr int H_OFF = X_OFF + 8 * XS;
constexpr int A_OFF = H_OFF + 4096;
constexpr int F_OFF = A_OFF + 8192;
constexpr int BAR_OFF = F_OFF + 2048;
constexpr int D_OFF = BAR_OFF + 384;
constexpr int SMEM_BYTES = D_OFF + 64 + 256;
constexpr int KB = 8704;
constexpr int KVB_OFF = M_OFF + 32768;
static_assert(H_OFF % 256 == 0 && X_OFF % 128 == 0 && SMEM_BYTES <= 232448, "layout");
constexpr int B_XF = 0, B_F0 = 3, B_FULL = 4, B_FA = 4, B_FULL2 = 25, B_KVL = 24, B_STG = 8, B_X = 12, B_Z = 13, B_H = 14, B_Q = 15, B_YR = 16,
              B_SK = 29, B_GO = 30, B_QE = 31,
              B_EMPTY = 32, B_KVB = 36, B_EMPTY2 = 37, B_SFREE = 41, B_CD = 43, B_MF = 44, B_OD = 45;
constexpr int KV_PER_HP = 2 * 1056;

__device__ __align__(1024) uint4 g_O[S_LEN * DM / 8];
__device__ __align__(128) float g_kv[16 * KV_PER_HP];
__device__ __align__(128) unsigned g_cnt[64 * 32];

#define OSTAMP(i) do {} while (0)
#define TSTAMP(k, i) do {} while (0)

__device__ __forceinline__ uint32_t cta_ids() {
  uint32_t b = blockIdx.x;
  if (SMAP) { asm("mov.u32 %0, %%smid;" : "=r"(b)); b = b >= 124 ? b - 124 : b + 8; }
  const uint32_t c = b >> 1, q = ((c - 36) * 37) >> 8;
  const uint32_t lo = (4 + c) << 12, mid = (((c - 4) & 7) << 8) + (((c - 4) >> 3) << 12), hi = ((c - 35) << 8) + q * (4096 - 7 * 256) + (4 << 12);
  uint32_t r;
  asm("{\n.reg .pred p, q;\nsetp.lt.u32 p, %4, 4;\nsetp.lt.u32 q, %4, 36;\nselp.u32 %0, %2, %3, q;\nselp.u32 %0, %1, %0, p;\n}" : "=&r"(r) : "r"(lo), "r"(mid), "r"(hi), "r"(c));
  return r + b;
}

#define ELECT "{\n.reg .pred e;\nelect.sync _|e, 0xffffffff;\n@e "
__device__ __forceinline__ uint32_t uni(uint32_t v) { return __shfl_sync(0xffffffffu, v, 0); }
__device__ __forceinline__ uint32_t fresh(uint32_t v) { asm volatile("" : "+r"(v)); return v; }
__device__ __forceinline__ uint32_t smem_u32(const void* p) { return (uint32_t)__cvta_generic_to_shared(p); }
__device__ __forceinline__ void mbar_init(uint32_t b, uint32_t c) { asm volatile(ELECT "mbarrier.init.shared::cta.b64 [%0], %1;\n}" :: "r"(b), "r"(c) : "memory"); }
__device__ __forceinline__ void mbar_expect_tx(uint32_t b, uint32_t bytes) { asm volatile(ELECT "mbarrier.arrive.expect_tx.shared::cta.b64 _, [%0], %1;\n}" :: "r"(b), "r"(bytes) : "memory"); }
__device__ __forceinline__ void mbar_arrive(uint32_t b) { asm volatile(ELECT "mbarrier.arrive.shared::cluster.b64 _, [%0];\n}" :: "r"(b) : "memory"); }
__device__ __forceinline__ void mbar_wait(uint32_t b, uint32_t ph) {
  asm volatile("{\n.reg .pred p;\n.reg .u32 n;\nmov.u32 n, 0;\n"
    "WAIT_LOOP:\nmbarrier.try_wait.parity.shared::cta.b64 p, [%0], %1;\n@p bra.uni WAIT_DONE;\n"
    "add.u32 n, n, 1;\nsetp.lt.u32 p, n, %2;\n@p bra.uni WAIT_LOOP;\nWAIT_DONE:\n}" :: "r"(b), "r"(ph), "n"(WAIT_BOUND) : "memory"); }
__device__ __forceinline__ void tma2d(uint32_t dst, const CUtensorMap* m, int c0, int c1, uint32_t bar) {
  asm volatile(ELECT "cp.async.bulk.tensor.2d.shared::cluster.global.mbarrier::complete_tx::bytes [%0], [%1, {%3, %4}], [%2];\n}"
    :: "r"(dst), "l"(m), "r"(bar), "r"(c0), "r"(c1) : "memory"); }
__device__ __forceinline__ void tma2d_mc(uint32_t dst, const CUtensorMap* m, int c0, int c1, uint32_t bar) {
  asm volatile(ELECT "cp.async.bulk.tensor.2d.shared::cluster.global.mbarrier::complete_tx::bytes.multicast::cluster [%0], [%1, {%3, %4}], [%2], %5;\n}"
    :: "r"(dst), "l"(m), "r"(bar), "r"(c0), "r"(c1), "h"((uint16_t)3) : "memory"); }
__device__ __forceinline__ void tma3d(uint32_t dst, const CUtensorMap* m, int c0, int c1, int c2, uint32_t bar) {
  asm volatile(ELECT "cp.async.bulk.tensor.3d.shared::cluster.global.mbarrier::complete_tx::bytes [%0], [%1, {%3, %4, %5}], [%2];\n}"
    :: "r"(dst), "l"(m), "r"(bar), "r"(c0), "r"(c1), "r"(c2) : "memory"); }
__device__ __forceinline__ void tma2d_store(const CUtensorMap* m, int c0, int c1, uint32_t src) {
  asm volatile(ELECT "cp.async.bulk.tensor.2d.global.shared::cta.bulk_group [%0, {%2, %3}], [%1];\n}"
    :: "l"(m), "r"(src), "r"(c0), "r"(c1) : "memory"); }
__device__ __forceinline__ void bulk_load(uint32_t dst, const void* src, uint32_t bytes, uint32_t bar) {
  asm volatile(ELECT "cp.async.bulk.shared::cluster.global.mbarrier::complete_tx::bytes [%0], [%1], %2, [%3];\n}"
    :: "r"(dst), "l"(src), "r"(bytes), "r"(bar) : "memory"); }
__device__ __forceinline__ void bulk_commit() { asm volatile("cp.async.bulk.commit_group;" ::: "memory"); }
__device__ __forceinline__ void bulk_wait_read() { asm volatile("cp.async.bulk.wait_group.read 0;" ::: "memory"); }
__device__ __forceinline__ void fence_async_smem() { asm volatile("fence.proxy.async.shared::cta;" ::: "memory"); }
__device__ __forceinline__ void bar_sync(int id, int n) { asm volatile("bar.sync %0, %1;" :: "r"(id), "r"(n) : "memory"); }
__device__ __forceinline__ void bar_arrive(int id, int n) { asm volatile("bar.arrive %0, %1;" :: "r"(id), "r"(n) : "memory"); }
__device__ __forceinline__ void wg_fence() { asm volatile("wgmma.fence.sync.aligned;" ::: "memory"); }
__device__ __forceinline__ void wg_commit() { asm volatile("wgmma.commit_group.sync.aligned;" ::: "memory"); }
template <int N> __device__ __forceinline__ void wg_wait() { asm volatile("wgmma.wait_group.sync.aligned %0;" :: "n"(N) : "memory"); }
constexpr uint32_t SB0 = 1024;
__host__ __device__ constexpr uint64_t cdesc(uint32_t off, uint32_t lbo, uint32_t sbo, uint32_t swz) {
  return (uint64_t)((SB0 + off) >> 4) | ((uint64_t)(lbo >> 4) << 16) | ((uint64_t)(sbo >> 4) << 32) | ((uint64_t)swz << 62); }
__device__ __forceinline__ uint64_t dofs(uint64_t d, uint32_t bytes) { return (d & 0xffffffff00000000ull) | (uint32_t)((uint32_t)d + (bytes >> 4)); }
__device__ __forceinline__ uint32_t mbar_try(uint32_t b, uint32_t ph) {
  uint32_t ok;
  asm volatile("{\n.reg .pred p;\nmbarrier.test_wait.parity.shared::cta.b64 p, [%1], %2;\nselp.u32 %0, 1, 0, p;\n}" : "=r"(ok) : "r"(b), "r"(ph) : "memory");
  return ok; }
__device__ __forceinline__ void arrive_at(uint32_t a, bool on) {
  asm volatile("{\n.reg .pred p;\nsetp.ne.b32 p, %1, 0;\n@p mbarrier.arrive.shared::cluster.b64 _, [%0];\n}" :: "r"(a), "r"((uint32_t)on) : "memory"); }
__device__ __forceinline__ void ldsm4(uint32_t* r, uint32_t a) {
  asm volatile("ldmatrix.sync.aligned.m8n8.x4.shared.b16 {%0,%1,%2,%3}, [%4];" : "=r"(r[0]), "=r"(r[1]), "=r"(r[2]), "=r"(r[3]) : "r"(a) : "memory"); }
__device__ __forceinline__ void ldsm4t(uint32_t* r, uint32_t a) {
  asm volatile("ldmatrix.sync.aligned.m8n8.x4.trans.shared.b16 {%0,%1,%2,%3}, [%4];" : "=r"(r[0]), "=r"(r[1]), "=r"(r[2]), "=r"(r[3]) : "r"(a) : "memory"); }
__device__ __forceinline__ void stsm4(uint32_t a, uint32_t r0, uint32_t r1, uint32_t r2, uint32_t r3) {
  asm volatile("stmatrix.sync.aligned.m8n8.x4.shared.b16 [%0], {%1,%2,%3,%4};" :: "r"(a), "r"(r0), "r"(r1), "r"(r2), "r"(r3) : "memory"); }
__device__ __forceinline__ void stsm4t(uint32_t a, uint32_t r0, uint32_t r1, uint32_t r2, uint32_t r3) {
  asm volatile("stmatrix.sync.aligned.m8n8.x4.trans.shared.b16 [%0], {%1,%2,%3,%4};" :: "r"(a), "r"(r0), "r"(r1), "r"(r2), "r"(r3) : "memory"); }
__device__ __forceinline__ uint32_t lds32(uint32_t a) { uint32_t v; asm volatile("ld.shared.b32 %0, [%1];" : "=r"(v) : "r"(a) : "memory"); return v; }
__device__ __forceinline__ void lds128(uint32_t* v, uint32_t a) { asm volatile("ld.shared.v4.b32 {%0,%1,%2,%3}, [%4];" : "=r"(v[0]), "=r"(v[1]), "=r"(v[2]), "=r"(v[3]) : "r"(a) : "memory"); }
__device__ __forceinline__ void sts32(uint32_t a, uint32_t v) { asm volatile("st.shared.b32 [%0], %1;" :: "r"(a), "r"(v) : "memory"); }
__device__ __forceinline__ void sts128(uint32_t a, uint32_t v0, uint32_t v1, uint32_t v2, uint32_t v3) {
  asm volatile("st.shared.v4.b32 [%0], {%1,%2,%3,%4};" :: "r"(a), "r"(v0), "r"(v1), "r"(v2), "r"(v3) : "memory"); }
__device__ __forceinline__ uint32_t pack_bf16(float lo, float hi) { uint32_t r; asm("cvt.rn.bf16x2.f32 %0, %1, %2;" : "=r"(r) : "f"(hi), "f"(lo)); return r; }
template <int ID = 0> __device__ __forceinline__ void sched_fence(uint32_t key) {
  asm volatile("{\n.reg .pred p;\nsetp.eq.u32 p, %0, %1;\nSF_LOOP:\n@p pmevent 1;\n@p bra.uni SF_LOOP;\n}" :: "r"(key), "n"(ID) : "memory");
}
template <int N> __device__ __forceinline__ void pinv(float* v) {
  #pragma unroll
  for (int i = 0; i < N; i++) asm volatile("" : "+f"(v[i]) :: "memory"); }
__device__ __forceinline__ uint32_t bmul2(uint32_t a, uint32_t b) { uint32_t r; asm("mul.rn.bf16x2 %0, %1, %2;" : "=r"(r) : "r"(a), "r"(b)); return r; }
__device__ __forceinline__ uint32_t badd2(uint32_t a, uint32_t b) { uint32_t r; asm("add.rn.bf16x2 %0, %1, %2;" : "=r"(r) : "r"(a), "r"(b)); return r; }
__device__ __forceinline__ void spin_until(const unsigned* p, unsigned target) {
  int n = 0;
  unsigned v;
  do { asm volatile("ld.relaxed.gpu.global.u32 %0, [%1];" : "=r"(v) : "l"(p) : "memory"); } while ((int)(v - target) < 0 && ++n < WAIT_BOUND);
  asm volatile("fence.acquire.gpu;" ::: "memory");
}
__device__ __forceinline__ void cluster_wait() { asm volatile("barrier.cluster.wait.aligned;" ::: "memory"); }
__device__ __forceinline__ void fence_gpu() { asm volatile("fence.release.gpu;" ::: "memory"); }
__device__ __forceinline__ void fence_async_global() { asm volatile("fence.proxy.async.global;" ::: "memory"); }
__device__ __forceinline__ void red_add(unsigned* p) { asm volatile(ELECT "red.relaxed.gpu.global.add.u32 [%0], 1;\n}" :: "l"(p) : "memory"); }
__device__ __forceinline__ float rcp_fast(float x) { float r; asm("rcp.approx.ftz.f32 %0, %1;" : "=f"(r) : "f"(x)); return r; }
__device__ __forceinline__ uint32_t mapa(uint32_t a, uint32_t rank) { uint32_t r; asm("mapa.shared::cluster.u32 %0, %1, %2;" : "=r"(r) : "r"(a), "r"(rank)); return r; }
__device__ __forceinline__ void st_async128(uint32_t a, uint32_t bar, uint32_t v0, uint32_t v1, uint32_t v2, uint32_t v3) {
  asm volatile("st.async.weak.shared::cluster.mbarrier::complete_tx::bytes.v4.b32 [%0], {%2,%3,%4,%5}, [%1];"
    :: "r"(a), "r"(bar), "r"(v0), "r"(v1), "r"(v2), "r"(v3) : "memory"); }
__device__ __forceinline__ int fresh_tid() { int t; asm volatile("mov.u32 %0, %%tid.x;" : "=r"(t)); return t; }
__device__ __forceinline__ void pace(uint32_t& t, uint32_t dt) {
  uint32_t c;
  while ((int)((c = uni((uint32_t)clock())) - t) < 0) __nanosleep(20);
  t = ((int)(c - t) > (int)dt ? c : t) + dt;
}
template <int LOG> __device__ __forceinline__ void unit_root(int a, float& c, float& s) {
  const float x = (float)((a << (32 - LOG)) >> (32 - LOG)) * (6.283185307179586f / (1 << LOG));
  c = __cosf(x); s = __sinf(x); }

struct D2 { uint64_t a, b; };
template <int TA, int TB> __device__ __forceinline__ void ss128p(float* d, uint64_t da, uint64_t db, int sd) {
  asm volatile("{\n.reg .pred p;\nsetp.ne.b32 p, %68, 0;\n"
    "wgmma.mma_async.sync.aligned.m64n128k16.f32.bf16.bf16 "
    "{%0, %1, %2, %3, %4, %5, %6, %7, %8, %9, %10, %11, %12, %13, %14, %15, "
    "%16, %17, %18, %19, %20, %21, %22, %23, %24, %25, %26, %27, %28, %29, %30, %31, "
    "%32, %33, %34, %35, %36, %37, %38, %39, %40, %41, %42, %43, %44, %45, %46, %47, "
    "%48, %49, %50, %51, %52, %53, %54, %55, %56, %57, %58, %59, %60, %61, %62, %63}, %64, %65, p, 1, 1, %66, %67;\n}\n"
    : "+f"(d[0]), "+f"(d[1]), "+f"(d[2]), "+f"(d[3]), "+f"(d[4]), "+f"(d[5]), "+f"(d[6]), "+f"(d[7]),
      "+f"(d[8]), "+f"(d[9]), "+f"(d[10]), "+f"(d[11]), "+f"(d[12]), "+f"(d[13]), "+f"(d[14]), "+f"(d[15]),
      "+f"(d[16]), "+f"(d[17]), "+f"(d[18]), "+f"(d[19]), "+f"(d[20]), "+f"(d[21]), "+f"(d[22]), "+f"(d[23]),
      "+f"(d[24]), "+f"(d[25]), "+f"(d[26]), "+f"(d[27]), "+f"(d[28]), "+f"(d[29]), "+f"(d[30]), "+f"(d[31]),
      "+f"(d[32]), "+f"(d[33]), "+f"(d[34]), "+f"(d[35]), "+f"(d[36]), "+f"(d[37]), "+f"(d[38]), "+f"(d[39]),
      "+f"(d[40]), "+f"(d[41]), "+f"(d[42]), "+f"(d[43]), "+f"(d[44]), "+f"(d[45]), "+f"(d[46]), "+f"(d[47]),
      "+f"(d[48]), "+f"(d[49]), "+f"(d[50]), "+f"(d[51]), "+f"(d[52]), "+f"(d[53]), "+f"(d[54]), "+f"(d[55]),
      "+f"(d[56]), "+f"(d[57]), "+f"(d[58]), "+f"(d[59]), "+f"(d[60]), "+f"(d[61]), "+f"(d[62]), "+f"(d[63])
    : "l"(da), "l"(db), "n"(TA), "n"(TB), "r"(sd));
}
template <int TA, int TB> __device__ __forceinline__ void ss128a(float* d, uint64_t da, uint64_t db) {
  asm volatile("{\n.reg .pred p;\nsetp.eq.b32 p, 0, 0;\n"
    "wgmma.mma_async.sync.aligned.m64n128k16.f32.bf16.bf16 "
    "{%0, %1, %2, %3, %4, %5, %6, %7, %8, %9, %10, %11, %12, %13, %14, %15, "
    "%16, %17, %18, %19, %20, %21, %22, %23, %24, %25, %26, %27, %28, %29, %30, %31, "
    "%32, %33, %34, %35, %36, %37, %38, %39, %40, %41, %42, %43, %44, %45, %46, %47, "
    "%48, %49, %50, %51, %52, %53, %54, %55, %56, %57, %58, %59, %60, %61, %62, %63}, %64, %65, p, 1, 1, %66, %67;\n}\n"
    : "+f"(d[0]), "+f"(d[1]), "+f"(d[2]), "+f"(d[3]), "+f"(d[4]), "+f"(d[5]), "+f"(d[6]), "+f"(d[7]),
      "+f"(d[8]), "+f"(d[9]), "+f"(d[10]), "+f"(d[11]), "+f"(d[12]), "+f"(d[13]), "+f"(d[14]), "+f"(d[15]),
      "+f"(d[16]), "+f"(d[17]), "+f"(d[18]), "+f"(d[19]), "+f"(d[20]), "+f"(d[21]), "+f"(d[22]), "+f"(d[23]),
      "+f"(d[24]), "+f"(d[25]), "+f"(d[26]), "+f"(d[27]), "+f"(d[28]), "+f"(d[29]), "+f"(d[30]), "+f"(d[31]),
      "+f"(d[32]), "+f"(d[33]), "+f"(d[34]), "+f"(d[35]), "+f"(d[36]), "+f"(d[37]), "+f"(d[38]), "+f"(d[39]),
      "+f"(d[40]), "+f"(d[41]), "+f"(d[42]), "+f"(d[43]), "+f"(d[44]), "+f"(d[45]), "+f"(d[46]), "+f"(d[47]),
      "+f"(d[48]), "+f"(d[49]), "+f"(d[50]), "+f"(d[51]), "+f"(d[52]), "+f"(d[53]), "+f"(d[54]), "+f"(d[55]),
      "+f"(d[56]), "+f"(d[57]), "+f"(d[58]), "+f"(d[59]), "+f"(d[60]), "+f"(d[61]), "+f"(d[62]), "+f"(d[63])
    : "l"(da), "l"(db), "n"(TA), "n"(TB));
}
template <int TA, int TB> __device__ __forceinline__ void ss128z(float* d, uint64_t da, uint64_t db) {
  asm volatile("{\n.reg .pred p;\nsetp.ne.b32 p, 0, 0;\n"
    "wgmma.mma_async.sync.aligned.m64n128k16.f32.bf16.bf16 "
    "{%0, %1, %2, %3, %4, %5, %6, %7, %8, %9, %10, %11, %12, %13, %14, %15, "
    "%16, %17, %18, %19, %20, %21, %22, %23, %24, %25, %26, %27, %28, %29, %30, %31, "
    "%32, %33, %34, %35, %36, %37, %38, %39, %40, %41, %42, %43, %44, %45, %46, %47, "
    "%48, %49, %50, %51, %52, %53, %54, %55, %56, %57, %58, %59, %60, %61, %62, %63}, %64, %65, p, 1, 1, %66, %67;\n}\n"
    : "=f"(d[0]), "=f"(d[1]), "=f"(d[2]), "=f"(d[3]), "=f"(d[4]), "=f"(d[5]), "=f"(d[6]), "=f"(d[7]),
      "=f"(d[8]), "=f"(d[9]), "=f"(d[10]), "=f"(d[11]), "=f"(d[12]), "=f"(d[13]), "=f"(d[14]), "=f"(d[15]),
      "=f"(d[16]), "=f"(d[17]), "=f"(d[18]), "=f"(d[19]), "=f"(d[20]), "=f"(d[21]), "=f"(d[22]), "=f"(d[23]),
      "=f"(d[24]), "=f"(d[25]), "=f"(d[26]), "=f"(d[27]), "=f"(d[28]), "=f"(d[29]), "=f"(d[30]), "=f"(d[31]),
      "=f"(d[32]), "=f"(d[33]), "=f"(d[34]), "=f"(d[35]), "=f"(d[36]), "=f"(d[37]), "=f"(d[38]), "=f"(d[39]),
      "=f"(d[40]), "=f"(d[41]), "=f"(d[42]), "=f"(d[43]), "=f"(d[44]), "=f"(d[45]), "=f"(d[46]), "=f"(d[47]),
      "=f"(d[48]), "=f"(d[49]), "=f"(d[50]), "=f"(d[51]), "=f"(d[52]), "=f"(d[53]), "=f"(d[54]), "=f"(d[55]),
      "=f"(d[56]), "=f"(d[57]), "=f"(d[58]), "=f"(d[59]), "=f"(d[60]), "=f"(d[61]), "=f"(d[62]), "=f"(d[63])
    : "l"(da), "l"(db), "n"(TA), "n"(TB));
}
template <int TA, int TB> __device__ __forceinline__ void ss64a(float* d, uint64_t da, uint64_t db) {
  asm volatile("{\n.reg .pred p;\nsetp.eq.b32 p, 0, 0;\n"
    "wgmma.mma_async.sync.aligned.m64n64k16.f32.bf16.bf16 "
    "{%0, %1, %2, %3, %4, %5, %6, %7, %8, %9, %10, %11, %12, %13, %14, %15, "
    "%16, %17, %18, %19, %20, %21, %22, %23, %24, %25, %26, %27, %28, %29, %30, %31}, %32, %33, p, 1, 1, %34, %35;\n}\n"
    : "+f"(d[0]), "+f"(d[1]), "+f"(d[2]), "+f"(d[3]), "+f"(d[4]), "+f"(d[5]), "+f"(d[6]), "+f"(d[7]),
      "+f"(d[8]), "+f"(d[9]), "+f"(d[10]), "+f"(d[11]), "+f"(d[12]), "+f"(d[13]), "+f"(d[14]), "+f"(d[15]),
      "+f"(d[16]), "+f"(d[17]), "+f"(d[18]), "+f"(d[19]), "+f"(d[20]), "+f"(d[21]), "+f"(d[22]), "+f"(d[23]),
      "+f"(d[24]), "+f"(d[25]), "+f"(d[26]), "+f"(d[27]), "+f"(d[28]), "+f"(d[29]), "+f"(d[30]), "+f"(d[31])
    : "l"(da), "l"(db), "n"(TA), "n"(TB));
}
template <int TA, int TB> __device__ __forceinline__ void ss64z(float* d, uint64_t da, uint64_t db) {
  asm volatile("{\n.reg .pred p;\nsetp.ne.b32 p, 0, 0;\n"
    "wgmma.mma_async.sync.aligned.m64n64k16.f32.bf16.bf16 "
    "{%0, %1, %2, %3, %4, %5, %6, %7, %8, %9, %10, %11, %12, %13, %14, %15, "
    "%16, %17, %18, %19, %20, %21, %22, %23, %24, %25, %26, %27, %28, %29, %30, %31}, %32, %33, p, 1, 1, %34, %35;\n}\n"
    : "=f"(d[0]), "=f"(d[1]), "=f"(d[2]), "=f"(d[3]), "=f"(d[4]), "=f"(d[5]), "=f"(d[6]), "=f"(d[7]),
      "=f"(d[8]), "=f"(d[9]), "=f"(d[10]), "=f"(d[11]), "=f"(d[12]), "=f"(d[13]), "=f"(d[14]), "=f"(d[15]),
      "=f"(d[16]), "=f"(d[17]), "=f"(d[18]), "=f"(d[19]), "=f"(d[20]), "=f"(d[21]), "=f"(d[22]), "=f"(d[23]),
      "=f"(d[24]), "=f"(d[25]), "=f"(d[26]), "=f"(d[27]), "=f"(d[28]), "=f"(d[29]), "=f"(d[30]), "=f"(d[31])
    : "l"(da), "l"(db), "n"(TA), "n"(TB));
}
__device__ __forceinline__ void ss64x4(float* d, const D2* c, int on) {
  asm volatile("{\n.reg .pred p, z, c;\nsetp.eq.b32 p, 0, 0;\nsetp.ne.b32 z, 0, 0;\nsetp.eq.b32 c, %40, 0;\n"
    "wgmma.mma_async.sync.aligned.m64n64k16.f32.bf16.bf16 "
    "{%0, %1, %2, %3, %4, %5, %6, %7, %8, %9, %10, %11, %12, %13, %14, %15, "
    "%16, %17, %18, %19, %20, %21, %22, %23, %24, %25, %26, %27, %28, %29, %30, %31}, %32, %33, z, 1, 1, 0, 1;\n"
    "wgmma.commit_group.sync.aligned;\n@c bra.uni X4_DONE;\n"
    "wgmma.mma_async.sync.aligned.m64n64k16.f32.bf16.bf16 "
    "{%0, %1, %2, %3, %4, %5, %6, %7, %8, %9, %10, %11, %12, %13, %14, %15, "
    "%16, %17, %18, %19, %20, %21, %22, %23, %24, %25, %26, %27, %28, %29, %30, %31}, %34, %35, p, 1, 1, 0, 1;\n"
    "wgmma.mma_async.sync.aligned.m64n64k16.f32.bf16.bf16 "
    "{%0, %1, %2, %3, %4, %5, %6, %7, %8, %9, %10, %11, %12, %13, %14, %15, "
    "%16, %17, %18, %19, %20, %21, %22, %23, %24, %25, %26, %27, %28, %29, %30, %31}, %36, %37, p, 1, 1, 0, 1;\n"
    "wgmma.mma_async.sync.aligned.m64n64k16.f32.bf16.bf16 "
    "{%0, %1, %2, %3, %4, %5, %6, %7, %8, %9, %10, %11, %12, %13, %14, %15, "
    "%16, %17, %18, %19, %20, %21, %22, %23, %24, %25, %26, %27, %28, %29, %30, %31}, %38, %39, p, 1, 1, 0, 1;\n"
    "wgmma.commit_group.sync.aligned;\nX4_DONE:\n}\n"
    : "=f"(d[0]), "=f"(d[1]), "=f"(d[2]), "=f"(d[3]), "=f"(d[4]), "=f"(d[5]), "=f"(d[6]), "=f"(d[7]),
      "=f"(d[8]), "=f"(d[9]), "=f"(d[10]), "=f"(d[11]), "=f"(d[12]), "=f"(d[13]), "=f"(d[14]), "=f"(d[15]),
      "=f"(d[16]), "=f"(d[17]), "=f"(d[18]), "=f"(d[19]), "=f"(d[20]), "=f"(d[21]), "=f"(d[22]), "=f"(d[23]),
      "=f"(d[24]), "=f"(d[25]), "=f"(d[26]), "=f"(d[27]), "=f"(d[28]), "=f"(d[29]), "=f"(d[30]), "=f"(d[31])
    : "l"(c[0].a), "l"(c[0].b), "l"(c[1].a), "l"(c[1].b), "l"(c[2].a), "l"(c[2].b), "l"(c[3].a), "l"(c[3].b), "r"(on));
}
template <int TB> __device__ __forceinline__ void rs32a(float* d, const uint32_t* a, uint64_t db) {
  asm volatile("{\n.reg .pred p;\nsetp.eq.b32 p, 0, 0;\n"
    "wgmma.mma_async.sync.aligned.m64n32k16.f32.bf16.bf16 "
    "{%0, %1, %2, %3, %4, %5, %6, %7, %8, %9, %10, %11, %12, %13, %14, %15}, {%16, %17, %18, %19}, %20, p, 1, 1, %21;\n}\n"
    : "+f"(d[0]), "+f"(d[1]), "+f"(d[2]), "+f"(d[3]), "+f"(d[4]), "+f"(d[5]), "+f"(d[6]), "+f"(d[7]),
      "+f"(d[8]), "+f"(d[9]), "+f"(d[10]), "+f"(d[11]), "+f"(d[12]), "+f"(d[13]), "+f"(d[14]), "+f"(d[15])
    : "r"(a[0]), "r"(a[1]), "r"(a[2]), "r"(a[3]), "l"(db), "n"(TB));
}
template <int TB> __device__ __forceinline__ void rs32z(float* d, const uint32_t* a, uint64_t db) {
  asm volatile("{\n.reg .pred p;\nsetp.ne.b32 p, 0, 0;\n"
    "wgmma.mma_async.sync.aligned.m64n32k16.f32.bf16.bf16 "
    "{%0, %1, %2, %3, %4, %5, %6, %7, %8, %9, %10, %11, %12, %13, %14, %15}, {%16, %17, %18, %19}, %20, p, 1, 1, %21;\n}\n"
    : "=&f"(d[0]), "=&f"(d[1]), "=&f"(d[2]), "=&f"(d[3]), "=&f"(d[4]), "=&f"(d[5]), "=&f"(d[6]), "=&f"(d[7]),
      "=&f"(d[8]), "=&f"(d[9]), "=&f"(d[10]), "=&f"(d[11]), "=&f"(d[12]), "=&f"(d[13]), "=&f"(d[14]), "=&f"(d[15])
    : "r"(a[0]), "r"(a[1]), "r"(a[2]), "r"(a[3]), "l"(db), "n"(TB));
}
template <int TB> __device__ __forceinline__ void rs40a(float* d, const uint32_t* a, uint64_t db) {
  asm volatile("{\n.reg .pred p;\nsetp.eq.b32 p, 0, 0;\n"
    "wgmma.mma_async.sync.aligned.m64n40k16.f32.bf16.bf16 "
    "{%0, %1, %2, %3, %4, %5, %6, %7, %8, %9, %10, %11, %12, %13, %14, %15, "
    "%16, %17, %18, %19}, {%20, %21, %22, %23}, %24, p, 1, 1, %25;\n}\n"
    : "+f"(d[0]), "+f"(d[1]), "+f"(d[2]), "+f"(d[3]), "+f"(d[4]), "+f"(d[5]), "+f"(d[6]), "+f"(d[7]),
      "+f"(d[8]), "+f"(d[9]), "+f"(d[10]), "+f"(d[11]), "+f"(d[12]), "+f"(d[13]), "+f"(d[14]), "+f"(d[15]),
      "+f"(d[16]), "+f"(d[17]), "+f"(d[18]), "+f"(d[19])
    : "r"(a[0]), "r"(a[1]), "r"(a[2]), "r"(a[3]), "l"(db), "n"(TB));
}
template <int TB> __device__ __forceinline__ void rs40z(float* d, const uint32_t* a, uint64_t db) {
  asm volatile("{\n.reg .pred p;\nsetp.ne.b32 p, 0, 0;\n"
    "wgmma.mma_async.sync.aligned.m64n40k16.f32.bf16.bf16 "
    "{%0, %1, %2, %3, %4, %5, %6, %7, %8, %9, %10, %11, %12, %13, %14, %15, "
    "%16, %17, %18, %19}, {%20, %21, %22, %23}, %24, p, 1, 1, %25;\n}\n"
    : "=&f"(d[0]), "=&f"(d[1]), "=&f"(d[2]), "=&f"(d[3]), "=&f"(d[4]), "=&f"(d[5]), "=&f"(d[6]), "=&f"(d[7]),
      "=&f"(d[8]), "=&f"(d[9]), "=&f"(d[10]), "=&f"(d[11]), "=&f"(d[12]), "=&f"(d[13]), "=&f"(d[14]), "=&f"(d[15]),
      "=&f"(d[16]), "=&f"(d[17]), "=&f"(d[18]), "=&f"(d[19])
    : "r"(a[0]), "r"(a[1]), "r"(a[2]), "r"(a[3]), "l"(db), "n"(TB));
}
template <int TB> __device__ __forceinline__ void rs72a(float* d, const uint32_t* a, uint64_t db) {
  asm volatile("{\n.reg .pred p;\nsetp.eq.b32 p, 0, 0;\n"
    "wgmma.mma_async.sync.aligned.m64n72k16.f32.bf16.bf16 "
    "{%0, %1, %2, %3, %4, %5, %6, %7, %8, %9, %10, %11, %12, %13, %14, %15, "
    "%16, %17, %18, %19, %20, %21, %22, %23, %24, %25, %26, %27, %28, %29, %30, %31, "
    "%32, %33, %34, %35}, {%36, %37, %38, %39}, %40, p, 1, 1, %41;\n}\n"
    : "+f"(d[0]), "+f"(d[1]), "+f"(d[2]), "+f"(d[3]), "+f"(d[4]), "+f"(d[5]), "+f"(d[6]), "+f"(d[7]),
      "+f"(d[8]), "+f"(d[9]), "+f"(d[10]), "+f"(d[11]), "+f"(d[12]), "+f"(d[13]), "+f"(d[14]), "+f"(d[15]),
      "+f"(d[16]), "+f"(d[17]), "+f"(d[18]), "+f"(d[19]), "+f"(d[20]), "+f"(d[21]), "+f"(d[22]), "+f"(d[23]),
      "+f"(d[24]), "+f"(d[25]), "+f"(d[26]), "+f"(d[27]), "+f"(d[28]), "+f"(d[29]), "+f"(d[30]), "+f"(d[31]),
      "+f"(d[32]), "+f"(d[33]), "+f"(d[34]), "+f"(d[35])
    : "r"(a[0]), "r"(a[1]), "r"(a[2]), "r"(a[3]), "l"(db), "n"(TB));
}
template <int TB> __device__ __forceinline__ void rs72z(float* d, const uint32_t* a, uint64_t db) {
  asm volatile("{\n.reg .pred p;\nsetp.ne.b32 p, 0, 0;\n"
    "wgmma.mma_async.sync.aligned.m64n72k16.f32.bf16.bf16 "
    "{%0, %1, %2, %3, %4, %5, %6, %7, %8, %9, %10, %11, %12, %13, %14, %15, "
    "%16, %17, %18, %19, %20, %21, %22, %23, %24, %25, %26, %27, %28, %29, %30, %31, "
    "%32, %33, %34, %35}, {%36, %37, %38, %39}, %40, p, 1, 1, %41;\n}\n"
    : "=&f"(d[0]), "=&f"(d[1]), "=&f"(d[2]), "=&f"(d[3]), "=&f"(d[4]), "=&f"(d[5]), "=&f"(d[6]), "=&f"(d[7]),
      "=&f"(d[8]), "=&f"(d[9]), "=&f"(d[10]), "=&f"(d[11]), "=&f"(d[12]), "=&f"(d[13]), "=&f"(d[14]), "=&f"(d[15]),
      "=&f"(d[16]), "=&f"(d[17]), "=&f"(d[18]), "=&f"(d[19]), "=&f"(d[20]), "=&f"(d[21]), "=&f"(d[22]), "=&f"(d[23]),
      "=&f"(d[24]), "=&f"(d[25]), "=&f"(d[26]), "=&f"(d[27]), "=&f"(d[28]), "=&f"(d[29]), "=&f"(d[30]), "=&f"(d[31]),
      "=&f"(d[32]), "=&f"(d[33]), "=&f"(d[34]), "=&f"(d[35])
    : "r"(a[0]), "r"(a[1]), "r"(a[2]), "r"(a[3]), "l"(db), "n"(TB));
}
template <int TB> __device__ __forceinline__ void rs128a(float* d, const uint32_t* a, uint64_t db) {
  asm volatile("{\n.reg .pred p;\nsetp.eq.b32 p, 0, 0;\n"
    "wgmma.mma_async.sync.aligned.m64n128k16.f32.bf16.bf16 "
    "{%0, %1, %2, %3, %4, %5, %6, %7, %8, %9, %10, %11, %12, %13, %14, %15, "
    "%16, %17, %18, %19, %20, %21, %22, %23, %24, %25, %26, %27, %28, %29, %30, %31, "
    "%32, %33, %34, %35, %36, %37, %38, %39, %40, %41, %42, %43, %44, %45, %46, %47, "
    "%48, %49, %50, %51, %52, %53, %54, %55, %56, %57, %58, %59, %60, %61, %62, %63}, {%64, %65, %66, %67}, %68, p, 1, 1, %69;\n}\n"
    : "+f"(d[0]), "+f"(d[1]), "+f"(d[2]), "+f"(d[3]), "+f"(d[4]), "+f"(d[5]), "+f"(d[6]), "+f"(d[7]),
      "+f"(d[8]), "+f"(d[9]), "+f"(d[10]), "+f"(d[11]), "+f"(d[12]), "+f"(d[13]), "+f"(d[14]), "+f"(d[15]),
      "+f"(d[16]), "+f"(d[17]), "+f"(d[18]), "+f"(d[19]), "+f"(d[20]), "+f"(d[21]), "+f"(d[22]), "+f"(d[23]),
      "+f"(d[24]), "+f"(d[25]), "+f"(d[26]), "+f"(d[27]), "+f"(d[28]), "+f"(d[29]), "+f"(d[30]), "+f"(d[31]),
      "+f"(d[32]), "+f"(d[33]), "+f"(d[34]), "+f"(d[35]), "+f"(d[36]), "+f"(d[37]), "+f"(d[38]), "+f"(d[39]),
      "+f"(d[40]), "+f"(d[41]), "+f"(d[42]), "+f"(d[43]), "+f"(d[44]), "+f"(d[45]), "+f"(d[46]), "+f"(d[47]),
      "+f"(d[48]), "+f"(d[49]), "+f"(d[50]), "+f"(d[51]), "+f"(d[52]), "+f"(d[53]), "+f"(d[54]), "+f"(d[55]),
      "+f"(d[56]), "+f"(d[57]), "+f"(d[58]), "+f"(d[59]), "+f"(d[60]), "+f"(d[61]), "+f"(d[62]), "+f"(d[63])
    : "r"(a[0]), "r"(a[1]), "r"(a[2]), "r"(a[3]), "l"(db), "n"(TB));
}
template <int TB> __device__ __forceinline__ void rs128z(float* d, const uint32_t* a, uint64_t db) {
  asm volatile("{\n.reg .pred p;\nsetp.ne.b32 p, 0, 0;\n"
    "wgmma.mma_async.sync.aligned.m64n128k16.f32.bf16.bf16 "
    "{%0, %1, %2, %3, %4, %5, %6, %7, %8, %9, %10, %11, %12, %13, %14, %15, "
    "%16, %17, %18, %19, %20, %21, %22, %23, %24, %25, %26, %27, %28, %29, %30, %31, "
    "%32, %33, %34, %35, %36, %37, %38, %39, %40, %41, %42, %43, %44, %45, %46, %47, "
    "%48, %49, %50, %51, %52, %53, %54, %55, %56, %57, %58, %59, %60, %61, %62, %63}, {%64, %65, %66, %67}, %68, p, 1, 1, %69;\n}\n"
    : "=&f"(d[0]), "=&f"(d[1]), "=&f"(d[2]), "=&f"(d[3]), "=&f"(d[4]), "=&f"(d[5]), "=&f"(d[6]), "=&f"(d[7]),
      "=&f"(d[8]), "=&f"(d[9]), "=&f"(d[10]), "=&f"(d[11]), "=&f"(d[12]), "=&f"(d[13]), "=&f"(d[14]), "=&f"(d[15]),
      "=&f"(d[16]), "=&f"(d[17]), "=&f"(d[18]), "=&f"(d[19]), "=&f"(d[20]), "=&f"(d[21]), "=&f"(d[22]), "=&f"(d[23]),
      "=&f"(d[24]), "=&f"(d[25]), "=&f"(d[26]), "=&f"(d[27]), "=&f"(d[28]), "=&f"(d[29]), "=&f"(d[30]), "=&f"(d[31]),
      "=&f"(d[32]), "=&f"(d[33]), "=&f"(d[34]), "=&f"(d[35]), "=&f"(d[36]), "=&f"(d[37]), "=&f"(d[38]), "=&f"(d[39]),
      "=&f"(d[40]), "=&f"(d[41]), "=&f"(d[42]), "=&f"(d[43]), "=&f"(d[44]), "=&f"(d[45]), "=&f"(d[46]), "=&f"(d[47]),
      "=&f"(d[48]), "=&f"(d[49]), "=&f"(d[50]), "=&f"(d[51]), "=&f"(d[52]), "=&f"(d[53]), "=&f"(d[54]), "=&f"(d[55]),
      "=&f"(d[56]), "=&f"(d[57]), "=&f"(d[58]), "=&f"(d[59]), "=&f"(d[60]), "=&f"(d[61]), "=&f"(d[62]), "=&f"(d[63])
    : "r"(a[0]), "r"(a[1]), "r"(a[2]), "r"(a[3]), "l"(db), "n"(TB));
}

template <int V> struct IC { static constexpr int value = V; };
struct PfType { const char* base; uint32_t gl, gh, sp, sr, su, l4, l2; };
struct Params {
  const __nv_bfloat16 *x, *w;
  uint32_t one;
  const __nv_bfloat16 *shift, *ssmD;
  __nv_bfloat16* out;
  uint4* o; float* kv; unsigned* cnt;
  const char *k, *v;
  PfType pt[6];
  uint8_t pf[32];
  uint64_t cd[18];
};

struct Tmp { float t0, t1; };
__device__ __forceinline__ void mul2(Tmp& t, float a0, float b0, float a1, float b1) {
  asm volatile("@p_one mul.rn.f32 %0, %2, %3;\n@p_one mul.rn.f32 %1, %4, %5;" : "+f"(t.t0), "+f"(t.t1) : "f"(a0), "f"(b0), "f"(a1), "f"(b1)); }
__device__ __forceinline__ void add2(Tmp& t, float a0, float b0, float a1, float b1) {
  asm volatile("@p_one add.rn.f32 %0, %2, %3;\n@p_one add.rn.f32 %1, %4, %5;" : "+f"(t.t0), "+f"(t.t1) : "f"(a0), "f"(b0), "f"(a1), "f"(b1)); }
__device__ __forceinline__ void fma2(Tmp& t, float a0, float b0, float a1, float b1) { t.t0 = fmaf(a0, b0, t.t0); t.t1 = fmaf(a1, b1, t.t1); }
__device__ __forceinline__ uint32_t bfma2(uint32_t a, uint32_t b, uint32_t c) { uint32_t r; asm("fma.rn.bf16x2 %0, %1, %2, %3;" : "=r"(r) : "r"(a), "r"(b), "r"(c)); return r; }
struct Tw { uint32_t c[2], s[2], ns[2]; };
__device__ __forceinline__ void rot(uint32_t& u, uint32_t& v, const Tw& w, int k) {
  asm("{\n.reg .b32 a, b;\nmul.rn.bf16x2 a, %0, %2;\nmul.rn.bf16x2 b, %0, %3;\nfma.rn.bf16x2 %0, %1, %4, a;\nfma.rn.bf16x2 %1, %1, %2, b;\n}"
    : "+r"(u), "+r"(v) : "r"(w.c[k]), "r"(w.s[k]), "r"(w.ns[k]));
}
__device__ __forceinline__ void pack_fwd(uint32_t (&f)[2][2][4], const float* a) {
  #pragma unroll
  for (int j = 0; j < 16; j++) f[j >> 3][(j >> 1) & 1][2 * (j & 1) + ((j >> 2) & 1)] = fresh(pack_bf16(a[2 * j], a[2 * j + 1]));
}
__device__ __forceinline__ void rot_fwd(uint32_t (&f)[2][2][4], const Tw& w) {
  #pragma unroll
  for (int j = 0; j < 8; j++) rot(f[j >> 2][j & 1][(j >> 1) & 1], f[j >> 2][j & 1][2 + ((j >> 1) & 1)], w, j & 1);
}
__device__ __forceinline__ void add_skip(float* h, float d) {
  asm volatile("add.rn.f32 %0, %0, %4;\nadd.rn.f32 %1, %1, %4;\nadd.rn.f32 %2, %2, %4;\nadd.rn.f32 %3, %3, %4;" : "+f"(h[0]), "+f"(h[1]), "+f"(h[4]), "+f"(h[5]) : "f"(d)); }
__device__ __forceinline__ void dft16h(float* d, const uint32_t (&f)[2][4], const D2& dF) { rs32z<0>(d, f[0], dF.a); rs32a<0>(d, f[1], dF.b); }
#define SP(h, p, im, k) (((p) >> 1 ? hi : lo) + 16 * (h) + 8 * (im) + 4 * (k) + 2 * ((p) & 1))
template <int PH, int G0 = 0, int G1 = 8> __device__ __forceinline__ void prod(Tmp& t, uint32_t (&f)[2][4], const float* lo, const float* hi) {
  #pragma unroll
  for (int g = G0; g < G1; g++) {
    const int p = 2 * PH + 1 - (g >> 2), k = (g >> 1) & 1, im = g & 1;
    #pragma unroll
    for (int q = 0; q <= p; q++) {
      const float *hr = SP(1, q, 0, k), *hi_ = SP(1, q, 1, k), *xa = SP(0, p - q, im, k), *xb = SP(0, p - q, 1 - im, k);
      if (q == 0) mul2(t, hr[0], xa[0], hr[1], xa[1]); else fma2(t, hr[0], xa[0], hr[1], xa[1]);
      if (im) fma2(t, hi_[0], xb[0], hi_[1], xb[1]); else fma2(t, -hi_[0], xb[0], -hi_[1], xb[1]);
    }
    f[k][2 * (1 - im) + (p & 1)] = pack_bf16(t.t0, t.t1);
  }
}

constexpr uint64_t dA = cdesc(A_OFF, 2048, 128, 0), dAi = cdesc(A_OFF, 128, 1024, 0), dF0 = cdesc(F_OFF, 128, 512, 0),
                   dT0 = cdesc(T_OFF, 1024, 128, 0), dH0 = cdesc(H_OFF, 1024, 256, 3), dX0 = cdesc(X_OFF, 1024, 128, 0);
#define CONV_DESC dF0, dF0 + 16, dAi, dT0, dAi + 16, dT0 + 128, dAi + 32, dT0 + 256, dAi + 48, dT0 + 384, dA, dH0, dA + 256, dH0 + 32, dA, dX0, dA + 256, dX0 + 128
__device__ __forceinline__ void make_tw(Tw& tw, int ht) {
  #pragma unroll
  for (int i = 0; i < 2; i++) {
    float c0, s0, c1, s1;
    unit_root<11>((4 * (ht >> 2) + 1) * (i * 8 + 2 * (ht & 3)), c0, s0);
    unit_root<11>((4 * (ht >> 2) + 1) * (i * 8 + 2 * (ht & 3) + 1), c1, s1);
    tw.c[i] = pack_bf16(c0, c1); tw.s[i] = pack_bf16(s0, s1); tw.ns[i] = fresh(tw.s[i] ^ 0x80008000u);
  }
}
template <bool COMMIT = true> __device__ __forceinline__ void dft32_h(float* r, const D2* d) {
  ss64z<1, 1>(r, d[0].a, d[0].b); ss64a<1, 1>(r, d[1].a, d[1].b);
  if (COMMIT) wg_commit();
}
template <bool COMMIT = true> __device__ __forceinline__ void dft32_x(float* r, D2* d) {
  ss64z<1, 0>(r, d[0].a, d[0].b); ss64a<1, 0>(r, d[1].a, d[1].b);
  if (COMMIT) wg_commit();
  d[0].b = dofs(d[0].b, XS); d[1].b = dofs(d[1].b, XS);
}
__device__ __forceinline__ void pack_inv(uint32_t (&u)[2][2][4], const float* r) {
  #pragma unroll
  for (int j = 0; j < 16; j++) u[j >> 3][(j >> 2) & 1][2 * (j & 1) + ((j >> 1) & 1)] = fresh(pack_bf16(r[2 * j], r[2 * j + 1]));
}
__device__ __forceinline__ void rot_inv(uint32_t (&u)[2][2][4], const Tw& tw, uint32_t ta) {
  #pragma unroll
  for (int m = 0; m < 2; m++) {
    #pragma unroll
    for (int j = 0; j < 4; j++) rot(u[m][0][j], u[m][1][j], tw, j & 1);
    stsm4(ta + m * 512, u[m][1][0], u[m][1][1], u[m][1][2], u[m][1][3]);
    stsm4(ta + 1024 + m * 512, u[m][0][0], u[m][0][1], u[m][0][2], u[m][0][3]);
  }
}
__device__ __forceinline__ void idft32(float* r, const D2* d) {
  wg_fence();
  ss64z<0, 1>(r, d[0].a, d[0].b);
  #pragma unroll
  for (int j = 1; j < 4; j++) ss64a<0, 1>(r, d[j].a, d[j].b);
  wg_commit();
}
__device__ __forceinline__ void finish(Tmp& t, const float* r, int ch, int ht, int rank, uint32_t y0, uint32_t y1) {
  const uint32_t ya = X_OFF + ch * XS + (ch & 1) * 16, yb = BAR_OFF + (B_YR + ch) * 8;
  uint32_t y[8];
  #pragma unroll
  for (int j = 0; j < 8; j++) {
    if (j >= 2) add2(t, r[4 * j], r[4 * j - 6], r[4 * j + 1], r[4 * j - 5]);
    y[j] = j < 2 ? pack_bf16(r[4 * j], r[4 * j + 1]) : pack_bf16(t.t0, t.t1);
  }
  st_async128(y0 + ya + (ht ^ (rank * 4)) * 16 + rank * (YX - XS), y0 + yb, y[0], y[1], y[2], y[3]);
  st_async128(y1 + ya + (ht ^ (rank * 4) ^ 4) * 16 + (rank ^ 1) * (YX - XS), y1 + yb, y[4], y[5], y[6], y[7]);
}

struct Team { uint32_t bars, rel, wofs; bool lead; };
template <bool M> __device__ __forceinline__ void mid_wait() { if (M) { wg_commit(); wg_wait<0>(); wg_fence(); } }
template <int J, bool M = false> __device__ __forceinline__ void kv_issue(float* aK, float* aV, uint32_t xo, int sd) {
  constexpr uint64_t dw = cdesc(W_OFF + J * 8192, 8192, 1024, 1);
  const uint64_t dx = dofs(cdesc((J & 1) * 64, 16, 1024, 1), xo);
  wg_fence();
  ss128p<1, 0>(aV, dw + (4096 >> 4), dx, sd);
  ss128p<1, 0>(aK, dw, dx, sd);
  mid_wait<M>();
  ss128a<1, 0>(aV, dw + (6144 >> 4), dofs(dx, 32));
  ss128a<1, 0>(aK, dw + (2048 >> 4), dofs(dx, 32));
  wg_commit();
}
template <int O, int J, bool M = false, bool FIRST = false> __device__ __forceinline__ void g2_issue(float* acc, const Team& c) {
  constexpr uint64_t db = cdesc(J * SLOT + 16384, 8192, 1024, 1);
  const uint64_t da = dofs(O ? cdesc(J * SLOT, 16, 512, 2) : cdesc(J * SLOT, 16, 1024, 1), c.wofs);
  wg_fence();
  if (FIRST) ss128z<0, 1>(acc, da, db); else ss128a<0, 1>(acc, da, db);
  ss128a<0, 1>(acc, dofs(da, 32), db + (2048 >> 4));
  mid_wait<M>();
  ss128a<0, 1>(acc, dofs(da, O ? 4096 : 64), db + (4096 >> 4));
  ss128a<0, 1>(acc, dofs(da, O ? 4128 : 96), db + (6144 >> 4));
  wg_commit();
}
template <bool DEEP, bool AB = false, class F>
__device__ __forceinline__ void ring_step(const Team& c, int fb, uint32_t ph, int eb, bool rel, F issue, uint32_t ab = 0, uint32_t aph = 0) {
  uint32_t ok = mbar_try(c.bars + fb * 8, ph);
  if (AB) ok &= mbar_try(ab, aph);
  if (!ok) {
    wg_wait<0>();
    arrive_at(c.rel + eb * 8, rel);
    rel = false;
    mbar_wait(c.bars + fb * 8, ph);
    if (AB) mbar_wait(ab, aph);
  }
  if (!DEEP) { wg_wait<0>(); arrive_at(c.rel + eb * 8, rel); }
  issue();
  if (DEEP) { wg_wait<1>(); arrive_at(c.rel + eb * 8, rel); }
}
template <int N, int I = 0, class R> __device__ __forceinline__ void tail_release(R rel) {
  if constexpr (I <= N) { wg_wait<N - I>(); rel(I - 1); tail_release<N, I + 1>(rel); }
}
template <int N, class F, class R> __device__ __forceinline__ void skew_tail(const Team& c, int ph, F issue, R rel) {
  if (c.wofs) { wg_wait<0>(); rel(-1); mbar_wait(c.bars + B_SK * 8, ph); }
  issue();
  arrive_at(c.bars + B_SK * 8, fresh_tid() == 0);
  tail_release<N>([&](int i) { if (i >= 0 || !c.wofs) rel(i); });
}
__device__ __forceinline__ void phi_a(float* a, uint32_t* f) {
  #pragma unroll
  for (int i = 0; i < 8; i++) {
    asm("cvt.rn.relu.bf16x2.f32 %0, %1, %2;" : "=r"(f[i]) : "f"(a[2 * i + 1]), "f"(a[2 * i]));
    asm("ex2.approx.ftz.f32 %0, %1;" : "=f"(a[2 * i]) : "f"(a[2 * i] * 1.4426950408889634f));
    asm("ex2.approx.ftz.f32 %0, %1;" : "=f"(a[2 * i + 1]) : "f"(a[2 * i + 1] * 1.4426950408889634f));
  }
  pinv<16>(a);
}
__device__ __forceinline__ void phi_b(const float* e, uint32_t* f) {
  #pragma unroll
  for (int i = 0; i < 8; i++) f[i] = badd2(f[i], pack_bf16(__saturatef(e[2 * i] + 1e-6f), __saturatef(e[2 * i + 1] + 1e-6f)));
}
__device__ __forceinline__ int g2_k(int st, int n2) { return st < 2 ? 2 * n2 + st : ((st >> 1) == n2 ? st & 1 : st); }

__global__ void __cluster_dims__(2, 1, 1) __launch_bounds__(NTHREADS, 1)
fused_kernel(const __grid_constant__ Params P, const __grid_constant__ CUtensorMap mX, const __grid_constant__ CUtensorMap mW,
             const __grid_constant__ CUtensorMap mWq, const __grid_constant__ CUtensorMap mWo,
             const __grid_constant__ CUtensorMap mK, const __grid_constant__ CUtensorMap mV, const __grid_constant__ CUtensorMap mH,
             const __grid_constant__ CUtensorMap mQ, const __grid_constant__ CUtensorMap mOut, const __grid_constant__ CUtensorMap mOutA,
             const __grid_constant__ CUtensorMap mWp) {
  extern __shared__ __align__(1024) uint8_t smem[];
  asm volatile(".reg .pred p_one;");
  if (__shfl_sync(0xffffffffu, threadIdx.x >> 5, 0) == 0) {
    asm volatile(ELECT "prefetch.tensormap [%0];\n}" :: "l"(&mW) : "memory");
    asm volatile(ELECT "prefetch.tensormap [%0];\n}" :: "l"(&mX) : "memory");
  }
  {
    const uint32_t t = threadIdx.x, bb = blockIdx.x;
    asm volatile("{\n.reg .pred p, q;\nsetp.eq.u32 p, %2, 2;\nsetp.eq.u32 q, %3, 8;\n@p prefetch.global.L2 [%0];\n@q prefetch.global.L2 [%1];\n}"
      :: "l"(reinterpret_cast<const char*>(P.x) + ((bb * 16 + t - 32) * 2048)),
         "l"(reinterpret_cast<const char*>(P.w) + ((bb >> 2) * 2048 + bb * 1024 + t * 128 - 6144)), "r"(t >> 4), "r"(t >> 3));
  }
  const uint32_t sb = uni(smem_u32(smem));
  const uint32_t bars = sb + BAR_OFF;
  const int tid = threadIdx.x, lane = tid & 31;
  const int warp = __shfl_sync(0xffffffffu, tid >> 5, 0);
  const uint32_t ids = uni(cta_ids());
#define IDS(w) const int b = (w) & 127, rank = (w) & 1, g = ((w) >> 8) & 7, mb = (w) >> 12, hp = g * 2 + rank, m2 = hp, n2 = mb, \
                         cp = g * 8 + mb; (void)b; (void)hp; (void)m2; (void)n2; (void)cp
  IDS(ids);

  if (warp == 0) {
    mbar_init(bars + (B_XF + 2) * 8, 1); mbar_init(bars + B_F0 * 8, 1); mbar_init(bars + B_FULL * 8, 1);
    mbar_expect_tx(bars + B_FULL * 8, 8192);
    tma3d(sb + W_OFF, &mW, hp * 64, 0, 1, bars + B_FULL * 8);
    mbar_expect_tx(bars + (B_XF + 2) * 8, 16384);
    tma2d(sb + 2 * SLOT, &mX, 0, mb * 256, bars + (B_XF + 2) * 8);
    mbar_expect_tx(bars + B_F0 * 8, 16384);
    tma2d(sb + 2 * SLOT + 16384, &mX, 0, mb * 256 + 128, bars + B_F0 * 8);
    #pragma unroll
    for (int i = 1; i < 4; i++) mbar_init(bars + (B_FULL + i) * 8, 1);
    mbar_init(bars + B_XF * 8, 1); mbar_init(bars + (B_XF + 1) * 8, 1);
    #pragma unroll
    for (int i = 1; i < 4; i++) {
      mbar_expect_tx(bars + (B_FULL + i) * 8, 8192);
      tma3d(sb + W_OFF + i * 8192, &mW, hp * 64, i * 32, 1, bars + (B_FULL + i) * 8);
    }
  } else if (warp >= 6) {
    const uint32_t cnt = warp < 12 || warp == 15 ? 1 : 4, b0 = bars + (warp - 4) * 32;
    #pragma unroll
    for (int i = 0; i < 4; i++) mbar_init(b0 + i * 8, i == 3 && warp == 15 ? 4 : cnt);
    if (warp == 8 || warp == 9) {
      #pragma unroll
      for (int i = 0; i < 4; i++) mbar_expect_tx(b0 + i * 8, 4096);
    } else if (warp == 13) {
      mbar_expect_tx(bars + B_KVB * 8, 5120);
    }
  }
  asm volatile("fence.mbarrier_init.release.cluster;" ::: "memory");
  __syncwarp();
  asm volatile("barrier.cluster.arrive.relaxed.aligned;" ::: "memory");

  if (warp < 8) {
    asm volatile("setmaxnreg.inc.sync.aligned.u32 %0;" :: "n"(160));
    const int wg = warp >> 2;
    Team c;
    c.bars = bars; c.rel = mapa(bars, tid & 1); c.wofs = wg * 8192; c.lead = (tid & 127) < 2;
    uint32_t key = P.one;
    auto gemm2 = [&](float* a, auto O_, auto SK_) {
      constexpr int O = O_.value, SK = SK_.value;
      static_assert(SK >= 1 && SK <= 3, "tail");
      uint32_t ph = 1;
      const uint32_t ab = bars + B_FA * 8 + wg * 32;
      #pragma unroll 1
      for (int it = 1; it < 4; it++, ph ^= 1) {
        ring_step<false, O>(c, B_FULL2, ph ^ O, B_EMPTY2 + 3, c.lead, [&]() { g2_issue<O, 0, (MID >> (1 + O)) & 1>(a, c); }, ab, ph ^ 1);
        if (!O && (tid & 127) == 0) OSTAMP(55 + wg * 4 + it);
        if (O && (tid & 127) == 0) OSTAMP(40 + wg * 4 + it);
        if (SK == 3 && it == 3) break;
        ring_step<false, O>(c, B_FULL2 + 1, ph, B_EMPTY2, c.lead && (!O || it < 3), [&]() { g2_issue<O, 1, (MID >> (1 + O)) & 1>(a, c); }, ab + 8, ph);
        if (SK == 2 && it == 3) break;
        ring_step<false, O>(c, B_FULL2 + 2, ph, B_EMPTY2 + 1, c.lead && (!O || it < 3), [&]() { g2_issue<O, 2, (MID >> (1 + O)) & 1>(a, c); }, ab + 16, ph);
        if (SK == 1 && it == 3) break;
        ring_step<false, O>(c, B_FULL2 + 3, ph, B_EMPTY2 + 2, c.lead, [&]() { g2_issue<O, 3, (MID >> (1 + O)) & 1>(a, c); }, ab + 24, ph);
      }
      skew_tail<SK>(c, O ^ 1,
        [&]() {
          auto full = [&](int jj) { mbar_wait(bars + (B_FULL2 + jj) * 8, 1); if (O) mbar_wait(ab + jj * 8, 1); };
          if (SK >= 3) { full(1); g2_issue<O, 1>(a, c); }
          if (SK >= 2) { full(2); g2_issue<O, 2>(a, c); }
          full(3); g2_issue<O, 3>(a, c);
        },
        [&](int i) { if (!O) arrive_at(c.rel + (B_EMPTY2 + ((16 - SK + i) & 3)) * 8, c.lead); });
      pinv<64>(a);
    };
    float aq[64];
    {
      float aK[64], aV[64];
      if (wg == 0) { kv_issue<0>(aK, aV, 0, 0); wg_wait<0>(); }
      cluster_wait();
      if (wg == 1) mbar_wait(bars + B_F0 * 8, 0);
      static_assert(SK1 >= 1 && SK1 <= 3, "tail");
      uint32_t ph = 0, xs = 2, xp = 0;
      auto next_x = [&]() { if (xs == 1) xp ^= 1; xs = xs == 2 ? 0 : xs + 1; };
      #pragma unroll 1
      for (int it = 0; it < 8; it++, ph ^= 1) {
        uint32_t xo = xs * SLOT + wg * 16384;
        ring_step<false, true>(c, B_FULL, ph, B_EMPTY + 3, c.lead && it > 0, [&]() { kv_issue<0, MID & 1>(aK, aV, xo, it); if (tid == 0 && it == 0) OSTAMP(1); }, bars + (B_XF + xs) * 8, xp);
        if (SK1 == 3 && it == 7) break;
        next_x();
        ring_step<false>(c, B_FULL + 1, ph, B_EMPTY, c.lead, [&]() { kv_issue<1, MID & 1>(aK, aV, xo, 1); });
        if (SK1 == 2 && it == 7) break;
        xo = xs * SLOT + wg * 16384;
        ring_step<false, true>(c, B_FULL + 2, ph, B_EMPTY + 1, c.lead, [&]() { kv_issue<2, MID & 1>(aK, aV, xo, 1); }, bars + (B_XF + xs) * 8, xp);
        if (SK1 == 1 && it == 7) break;
        next_x();
        ring_step<false>(c, B_FULL + 3, ph, B_EMPTY + 2, c.lead, [&]() { kv_issue<3, MID & 1>(aK, aV, xo, 1); });
      }
      skew_tail<SK1>(c, 0,
        [&]() {
          auto wait = [&](uint32_t a) { mbar_wait(a, 1); };
          if (SK1 >= 3) { wait(bars + (B_FULL + 1) * 8); kv_issue<1>(aK, aV, SLOT + wg * 16384, 1); }
          if (SK1 >= 2) { wait(bars + (B_FULL + 2) * 8); wait(bars + (B_XF + 2) * 8); kv_issue<2>(aK, aV, 2 * SLOT + wg * 16384, 1); }
          wait(bars + (B_FULL + 3) * 8); kv_issue<3>(aK, aV, 2 * SLOT + wg * 16384, 1);
        },
        [&](int i) { arrive_at(c.rel + (B_EMPTY + ((32 - SK1 + i) & 3)) * 8, c.lead); });
      pinv<64>(aV); pinv<64>(aK);
      if (tid == 128) OSTAMP(3);
      const uint32_t vb = sb + M_OFF + wg * VT;
      float kv[36];
      uint32_t kf[4][8];
      const uint64_t dv = dofs(cdesc(M_OFF, 1152, 128, 0), wg * VT);
      const int t = fresh_tid();
      const uint32_t va = vb + ((t >> 4) & 1) * 1152 + ((t >> 5) & 3) * 256 + (t & 15) * 16;
      mbar_wait(bars + B_X * 8, 0);
      #pragma unroll
      for (int i = 0; i < 8; i++) {
        const float* a = aV + 8 * i;
        stsm4(va + i * 2304, pack_bf16(a[0], a[1]), pack_bf16(a[2], a[3]), pack_bf16(a[4], a[5]), pack_bf16(a[6], a[7]));
      }
      phi_a(aK + 48, kf[3]);
      mbar_wait(bars + B_FULL2 * 8, 0);
      if ((tid & 127) == 0) OSTAMP(50 + wg);
      g2_issue<0, 0, false, true>(aq, c);
      sts128(vb + ((t & 127) >> 3) * 1152 + 1024 + (t & 7) * 16, 0x3f803f80u, 0x3f803f80u, 0x3f803f80u, 0x3f803f80u);
      phi_a(aK + 32, kf[2]); phi_b(aK + 48, kf[3]);
      sched_fence(key++);
      ring_step<true>(c, B_FULL2 + 1, 0, B_EMPTY2, c.lead, [&]() { g2_issue<0, 1>(aq, c); });
      phi_a(aK + 16, kf[1]); phi_b(aK + 32, kf[2]);
      sched_fence(key++);
      ring_step<true>(c, B_FULL2 + 2, 0, B_EMPTY2 + 1, c.lead, [&]() { g2_issue<0, 2>(aq, c); });
      phi_a(aK, kf[0]); phi_b(aK + 16, kf[1]);
      sched_fence(key++);
      fence_async_smem(); bar_sync(1 + wg, 128);
      phi_b(aK, kf[0]);
      sched_fence(key++);
      wg_fence();
      #pragma unroll
      for (int ks = 0; ks < 8; ks++) {
        if (ks == 0) rs72z<0>(kv, kf[0], dv); else rs72a<0>(kv, kf[ks >> 1] + 4 * (ks & 1), dofs(dv, ks * 2304));
      }
      wg_commit();
      wg_wait<1>();
      arrive_at(c.rel + (B_EMPTY2 + 2) * 8, c.lead);
      mbar_wait(bars + (B_FULL2 + 3) * 8, 0);
      g2_issue<0, 3>(aq, c);
      wg_wait<1>();
      pinv<36>(kv);
      const int a = fresh_tid() & 127;
      const bool hi = a >= 64;
      #pragma unroll
      for (int u = 0; u < 4; u++) {
        const int o = (u & 1) * 8 + (u & 2);
        sts128(vb + (a ^ ((a >> 3) & 3)) * 16 + u * 2048, __float_as_uint(hi ? kv[16 + o] : kv[o]), __float_as_uint(hi ? kv[17 + o] : kv[o + 1]),
               __float_as_uint(hi ? kv[20 + o] : kv[o + 4]), __float_as_uint(hi ? kv[21 + o] : kv[o + 5]));
      }
      if ((a & 3) < 2) sts32(vb + 8192 + ((a >> 5) * 16 + ((a & 31) >> 2) + (a & 1) * 8) * 4, __float_as_uint((a & 1) ? kv[34] : kv[32]));
      bar_arrive(4, 352);
    }
    if (tid == 0) OSTAMP(4);
    if (tid == 128) OSTAMP(5);
    float acc[64];
    {
      gemm2(aq, IC<0>(), IC<SK2>());
      if (tid == 0) OSTAMP(6);
      if (tid == 128) OSTAMP(7);
      constexpr uint64_t dk = cdesc(KVB_OFF, 640, 128, 0);
      const uint32_t id2 = fresh(ids); IDS(id2);
      float nu[4][20];
      uint32_t gen, far;
      uint32_t pq[4][8], o[4][2][4];
      const int t2 = fresh_tid();
      const uint32_t oo = (t2 & 96) * 32 + (t2 & 28) * 16 + ((t2 ^ (t2 >> 3)) & 3) * 16;
      uint4* og = P.o + ((m2 * 8 + n2) * 4 + wg) * 512 + (oo >> 4);
      auto o_put = [&](int h, int e) {
        if (AB & 8) return;
        asm volatile("st.global.v4.b32 [%0], {%1,%2,%3,%4};" :: "l"(og + (h >> 1) * 1024 + (h & 1) * 256 + e * 32),
          "r"(o[h][e][0]), "r"(o[h][e][1]), "r"(o[h][e][2]), "r"(o[h][e][3]) : "memory");
      };
      auto o_out = [&](int h) {
        pinv<20>(nu[h]);
        #pragma unroll
        for (int e = 0; e < 2; e++) {
          const float* n = nu[h] + 2 * e;
          const float iv = rcp_fast(n[16] + 1e-6f);
          #pragma unroll
          for (int i = 0; i < 4; i++) o[h][e][i] = pack_bf16(n[4 * i] * iv, n[4 * i + 1] * iv);
          o_put(h, e);
        }
      };
      auto o_mma = [&](int h) {
        wg_fence();
        rs40z<1>(nu[h], pq[h], dk + h * (2560 >> 4));
        rs40a<1>(nu[h], pq[h] + 4, dk + h * (2560 >> 4) + (1280 >> 4));
        wg_commit();
      };
#define QSTAMP(i) do { if ((t2 & 127) == 0) TSTAMP(6, wg * 16 + (i)); } while (0)
      QSTAMP(0);
      #pragma unroll
      for (int u = 0; u < 5; u++) {
        if (u >= 3) { wg_wait<1>(); QSTAMP(2 * u + 1); o_out(u - 3); }
        if (u < 4) phi_a(aq + 16 * u, pq[u]);
        if (u > 0) phi_b(aq + 16 * (u - 1), pq[u - 1]);
        if (u == 1) { QSTAMP(2); if (!(AB & 16)) mbar_wait(bars + B_KVB * 8, 0); QSTAMP(3); gen = lds32(sb + D_OFF + 40); far = lds32(sb + D_OFF + 48); fence_async_smem(); } else sched_fence(key++);
        QSTAMP(u ? 2 * u + 2 : 1);
        if (u > 0) o_mma(u - 1);
        if (u == 1) QSTAMP(5);
      }
      wg_wait<1>(); QSTAMP(11); o_out(2);
      sched_fence(key++);
      wg_wait<0>(); QSTAMP(12); o_out(3);
      QSTAMP(13);
      asm volatile(ELECT "st.relaxed.gpu.global.u32 [%0], %1;\n}" :: "l"(&P.cnt[(32 + m2 * 2 + wg) * 32 + n2 * 4 + (warp & 3)]), "r"(gen) : "memory");
      bar_arrive(6, 288);
      if (OWNL) arrive_at(bars + B_OD * 8, t2 == 128);
      if ((t2 & 127) == 0) OSTAMP(8 + wg * 2);
      if (OCP) {
        sched_fence(key++);
        #pragma unroll
        for (int i = 0; i < 32; i++) asm volatile("lop3.b32 %0, %1, %2, 0, 0xf0 | 0xcc;" : "=r"(o[i >> 3][(i >> 2) & 1][i & 3]) : "r"(o[i >> 3][(i >> 2) & 1][i & 3]), "r"(P.one - 1));
      }
      if (OWNL && wg == 0) mbar_wait(bars + B_OD * 8, 0);
      mbar_wait(bars + (B_FULL2 + 1) * 8, 0);
      QSTAMP(14);
      wg_fence();
      #pragma unroll
      for (int i = 0; i < 8; i++) {
        const uint32_t f[4] = {o[i >> 1][0][i & 1], o[i >> 1][1][i & 1], o[i >> 1][0][2 + (i & 1)], o[i >> 1][1][2 + (i & 1)]};
        constexpr uint64_t dw = cdesc(SLOT, 16384, 2048, 1);
        if (i == 0) rs128z<1>(acc, f, dw); else rs128a<1>(acc, f, dw + (((i >> 1) * 4096 + (i & 1) * 1024) >> 4));
      }
      wg_commit();
      if ((t2 & 127) == 0) OSTAMP(37 + wg);
      const uint32_t ab = bars + B_FA * 8 + wg * 32;
      const int k2 = g2_k(2, n2);
      const bool doubt = NEAR == 2 || (uni(far) >> (k2 >> 1)) & 1;
      auto look = [&](int j) {
        if (doubt) {
          const uint32_t a = sb + (2 + j) * SLOT + wg * 8192 + (t2 & 96) * 32;
          if (__any_sync(0xffffffffu, lds32(a + (t2 & 16) * 256 + (t2 & 15) * 64 + (t2 & 30) * 2) == ~0u)) {
            const uint4* src = P.o + (m2 * 16 + k2 + j) * 1024 + wg * 512 + (t2 & 96) * 2 + (t2 & 31);
            if ((t2 & 31) == 0) OSTAMP(34);
            #pragma unroll 1
            for (int i = 0; i < 4; i++) {
              uint32_t v[4];
              int n = 0;
              do asm volatile("ld.relaxed.gpu.global.v4.u32 {%0,%1,%2,%3}, [%4];" : "=r"(v[0]), "=r"(v[1]), "=r"(v[2]), "=r"(v[3]) : "l"(src + (i & 1) * 32 + (i >> 1) * 256) : "memory");
              while (__any_sync(0xffffffffu, v[0] == ~0u) && ++n < 64);
              sts128(a + (t2 & 31) * 16 + (i & 1) * 512 + (i >> 1) * 4096, v[0], v[1], v[2], v[3]);
            }
            fence_async_smem();
            __syncwarp();
          }
        }
      };
      ring_step<true, true>(c, B_FULL2 + 2, 0, B_EMPTY2 + 1, c.lead, [&]() { look(0); if ((t2 & 127) == 0) OSTAMP(11 + wg * 24); g2_issue<1, 2>(acc, c); }, ab + 16, 0);
      ring_step<true, true>(c, B_FULL2 + 3, 0, B_EMPTY2 + 2, c.lead, [&]() { look(1); g2_issue<1, 3>(acc, c); }, ab + 24, 0);
    }
    gemm2(acc, IC<1>(), IC<SK3>());
    if (tid == 0) OSTAMP(13);
    if (tid == 128) OSTAMP(14);
    {
      const uint32_t id2 = fresh(ids); IDS(id2);
      const int t2 = fresh_tid();
      const int row = ((t2 >> 5) & 3) * 16 + (t2 & 15);
      const int cq = (t2 >> 4) & 1, sw = t2 & 7;
      const uint32_t stg = sb + (EHI ? T_OFF : 0) + wg * 8192;
      constexpr uint32_t HS = EHI ? 16384 : SLOT;
      if (EHI) mbar_wait(bars + B_CD * 8, 0);
      #pragma unroll 1
      for (int pass = 0;; pass++) {
      const bool bad = acc[0] != acc[0] || acc[2] != acc[2];
      #pragma unroll
      for (int hf = 0; hf < 2; hf++) {
        #pragma unroll
        for (int jj = 0; jj < 4; jj++) {
          const int o = hf * 32 + jj * 8;
          stsm4(stg + hf * HS + row * 128 + (((2 * jj + cq) ^ sw) << 4),
                pack_bf16(acc[o], acc[o + 1]), pack_bf16(acc[o + 2], acc[o + 3]),
                pack_bf16(acc[o + 4], acc[o + 5]), pack_bf16(acc[o + 6], acc[o + 7]));
        }
        fence_async_smem();
        __syncwarp();
        if (!(AB & 1) && !((AB & 32) && wg == 0)) tma2d_store(&mOut, 1024 + n2 * 128 + hf * 64, m2 * 128 + warp * 16, sb + (EHI ? T_OFF : 0) + hf * HS + warp * 2048);
      }
      bulk_commit();
      uint32_t redo;
      asm volatile("{\n.reg .pred p, q;\nsetp.ne.b32 p, %1, 0;\nbar.red.or.pred q, %2, 128, p;\nselp.u32 %0, 1, 0, q;\n}" : "=r"(redo) : "r"((uint32_t)bad), "r"(1 + wg) : "memory");
      if (!uni(redo) || pass) break;
      if ((t2 & 127) == 0) OSTAMP(48 + wg);
      asm volatile("cp.async.bulk.wait_group 0;" ::: "memory");
      spin_until(&P.cnt[(16 + m2) * 32 + (t2 & 7)], lds32(sb + D_OFF + 40));
      fence_async_global();
      const uint32_t ab = bars + B_FA * 8 + wg * 32;
      #pragma unroll 1
      for (int k = 0; k < 16; k++) {
        bar_sync(1 + wg, 128);
        if ((warp & 3) == 0) {
          mbar_expect_tx(ab, 24576);
          bulk_load(sb + c.wofs, P.o + (m2 * 16 + k) * 1024 + wg * 512, 8192, ab);
          tma2d(sb + SLOT + c.wofs, &mWo, n2 * 128, k * 64, ab);
          tma2d(sb + 2 * SLOT + c.wofs, &mWo, n2 * 128 + 64, k * 64, ab);
        }
        mbar_wait(ab, ~k & 1);
        const uint64_t da = dofs(cdesc(0, 16, 512, 2), c.wofs), db = dofs(cdesc(SLOT, SLOT, 1024, 1), c.wofs);
        wg_fence();
        ss128p<0, 1>(acc, da, db, k);
        ss128a<0, 1>(acc, dofs(da, 32), dofs(db, 2048));
        ss128a<0, 1>(acc, dofs(da, 4096), dofs(db, 4096));
        ss128a<0, 1>(acc, dofs(da, 4128), dofs(db, 6144));
        wg_commit();
        wg_wait<0>(); pinv<64>(acc);
      }
      }
      bulk_wait_read();
    }
  } else if (warp < 12) {
    asm volatile("setmaxnreg.inc.sync.aligned.u32 %0;" :: "n"(160));
    const uint32_t id2 = fresh(ids); IDS(id2);
    const int ht = tid - 256, w = warp - 8;
    const int kap = w & 1;
    uint32_t w0, w1, w2, w3;
    {
      const uint4 s = *reinterpret_cast<const uint4*>(P.shift + (cp * 16 + kap * 8 + 2 * (lane & 3)) * 4);
      w0 = __byte_perm(s.x, s.z, 0x5410); w1 = __byte_perm(s.x, s.z, 0x7632);
      w2 = __byte_perm(s.y, s.w, 0x5410); w3 = __byte_perm(s.y, s.w, 0x7632);
      float dv = 0.f;
      if (ht < 8) dv = __bfloat162float(P.ssmD[cp * 16 + rank * 8 + ht]) * 0.125f;
      uint32_t c4[4], s4[4];
      #pragma unroll
      for (int i = 0; i < 4; i++) {
        float c0, s0, c1, s1;
        unit_root<7>((32 * (ht & 3) + 8 * i + 1) * (ht >> 2), c0, s0);
        unit_root<7>((32 * (ht & 3) + 8 * i + 5) * (ht >> 2), c1, s1);
        c4[i] = pack_bf16(c0 * 0.125f, c1 * 0.125f); s4[i] = pack_bf16(s0 * 0.125f, s1 * 0.125f);
      }
      const uint32_t aa = sb + A_OFF + w * 2048 + (ht & 3) * 256 + ((ht >> 2) & 7) * 16;
      sts128(aa, c4[0], c4[1], c4[2], c4[3]);
      sts128(aa + 128, s4[0], s4[1], s4[2], s4[3]);
      sts128(aa + 1024, s4[0] ^ 0x80008000u, s4[1] ^ 0x80008000u, s4[2] ^ 0x80008000u, s4[3] ^ 0x80008000u);
      sts128(aa + 1024 + 128, c4[0], c4[1], c4[2], c4[3]);
      float c0, s0, c1, s1;
      unit_root<4>((ht >> 3) * (2 * (ht & 7)), c0, s0);
      unit_root<4>((ht >> 3) * (2 * (ht & 7) + 1), c1, s1);
      const uint32_t fa = sb + F_OFF + (ht >> 6) * 512 + ((ht >> 2) & 1) * 256 + ((ht >> 3) & 7) * 16 + (ht & 3) * 4;
      const uint32_t cc = pack_bf16(c0, c1), ss = pack_bf16(s0, s1);
      sts32(fa, cc); sts32(fa + 128, ss ^ 0x80008000u); sts32(fa + 1024, ss); sts32(fa + 1024 + 128, cc);
      if (ht < 8) sts32(sb + D_OFF + ht * 4, __float_as_uint(dv));
    }
    Tw tw;
    make_tw(tw, ht);
    D2 cd[9];
    {
      const uint64_t v = P.cd[min(lane, 17)];
      #pragma unroll
      for (int i = 0; i < 9; i++) { cd[i].a = __shfl_sync(0xffffffffu, v, 2 * i); cd[i].b = __shfl_sync(0xffffffffu, v, 2 * i + 1); }
    }
    const D2 &dF = cd[0], *dT = cd + 1, *dH = cd + 5;
    D2* dX = cd + 7;
#define CFENCE(n) sched_fence<n>((uint32_t)dF.a)
    cluster_wait();
    const uint32_t psb = uni(mapa(sb, rank ^ 1));
    if (ht == 0) OSTAMP(20);
    {
      const int m = lane >> 3, n1 = (w >> 1) * 8 + (lane & 7);
      const int rk = 17 * m + n1 + 1, rh = 17 * (12 + m) + n1, rv = 16 * m + n1;
      const uint32_t ka = rk * 32 + ((kap ^ (rk >> 2)) & 1) * 16, ha = rh * 32 + ((kap ^ (rh >> 2)) & 1) * 16;
      const uint32_t va = rv * 32 + ((kap ^ (rv >> 2)) & 1) * 16;
      const uint32_t po = sb + T_OFF + (w >> 1) * 2176;
      #pragma unroll 1
      for (int rd = 0; rd < 4; rd++) {
        const uint32_t kb = sb + M_OFF + (rd & 1) * KB, vb = sb + M_OFF + 2 * KB + (rd & 1) * 8192;
        const uint32_t xo = X_OFF + ((rd & 1) * 2 + (w >> 1)) * 1024 + (2 * rank + (rd >> 1)) * 256;
        const uint32_t xa = (kap == rank ? sb + xo + (lane & 7) * XS : po + (lane & 7) * 272) + m * 16;
        mbar_wait(bars + (B_STG + (rd & 1) * 2) * 8, rd >> 1);
        uint32_t kk[20], vv[16];
        const uint32_t zero = P.one - 1;
        ldsm4(kk, kb + ha);
        ldsm4(kk + 4, kb + ka);
        #pragma unroll
        for (int i = 0; i < 16; i++) {
          if ((i & 3) == 0 && i < 12) ldsm4(kk + 8 + i, kb + (ka ^ ((~i & 4) * 4)) + (i + 4) * 544 + (kk[i + 4] & zero));
          uint32_t t = bmul2(kk[i + 1], w3);
          t = badd2(t, bmul2(kk[i + 2], w2));
          t = badd2(t, bmul2(kk[i + 3], w1));
          kk[i] = badd2(t, bmul2(kk[i + 4], w0));
          asm volatile("" : "+r"(kk[i]));
        }
        mbar_wait(bars + (B_STG + (rd & 1) * 2 + 1) * 8, rd >> 1);
        ldsm4(vv, vb + va);
        #pragma unroll
        for (int i = 0; i < 16; i += 4) {
          if (i < 12) ldsm4(vv + 4 + i, vb + va + (i + 4) * 512 + (i == 4 ? vv[0] & zero : 0));
          stsm4t(xa + (i >> 2) * 64, bmul2(kk[i], vv[i]), bmul2(kk[i + 1], vv[i + 1]), bmul2(kk[i + 2], vv[i + 2]), bmul2(kk[i + 3], vv[i + 3]));
        }
        if (rd < 2) {
          fence_async_smem();
          __syncwarp();
          mbar_arrive(bars + (B_SFREE + (rd & 1)) * 8);
        }
        __syncwarp();
        if (kap != rank) {
          #pragma unroll
          for (int i = 0; i < 4; i++) lds128(vv + 4 * i, po + (2 * i + (lane >> 4)) * 272 + (lane & 15) * 16);
          #pragma unroll
          for (int i = 0; i < 4; i++)
            st_async128(psb + xo + (2 * i + (lane >> 4)) * XS + (lane & 15) * 16, psb + BAR_OFF + B_X * 8, vv[4 * i], vv[4 * i + 1], vv[4 * i + 2], vv[4 * i + 3]);
          __syncwarp();
        }
      }
    }
    bar_sync(3, 128);
    if (w == 0) mbar_expect_tx(bars + B_X * 8, 16384);
    {
      constexpr int NC = 8;
      Tmp t; t.t0 = 0.f; t.t1 = 0.f;
      asm volatile("setp.ne.b32 p_one, %0, 0;" :: "r"(lds32(sb + F_OFF)));
      float ra[32], lo[32], hi[32];
      uint32_t fa[2][2][4], fb[2][2][4];
      const uint32_t ta = sb + T_OFF + w * 2048 + lane * 16;
      const uint32_t y0 = rank ? psb : sb, y1 = rank ? sb : psb;
      auto fin = [&](int ch) {
        if (ch > 0) mbar_wait(bars + (B_YR + ch - 1) * 8, 0);
        finish(t, ra, ch, ht, rank, y0, y1);
      };
      auto load_h = [&](int i) {
        mbar_expect_tx(bars + B_H * 8, 4096);
        tma2d(sb + H_OFF, &mH, 0, (cp * 16 + rank * 8 + i) * 128, bars + B_H * 8);
      };
      auto skip = [&](int i) {
        const float dn = __uint_as_float(lds32(sb + D_OFF + i * 4));
        return dn;
      };
      mbar_wait(bars + B_H * 8, 0);
      wg_fence();
      dft32_h(lo, dH);
      mbar_wait(bars + B_X * 8, 0);
      fence_async_smem();
      if (ht == 0) OSTAMP(21);
      wg_fence();
      dft32_x(hi, dX);
      float dn = skip(0);
      wg_wait<1>(); pinv<32>(lo);
      if (w == 0) load_h(1);
      pack_fwd(fa, lo); CFENCE(0); rot_fwd(fa, tw); CFENCE(1);
      wg_wait<0>(); pinv<32>(hi);
      pack_fwd(fb, hi); CFENCE(2); rot_fwd(fb, tw); CFENCE(3);
      wg_fence();
      dft16h(hi, fb[1], dF); dft16h(hi + 16, fa[1], dF); dft16h(lo, fb[0], dF); dft16h(lo + 16, fa[0], dF);
      wg_commit();
      wg_wait<0>(); pinv<32>(lo); pinv<32>(hi);
#define CSTAMP(n) do {} while (0)
      #pragma unroll 1
      for (int i = 0;; i++) {
        CSTAMP(0);
        add_skip(lo + 16, dn);
        prod<1, 0, FG>(t, fa[1], lo, hi);
        CFENCE(4);
        CSTAMP(1);
        fence_async_smem();
        bar_sync(3, 128);
        CSTAMP(2);
        float rg[32];
        if (DRY) idft32(rg, dT); else { wg_fence(); ss64x4(rg, dT, i); }
        CFENCE(5);
        CSTAMP(3);
        const uint32_t yr = bars + (i < 2 ? B_X : B_YR + i - 2) * 8;
        const uint32_t oky = mbar_try(yr, 0);
        dn = skip(i + 1);
        prod<1, FG, 8>(t, fa[1], lo, hi);
        pinv<32>(lo);
        if (!oky) mbar_wait(yr, 0);
        CSTAMP(4);
        wg_wait<0>(); pinv<32>(rg);
        if (i > 0) finish(t, rg, i - 1, ht, rank, y0, y1);
        if (i == NC - 1) break;
        CSTAMP(5);
        wg_fence();
        dft32_x<false>(hi, dX);
        if (HINT & 1) { asm volatile("@!p_one mov.b32 %0, %1;" : "+f"(t.t1) : "f"(rg[0])); if (SF & 16) CFENCE(6); wg_fence(); }
        dft16h(ra + 16, fa[1], dF);
        wg_commit();
        CFENCE(7);
        CSTAMP(6);
        const uint32_t okh = mbar_try(bars + B_H * 8, (i + 1) & 1);
        prod<0>(t, fa[0], lo, lo);
        if ((AB & 128) && i == 4) mbar_wait(bars + B_GO * 8, 0);
        if (!okh) mbar_wait(bars + B_H * 8, (i + 1) & 1);
        CSTAMP(7);
        wg_fence();
        dft32_h<false>(lo, dH);
        if (HINT & 2) { asm volatile("@!p_one mov.b32 %0, %1;" : "+f"(t.t0) : "f"(rg[31])); if (SF & 8) CFENCE(8); wg_fence(); }
        dft16h(ra, fa[0], dF);
        wg_commit();
        wg_wait<1>(); pinv<32>(hi);
        if (ht == 64) OSTAMP(22 + i);
        CSTAMP(8);
        pack_fwd(fb, hi); CFENCE(9); rot_fwd(fb, tw); CFENCE(10);
        CSTAMP(9);
        wg_wait<0>(); pinv<32>(lo); pinv<32>(ra);
        CSTAMP(10);
        if (w == HW && i < NC - 2) load_h(i + 2);
        pack_fwd(fa, lo);
        if (SF & 32) CFENCE(11);
        wg_fence();
        dft16h(hi, fb[1], dF); dft16h(lo, fb[0], dF);
        wg_commit();
        CFENCE(12);
        rot_fwd(fa, tw);
        uint32_t u[2][2][4];
        if (CX) { CFENCE(13); pack_inv(u, ra); }
        if (SF & 64) CFENCE(14);
        CSTAMP(11);
        wg_fence();
        dft16h(hi + 16, fa[1], dF); dft16h(lo + 16, fa[0], dF);
        wg_commit();
        CFENCE(15);
        CSTAMP(12);
        if (!CX) { pack_inv(u, ra); CFENCE(13); }
        rot_inv(u, tw, ta);
        CSTAMP(13);
        if (SF & 1) CFENCE(16);
        wg_wait<0>(); pinv<32>(lo); pinv<32>(hi);
        CSTAMP(14);
      }
      wg_fence();
      dft16h(hi + 16, fa[1], dF);
      wg_commit();
      CFENCE(17);
      prod<0>(t, fa[0], lo, lo);
      CFENCE(18);
      wg_fence();
      dft16h(hi, fa[0], dF);
      wg_commit();
      if (ht == 64) OSTAMP(29);
      wg_wait<0>(); pinv<32>(hi);
      pack_inv(fb, hi); CFENCE(19); rot_inv(fb, tw, ta);
      fence_async_smem();
      bar_sync(3, 128);
      idft32(ra, dT);
      const int l3 = fresh_tid() & 31;
      uint32_t qa = sb + M_OFF + ((l3 >> 4) * 512 + w * 128 + (l3 & 8) + ((l3 >> 2) & 1) + (l3 & 2)) * 32 + (l3 & 1) * 16;
      uint32_t yb = sb + X_OFF + (l3 & 1) * (XS + 16) + w * 512
                    + (((l3 >> 1) & 1) == rank ? (l3 >> 2) * 16 : YX - XS + ((l3 >> 2) ^ 4) * 16);
      mbar_wait(bars + B_Q * 8, 0);
      wg_wait<0>(); pinv<32>(ra);
      fin(NC - 1);
      if (ht == 64) OSTAMP(30);
      uint32_t t0 = 0, dt = 0;
      #pragma unroll 1
      for (int sg = 0; sg < 4; sg++, qa += 1024, yb += 128) {
        uint32_t qv[4][4], yv[4][4];
        #pragma unroll
        for (int i = 0; i < 4; i++) lds128(qv[i], qa + (i >> 1) * 512 + (i & 1) * 128);
        #pragma unroll
        for (int m = 0; m < 4; m++) {
          if (m == 3 && sg == 0) mbar_wait(bars + (B_YR + NC - 1) * 8, 0);
          ldsm4t(yv[m], yb + 2 * m * XS);
        }
        #pragma unroll
        for (int i = 0; i < 4; i++)
          sts128(qa + (i >> 1) * 512 + (i & 1) * 128, bmul2(qv[i][0], yv[0][i]), bmul2(qv[i][1], yv[1][i]), bmul2(qv[i][2], yv[2][i]), bmul2(qv[i][3], yv[3][i]));
        if (sg == 3) mbar_arrive(bars + B_CD * 8);
        fence_async_smem();
        __syncwarp();
        if (sg == 0) {
          mbar_wait(bars + B_GO * 8, 0);
          t0 = uni((uint32_t)clock());
          dt = uni(min(max((int)(lds32(sb + D_OFF + 44) + OA_END - t0) >> 2, 4 * OA_MIN), 4 * OA_MAX));
          t0 += w * (dt >> 2);
        }
        pace(t0, dt);
        #pragma unroll
        for (int hf = 0; hf < 2; hf++) {
          const int r = w * 128 + sg * 32 + hf * 512;
          if (!(AB & 2)) tma2d_store(&mOutA, cp * 16, rank * 1024 + r, sb + M_OFF + r * 32);
        }
      }
      bulk_commit(); bulk_wait_read();
      if (ht == 0) OSTAMP(31);
    }
  } else {
    asm volatile("setmaxnreg.dec.sync.aligned.u32 %0;" :: "n"(32));
    const uint32_t id2 = fresh(ids); IDS(id2);
    const uint32_t t_pf = (uint32_t)clock();
    if (warp == 14)
      asm volatile("prefetch.global.L2 [%0];" :: "l"(((lane & 1) ? P.v : P.k) + (rank * 2097152 + cp * 32 + (lane >> 1) * 131072)));
    if (warp != 15) cluster_wait();
    auto reduce_kv = [&](int i0, int i1) {
      float* kr = P.kv + hp * KV_PER_HP;
      mbar_wait(bars + B_Z * 8, 0);
      bar_sync(4, 352);
      #pragma unroll 1
      for (; i0 < i1; i0 += 2) {
        uint32_t p[2][4], q[2][4];
        const int i = (i0 + 2 * mb) & 15;
        const uint32_t pa = sb + M_OFF + (i & 3) * 2048 + (i >> 2) * 512 + (lane & 7) * 64 + (((lane >> 3) ^ (lane >> 1)) & 3) * 16;
        lds128(p[0], pa); lds128(q[0], pa + VT); lds128(p[1], pa + 2048); lds128(q[1], pa + VT + 2048);
        #pragma unroll
        for (int j = 0; j < 2; j++)
          asm volatile("red.relaxed.gpu.global.add.v4.f32 [%0], {%1,%2,%3,%4};" :: "l"(kr + (i >> 3) * 32 + (i + j) * 128 + lane * 4),
            "f"(__uint_as_float(p[j][0]) + __uint_as_float(q[j][0])), "f"(__uint_as_float(p[j][1]) + __uint_as_float(q[j][1])),
            "f"(__uint_as_float(p[j][2]) + __uint_as_float(q[j][2])), "f"(__uint_as_float(p[j][3]) + __uint_as_float(q[j][3])) : "memory");
      }
      if (i1 == 4) {
        const uint32_t za = sb + M_OFF + 8192 + lane * 4;
        #pragma unroll
        for (int h = 0; h < 2; h++)
          asm volatile("red.relaxed.gpu.global.add.f32 [%0], %1;" :: "l"(kr + h * 1056 + 1024 + lane),
            "f"(__uint_as_float(lds32(za + h * 128)) + __uint_as_float(lds32(za + h * 128 + VT))) : "memory");
      }
      bar_sync(5, 96);
    };
    auto convert_kv = [&](int u0, auto N_) {
      constexpr int N = N_.value;
      const float* kg = P.kv + (2 * n2 + rank) * KV_PER_HP;
      const uint32_t psb = uni(mapa(sb, rank ^ 1));
      auto put = [&](uint32_t o, uint32_t v0, uint32_t v1, uint32_t v2, uint32_t v3) {
        st_async128(psb + o, psb + BAR_OFF + B_KVB * 8, v0, v1, v2, v3);
        sts128(sb + o, v0, v1, v2, v3);
      };
      mbar_wait(bars + B_KVL * 8, 0);
      spin_until(&P.cnt[(2 * n2 + rank) * 32 + 1], uni(lds32(sb + D_OFF + 40)) * 8);
      float4 v[N][2];
      float z[2];
      #pragma unroll
      for (int j = 0; j < N; j++) {
        const float4* kr = reinterpret_cast<const float4*>(kg + ((u0 + j) >> 2) * 32 + (u0 + j) * 256) + lane;
        v[j][0] = __ldcg(kr); v[j][1] = __ldcg(kr + 32);
      }
      if (N == 2) { z[0] = __ldcg(kg + 1024 + lane); z[1] = __ldcg(kg + 2080 + lane); }
      #pragma unroll
      for (int j = 0; j < N; j++)
        put(KVB_OFF + (rank * 8 + u0 + j) * 640 + lane * 16,
            pack_bf16(v[j][0].x, v[j][0].y), pack_bf16(v[j][0].z, v[j][0].w), pack_bf16(v[j][1].x, v[j][1].y), pack_bf16(v[j][1].z, v[j][1].w));
      if (N == 2) {
        #pragma unroll
        for (int h = 0; h < 2; h++) {
          const uint32_t zz = pack_bf16(z[h], z[h]);
          put(KVB_OFF + (rank * 8 + h * 4 + (lane >> 3)) * 640 + 512 + (lane & 7) * 16, zz, zz, zz, zz);
        }
      }
      fence_async_smem();
      __syncwarp();
      mbar_arrive(bars + B_KVB * 8);
    };
    if (warp == 12) {
      uint32_t xs = 0;
      auto load_x = [&](int k) {
        tma2d_mc(sb + xs * SLOT + rank * 16384, &mX, k, mb * 256 + rank * 128, bars + (B_XF + xs) * 8);
        mbar_expect_tx(bars + (B_XF + xs) * 8, SLOT);
        xs = xs == 2 ? 0 : xs + 1;
      };
      load_x(64); load_x(128);
      mbar_expect_tx(bars + B_Q * 8, 32768);
      #pragma unroll 1
      for (int it = 1; it < 8; it++) {
        #pragma unroll
        for (int j = 0; j < 4; j++) {
          mbar_wait(bars + (B_EMPTY + j) * 8, (it - 1) & 1);
          TSTAMP(1, 4 * it + j);
          tma3d(sb + W_OFF + j * 8192, &mW, hp * 64, it * 128 + j * 32, 1, bars + (B_FULL + j) * 8);
          if (j == 1 || (j == 3 && it < 7)) load_x(it * 128 + j * 32 + 32);
          mbar_expect_tx(bars + (B_FULL + j) * 8, 8192);
        }
      }
      #pragma unroll 1
      for (int it = 0; it < 4; it++) {
        #pragma unroll
        for (int j = 0; j < 4; j++) {
          const uint32_t fb = bars + (B_FULL2 + j) * 8;
          if (j || it) mbar_wait(bars + (it ? B_EMPTY2 + j : B_EMPTY + (j | 1)) * 8, (it - 1) & 1);
          TSTAMP(5, 4 * it + j);
          tma2d_mc(sb + j * SLOT + 16384 + rank * 8192, &mWq, n2 * 128 + rank * 64, it * 256 + j * 64, fb);
          tma2d(sb + j * SLOT, &mX, it * 256 + j * 64, m2 * 128, fb);
          mbar_expect_tx(fb, SLOT);
          const int pc = 4 * it + j - Q_ST;
          if (pc >= 0) {
            mbar_wait(bars + B_MF * 8, 0);
            tma2d(sb + M_OFF + pc * 4096, &mQ, cp * 16, rank * 1024 + pc * 128, bars + B_Q * 8);
          }
        }
      }
      #pragma unroll 1
      for (int pc = 16 - Q_ST; pc < 8; pc++) tma2d(sb + M_OFF + pc * 4096, &mQ, cp * 16, rank * 1024 + pc * 128, bars + B_Q * 8);
      auto load_wo = [&](int st, uint32_t ph) {
        const uint32_t j = st & 3, fb = bars + (B_FULL2 + j) * 8, k = fresh(g2_k(st, n2) * 64);
        mbar_wait(bars + (B_EMPTY2 + j) * 8, ph);
        TSTAMP(5, 16 + st);
        tma2d_mc(sb + j * SLOT + 16384 + rank * 8192, &mWo, n2 * 128 + rank * 64, k, fb);
        mbar_expect_tx(fb, 16384);
      };
      load_wo(4, 1);
      mbar_wait(bars + (B_EMPTY2 + 1) * 8, 1);
      asm volatile(ELECT "cp.async.bulk.tensor.5d.shared::cluster.global.mbarrier::complete_tx::bytes.multicast::cluster [%0], [%1, {%3, %4, %4, %4, %5}], [%2], %6;\n}"
        :: "r"(sb + SLOT + rank * 16384), "l"(&mWp), "r"(bars + (B_FULL2 + 1) * 8), "r"(n2 * 128 + rank * 64), "r"(0), "r"(n2 * 4), "h"((uint16_t)3) : "memory");
      mbar_expect_tx(bars + (B_FULL2 + 1) * 8, SLOT);
      load_wo(2, 1); load_wo(3, 1);
      mbar_arrive(bars + B_QE * 8);
      #pragma unroll 1
      for (int it = 1; it < 4; it++) {
        load_wo(4 * it + 1, (it - 1) & 1); load_wo(4 * it + 2, (it - 1) & 1); load_wo(4 * it + 3, (it - 1) & 1);
        if (it < 3) load_wo(4 * it + 4, (it - 1) & 1);
      }
    } else if (warp == 13) {
      if ((sb & 0xffffff) != SB0) __trap();
      float4* zp = reinterpret_cast<float4*>(P.kv + hp * KV_PER_HP + mb * 264);
      const float4 z4 = make_float4(0.f, 0.f, 0.f, 0.f);
      zp[lane] = z4; zp[lane + 32] = z4;
      if (lane < 2) zp[lane + 64] = z4;
      if (lane == 0) P.cnt[hp * 32 + 8 + mb] = t_pf;
      if (SPEC) {
        uint4* op = P.o + m2 * 16384 + mb * (SPEC * 256) + lane;
        uint32_t t0 = t_pf + RS_T0 + mb * (RS_DT / 8);
        #pragma unroll 1
        for (int i = 0; i < 8; i++) {
          while ((int)((uint32_t)clock() - t0) < 0) __nanosleep(100);
          t0 += RS_DT;
          #pragma unroll
          for (int j = 0; j < SPEC; j++) op[(i * SPEC + j) * 32] = make_uint4(~0u, ~0u, ~0u, ~0u);
        }
      }
      fence_gpu();
      __syncwarp();
      unsigned gen = 0;
      if (lane == 0) gen = (atomicAdd(&P.cnt[hp * 32], 1u) >> 3) + 1;
      gen = uni(gen);
      sts32(sb + D_OFF + 40, gen);
      spin_until(&P.cnt[hp * 32], gen * 8);
      sts32(sb + D_OFF + 48, __ballot_sync(0xffffffffu, NEAR && __ldcg(&P.cnt[hp * 32 + 8 + (lane & 7)]) - t_pf + 4096 >= 8192));
      mbar_arrive(bars + B_Z * 8);
      reduce_kv(0, 4);
      mbar_arrive(mapa(bars, rank ^ 1) + B_KVL * 8);
      mbar_arrive(bars + B_MF * 8);
      OSTAMP(17);
      fence_gpu();
      red_add(&P.cnt[hp * 32 + 1]);
      OSTAMP(15);
      convert_kv(0, IC<2>());
      bar_sync(6, 288);
      fence_gpu();
      asm volatile(ELECT "st.relaxed.gpu.global.u32 [%0], %1;\n}" :: "l"(&P.cnt[(16 + m2) * 32 + n2]), "r"(gen) : "memory");
      OSTAMP(32);
    } else {
      if (warp == 14) {
        uint32_t t0 = t_pf + STG_T0;
        #pragma unroll 1
        for (int pc = 0; pc < 16; pc++) {
          const int rd = pc >> 2, u = pc & 3;
          const uint32_t gb = bars + (B_STG + (rd & 1) * 2 + (u >> 1)) * 8;
          if (pc == 8 || pc == 12) mbar_wait(bars + (B_SFREE + (rd & 1)) * 8, 0);
          if (!(u & 1)) mbar_expect_tx(gb, u ? 8192 : KB);
          pace(t0, STG_DT);
          TSTAMP(3, 16 + pc);
          tma3d(sb + M_OFF + (u < 2 ? (rd & 1) * KB + u * (KB / 2) : 2 * KB + (rd & 1) * 8192 + (u & 1) * 4096), u < 2 ? &mK : &mV,
                cp * 16, rank * 64 + rd * 16 - (u < 2), (u & 1) * 8, gb);
        }
        mbar_expect_tx(bars + B_H * 8, 4096);
        tma2d(sb + H_OFF, &mH, 0, (cp * 16 + rank * 8) * 128, bars + B_H * 8);
      }
      if (warp == 15) {
        uint32_t t0 = t_pf + b * 2;
        #pragma unroll 1
        for (int i = 0; i < PF_N; i++) {
          const int u = P.pf[i];
          const PfType& f = P.pt[u >> 4];
          pace(t0, i == 0 ? PF_DT0 : (i < PF_N1 ? PF_DT1 : PF_DT2));
          asm volatile("prefetch.global.L2 [%0];" :: "l"(f.base + ((g & 3) * f.gl + (g >> 2) * f.gh + mb * f.sp + rank * f.sr + (u & 15) * f.su
                                                                   + (lane >> 2) * f.l4 + ((lane >> 1) & 1) * f.l2 + (lane & 1) * 128)));
        }
        cluster_wait();
      }
      reduce_kv(warp * 6 - 80, warp * 6 - 74);
      convert_kv(warp * 3 - 40, IC<3>());
      {
        const int wg = 15 - warp;
        const unsigned gen = uni(lds32(sb + D_OFF + 40));
        const uint32_t ab = bars + B_FA * 8 + wg * 32, far = uni(lds32(sb + D_OFF + 48));
        const unsigned* fp = &P.cnt[SPEC ? (32 + m2 * 2 + wg) * 32 + lane : (16 + m2) * 32 + (lane >> 2)];
        uint32_t miss = ~0u, safe = t_pf;
        auto poll = [&]() {
          unsigned v;
          asm volatile("ld.relaxed.gpu.global.u32 %0, [%1];" : "=r"(v) : "l"(fp) : "memory");
          miss = __ballot_sync(0xffffffffu, v != gen);
        };
        mbar_arrive(ab + 8);
        mbar_wait(bars + B_QE * 8, 0);
        #pragma unroll 1
        for (int st = 2; st < 16; st += 2) {
          const int k = g2_k(st, n2), j = st & 3;
          const uint4* src = P.o + (m2 * 16 + k) * 1024 + wg * 512;
          const uint32_t eb = bars + (B_EMPTY2 + j) * 8, ph = ((st >> 2) - 1) & 1, dst = sb + j * SLOT + wg * 8192;
          if (!(AB & 4) && ((miss >> (2 * k)) & 15)) {
            #pragma unroll 1
            for (int n = 0; n < WAIT_BOUND && ((miss >> (2 * k)) & 15); n++) poll();
            if (!SPEC) asm volatile("fence.acquire.gpu;" ::: "memory");
            fence_async_global();
            safe = (uint32_t)clock() + FAR_DT;
          }
          if (st >= 4) {
            if ((far >> (k >> 1)) & 1) while ((int)(uni((uint32_t)clock()) - safe) < 0) {}
            mbar_wait(eb, j ? ph : ph ^ 1);
          }
          bulk_load(dst, src, 8192, ab + j * 8);
          mbar_expect_tx(ab + j * 8, 8192);
          if (st >= 4) mbar_wait(eb + 8, ph);
          bulk_load(dst + SLOT, src + 1024, 8192, ab + j * 8 + 8);
          mbar_expect_tx(ab + j * 8 + 8, 8192);
          if (st == 2) { OSTAMP(18 + wg * 15); if (wg) { sts32(sb + D_OFF + 44, (uint32_t)clock()); mbar_arrive(bars + B_GO * 8); } }
        }
      }
    }
  }
}

typedef CUresult (*EncodeFn)(CUtensorMap*, CUtensorMapDataType, cuuint32_t, void*, const cuuint64_t*, const cuuint64_t*,
                             const cuuint32_t*, const cuuint32_t*, CUtensorMapInterleave, CUtensorMapSwizzle,
                             CUtensorMapL2promotion, CUtensorMapFloatOOBfill);

void encode(EncodeFn fn, CUtensorMap* m, const void* ptr, int rank, const cuuint64_t* dims, const cuuint64_t* strides,
            const cuuint32_t* box, CUtensorMapSwizzle sw, CUtensorMapL2promotion pr) {
  const cuuint32_t es[5] = {1, 1, 1, 1, 1};
  fn(m, CU_TENSOR_MAP_DATA_TYPE_BFLOAT16, rank, const_cast<void*>(ptr), dims, strides, box, es,
     CU_TENSOR_MAP_INTERLEAVE_NONE, sw, pr, CU_TENSOR_MAP_FLOAT_OOB_FILL_NONE);
}

}

extern "C" void kernel_launch(void* const* d_in, const int* in_sizes, int n_in, void* d_out, int out_size) {
  (void)in_sizes; (void)n_in; (void)out_size;
  static EncodeFn fn = nullptr;
  static void *po, *pkv, *pcnt;
  if (!fn) {
    void* p = nullptr; cudaDriverEntryPointQueryResult qr;
    cudaGetDriverEntryPoint("cuTensorMapEncodeTiled", &p, cudaEnableDefault, &qr);
    fn = (EncodeFn)p;
    cudaGetSymbolAddress(&po, g_O); cudaGetSymbolAddress(&pkv, g_kv); cudaGetSymbolAddress(&pcnt, g_cnt);
    cudaFuncSetAttribute(fused_kernel, cudaFuncAttributeMaxDynamicSharedMemorySize, SMEM_BYTES);
  }
  const CUtensorMapL2promotion P128 = CU_TENSOR_MAP_L2_PROMOTION_L2_128B, P0 = CU_TENSOR_MAP_L2_PROMOTION_NONE;
  CUtensorMap mX, mW, mWq, mWo, mK, mV, mH, mQ, mOut, mOutA, mWp;
  { cuuint64_t d[2] = {1024, 2048}, s[1] = {2048}; cuuint32_t bx[2] = {64, 128}, bq[2] = {16, 128};
    encode(fn, &mX, d_in[6], 2, d, s, bx, CU_TENSOR_MAP_SWIZZLE_128B, P128);
    encode(fn, &mQ, d_in[0], 2, d, s, bq, CU_TENSOR_MAP_SWIZZLE_NONE, P128); }
  { cuuint64_t d[3] = {1024, 1024, 3}, s[2] = {6144, 2048}; cuuint32_t bx[3] = {64, 32, 2};
    encode(fn, &mW, d_in[7], 3, d, s, bx, CU_TENSOR_MAP_SWIZZLE_128B, P128); }
  { cuuint64_t d[2] = {1024, 1024}, s[1] = {6144}, so[1] = {2048}; cuuint32_t bx[2] = {64, 64};
    encode(fn, &mWq, d_in[7], 2, d, s, bx, CU_TENSOR_MAP_SWIZZLE_128B, P128);
    encode(fn, &mWo, d_in[8], 2, d, so, bx, CU_TENSOR_MAP_SWIZZLE_128B, P128); }
  { cuuint64_t d[5] = {1024, 2, 4, 4, 32}, s[4] = {2048, 16384, 4096, 65536}; cuuint32_t bx[5] = {64, 2, 4, 4, 4};
    encode(fn, &mWp, d_in[8], 5, d, s, bx, CU_TENSOR_MAP_SWIZZLE_128B, P128); }
  { cuuint64_t d[3] = {1024, 128, 16}, s[2] = {32768, 2048}; cuuint32_t bk[3] = {16, 17, 8}, bv[3] = {16, 16, 8};
    encode(fn, &mK, d_in[1], 3, d, s, bk, CU_TENSOR_MAP_SWIZZLE_32B, P128);
    encode(fn, &mV, d_in[2], 3, d, s, bv, CU_TENSOR_MAP_SWIZZLE_32B, P128); }
  { cuuint64_t d[2] = {16, 131072}, s[1] = {32}; cuuint32_t bx[2] = {16, 128};
    encode(fn, &mH, d_in[4], 2, d, s, bx, CU_TENSOR_MAP_SWIZZLE_32B, CU_TENSOR_MAP_L2_PROMOTION_L2_256B); }
  { cuuint64_t d[2] = {2048, 2048}, s[1] = {4096}; cuuint32_t bx[2] = {64, 16}, ba[2] = {16, 32};
    encode(fn, &mOut, d_out, 2, d, s, bx, CU_TENSOR_MAP_SWIZZLE_128B, P0);
    encode(fn, &mOutA, d_out, 2, d, s, ba, CU_TENSOR_MAP_SWIZZLE_NONE, P0); }
  Params P;
  P.shift = (const __nv_bfloat16*)d_in[3]; P.ssmD = (const __nv_bfloat16*)d_in[5];
  P.x = (const __nv_bfloat16*)d_in[6]; P.w = (const __nv_bfloat16*)d_in[7]; P.out = (__nv_bfloat16*)d_out; P.one = 1;
  P.o = (uint4*)po; P.kv = (float*)pkv; P.cnt = (unsigned*)pcnt;
  P.k = (const char*)d_in[1]; P.v = (const char*)d_in[2];
  P.pt[0] = {(const char*)d_in[6], 16 * 32768, 64 * 32768, 65536, 32768, 256, 4096, 2048};
  P.pt[1] = {(const char*)d_in[7] + 2048, 256, 1024, 16 * 6144, 8 * 6144, 128 * 6144, 6144, 2048};
  P.pt[2] = {(const char*)d_in[7], 512, 128 * 6144, 16 * 6144, 8 * 6144, 256 * 6144, 6144, 256};
  P.pt[3] = {(const char*)d_in[8], 512, 128 * 2048, 16 * 2048, 8 * 2048, 256 * 2048, 2048, 256};
  P.pt[4] = {(const char*)d_in[0], 256, 1024, 32768, 2097152, 262144, 4096, 2048};
  P.pt[5] = {(const char*)d_in[4], 16 * 32768, 64 * 32768, 65536, 32768, 4096, 512, 256};
  const uint8_t pf[32] = {PF_LIST};
  for (int i = 0; i < 32; i++) P.pf[i] = pf[i];
  const uint64_t cd[18] = {CONV_DESC};
  for (int i = 0; i < 18; i++) P.cd[i] = cd[i];
  fused_kernel<<<NCTA, NTHREADS, SMEM_BYTES, cudaStreamPerThread>>>(P, mX, mW, mWq, mWo, mK, mV, mH, mQ, mOut, mOutA, mWp);
}
```

```cpp
#include <cuda_runtime.h>
#include <cuda_bf16.h>
#include <cuda.h>
#include <stdint.h>

#define PARAM(name, value) constexpr int name = value
#define TUNE
namespace dflt {
PARAM(SK1, 2); PARAM(SK2, 3); PARAM(SK3, 2);
PARAM(OS, 7); PARAM(HT, 1); PARAM(PAUSE, 0); PARAM(PERM, 0x76154032); PARAM(ORD, 1); PARAM(OWNL, 1); PARAM(OCP, 1); PARAM(SMAP, 1); PARAM(NEAR, 1); PARAM(FAR_DT, 500); PARAM(SPEC, 8); PARAM(RS_T0, 12000); PARAM(RS_DT, 1000); PARAM(CI, 1); PARAM(CW, 2); PARAM(SF, 97); PARAM(CX, 1); PARAM(DRY, 0); PARAM(FG, 2); PARAM(HINT, 0); PARAM(HW, 0); PARAM(AB, 0); PARAM(EHI, 0); PARAM(MID, 3);
PARAM(STG_T0, 1300); PARAM(STG_DT, 540);
PARAM(Q_ST, 10);
PARAM(OA_END, 7400); PARAM(OA_MIN, 200); PARAM(OA_MAX, 450);
PARAM(PF_DT0, 200); PARAM(PF_DT1, 1060); PARAM(PF_DT2, 512); PARAM(PF_N1, 9);
}
#define PF_LIST 0x01, 0x11, 0x02, 0x12, 0x03, 0x13, 0x04, 0x14, 0x05, 0x15, 0x51, 0x06, 0x16, 0x20, 0x07, 0x17, 0x21, 0x22, 0x23, \
                0x40, 0x41, 0x42, 0x43, 0x44, 0x45, 0x46, 0x47, 0x30, 0x31, 0x32, 0x33
#define PF_N 31
#define WAIT_BOUND 262144

namespace {
using namespace dflt;
TUNE

constexpr int S_LEN = 2048;
constexpr int DM    = 1024;
constexpr int NCTA  = 128;
constexpr int NTHREADS = 512;
constexpr int SLOT  = 32768;
constexpr int W_OFF = 3 * SLOT;
constexpr int M_OFF = 4 * SLOT;
constexpr int VT    = 16 * 1152;
constexpr int T_OFF = M_OFF + 43008;
constexpr int XS    = 4096 + 16;
constexpr int YX    = 2048 + 16;
constexpr int X_OFF = T_OFF + 8192 + 2176;
constexpr int H_OFF = X_OFF + 8 * XS;
constexpr int A_OFF = H_OFF + 4096;
constexpr int F_OFF = A_OFF + 8192;
constexpr int BAR_OFF = F_OFF + 2048;
constexpr int D_OFF = BAR_OFF + 384;
constexpr int SMEM_BYTES = D_OFF + 64 + 256;
constexpr int KB = 8704;
constexpr int KVB_OFF = M_OFF + 32768;
static_assert(H_OFF % 256 == 0 && X_OFF % 128 == 0 && SMEM_BYTES <= 232448, "layout");
constexpr int B_XF = 0, B_F0 = 3, B_FULL = 4, B_FA = 4, B_FULL2 = 25, B_KVL = 24, B_STG = 8, B_X = 12, B_Z = 13, B_H = 14, B_Q = 15, B_YR = 16,
              B_SK = 29, B_GO = 30, B_QE = 31,
              B_EMPTY = 32, B_KVB = 36, B_EMPTY2 = 37, B_SFREE = 41, B_CD = 43, B_MF = 44, B_OD = 45, B_P0 = 46;
constexpr int KV_PER_HP = 2 * 1056;

__device__ __align__(1024) uint4 g_O[S_LEN * DM / 8];
__device__ __align__(128) float g_kv[16 * KV_PER_HP];
__device__ __align__(128) unsigned g_cnt[64 * 32];

#define OSTAMP(i) do {} while (0)
#define TSTAMP(k, i) do {} while (0)

__device__ __forceinline__ uint32_t cta_ids() {
  uint32_t b = blockIdx.x;
  if (SMAP) { asm("mov.u32 %0, %%smid;" : "=r"(b)); b = b >= 124 ? b - 124 : b + 8; }
  const uint32_t c = b >> 1, q = ((c - 36) * 37) >> 8;
  const uint32_t lo = (4 + c) << 12, mid = (((c - 4) & 7) << 8) + (((c - 4) >> 3) << 12), hi = ((c - 35) << 8) + q * (4096 - 7 * 256) + (4 << 12);
  uint32_t r;
  asm("{\n.reg .pred p, q;\nsetp.lt.u32 p, %4, 4;\nsetp.lt.u32 q, %4, 36;\nselp.u32 %0, %2, %3, q;\nselp.u32 %0, %1, %0, p;\n}" : "=&r"(r) : "r"(lo), "r"(mid), "r"(hi), "r"(c));
  if (PERM) r = (r & 0xfff) | ((((r & 0x700 ? PERM : 0x76543012) >> ((r >> 12) * 4)) & 7) << 12);
  return r + b;
}

#define ELECT "{\n.reg .pred e;\nelect.sync _|e, 0xffffffff;\n@e "
__device__ __forceinline__ uint32_t uni(uint32_t v) { return __shfl_sync(0xffffffffu, v, 0); }
__device__ __forceinline__ uint32_t fresh(uint32_t v) { asm volatile("" : "+r"(v)); return v; }
__device__ __forceinline__ uint32_t smem_u32(const void* p) { return (uint32_t)__cvta_generic_to_shared(p); }
__device__ __forceinline__ void mbar_init(uint32_t b, uint32_t c) { asm volatile(ELECT "mbarrier.init.shared::cta.b64 [%0], %1;\n}" :: "r"(b), "r"(c) : "memory"); }
__device__ __forceinline__ void mbar_expect_tx(uint32_t b, uint32_t bytes) { asm volatile(ELECT "mbarrier.arrive.expect_tx.shared::cta.b64 _, [%0], %1;\n}" :: "r"(b), "r"(bytes) : "memory"); }
__device__ __forceinline__ void mbar_arrive(uint32_t b) { asm volatile(ELECT "mbarrier.arrive.shared::cluster.b64 _, [%0];\n}" :: "r"(b) : "memory"); }
__device__ __forceinline__ void mbar_wait(uint32_t b, uint32_t ph) {
  asm volatile("{\n.reg .pred p;\n.reg .u32 n;\nmov.u32 n, 0;\n"
    "WAIT_LOOP:\nmbarrier.try_wait.parity.shared::cta.b64 p, [%0], %1;\n@p bra.uni WAIT_DONE;\n"
    "add.u32 n, n, 1;\nsetp.lt.u32 p, n, %2;\n@p bra.uni WAIT_LOOP;\nWAIT_DONE:\n}" :: "r"(b), "r"(ph), "n"(WAIT_BOUND) : "memory"); }
__device__ __forceinline__ void tma2d(uint32_t dst, const CUtensorMap* m, int c0, int c1, uint32_t bar) {
  asm volatile(ELECT "cp.async.bulk.tensor.2d.shared::cluster.global.mbarrier::complete_tx::bytes [%0], [%1, {%3, %4}], [%2];\n}"
    :: "r"(dst), "l"(m), "r"(bar), "r"(c0), "r"(c1) : "memory"); }
__device__ __forceinline__ void tma2d_mc(uint32_t dst, const CUtensorMap* m, int c0, int c1, uint32_t bar) {
  asm volatile(ELECT "cp.async.bulk.tensor.2d.shared::cluster.global.mbarrier::complete_tx::bytes.multicast::cluster [%0], [%1, {%3, %4}], [%2], %5;\n}"
    :: "r"(dst), "l"(m), "r"(bar), "r"(c0), "r"(c1), "h"((uint16_t)3) : "memory"); }
__device__ __forceinline__ void tma3d(uint32_t dst, const CUtensorMap* m, int c0, int c1, int c2, uint32_t bar) {
  asm volatile(ELECT "cp.async.bulk.tensor.3d.shared::cluster.global.mbarrier::complete_tx::bytes [%0], [%1, {%3, %4, %5}], [%2];\n}"
    :: "r"(dst), "l"(m), "r"(bar), "r"(c0), "r"(c1), "r"(c2) : "memory"); }
__device__ __forceinline__ void tma2d_store(const CUtensorMap* m, int c0, int c1, uint32_t src) {
  asm volatile(ELECT "cp.async.bulk.tensor.2d.global.shared::cta.bulk_group [%0, {%2, %3}], [%1];\n}"
    :: "l"(m), "r"(src), "r"(c0), "r"(c1) : "memory"); }
__device__ __forceinline__ void bulk_load(uint32_t dst, const void* src, uint32_t bytes, uint32_t bar) {
  asm volatile(ELECT "cp.async.bulk.shared::cluster.global.mbarrier::complete_tx::bytes [%0], [%1], %2, [%3];\n}"
    :: "r"(dst), "l"(src), "r"(bytes), "r"(bar) : "memory"); }
__device__ __forceinline__ void bulk_commit() { asm volatile("cp.async.bulk.commit_group;" ::: "memory"); }
__device__ __forceinline__ void bulk_wait_read() { asm volatile("cp.async.bulk.wait_group.read 0;" ::: "memory"); }
__device__ __forceinline__ void fence_async_smem() { asm volatile("fence.proxy.async.shared::cta;" ::: "memory"); }
__device__ __forceinline__ void bar_sync(int id, int n) { asm volatile("bar.sync %0, %1;" :: "r"(id), "r"(n) : "memory"); }
__device__ __forceinline__ void bar_arrive(int id, int n) { asm volatile("bar.arrive %0, %1;" :: "r"(id), "r"(n) : "memory"); }
__device__ __forceinline__ void wg_fence() { asm volatile("wgmma.fence.sync.aligned;" ::: "memory"); }
__device__ __forceinline__ void wg_commit() { asm volatile("wgmma.commit_group.sync.aligned;" ::: "memory"); }
template <int N> __device__ __forceinline__ void wg_wait() { asm volatile("wgmma.wait_group.sync.aligned %0;" :: "n"(N) : "memory"); }
constexpr uint32_t SB0 = 1024;
__host__ __device__ constexpr uint64_t cdesc(uint32_t off, uint32_t lbo, uint32_t sbo, uint32_t swz) {
  return (uint64_t)((SB0 + off) >> 4) | ((uint64_t)(lbo >> 4) << 16) | ((uint64_t)(sbo >> 4) << 32) | ((uint64_t)swz << 62); }
__device__ __forceinline__ uint64_t dofs(uint64_t d, uint32_t bytes) { return (d & 0xffffffff00000000ull) | (uint32_t)((uint32_t)d + (bytes >> 4)); }
__device__ __forceinline__ uint32_t mbar_try(uint32_t b, uint32_t ph) {
  uint32_t ok;
  asm volatile("{\n.reg .pred p;\nmbarrier.test_wait.parity.shared::cta.b64 p, [%1], %2;\nselp.u32 %0, 1, 0, p;\n}" : "=r"(ok) : "r"(b), "r"(ph) : "memory");
  return ok; }
__device__ __forceinline__ void arrive_at(uint32_t a, bool on) {
  asm volatile("{\n.reg .pred p;\nsetp.ne.b32 p, %1, 0;\n@p mbarrier.arrive.shared::cluster.b64 _, [%0];\n}" :: "r"(a), "r"((uint32_t)on) : "memory"); }
__device__ __forceinline__ void ldsm4(uint32_t* r, uint32_t a) {
  asm volatile("ldmatrix.sync.aligned.m8n8.x4.shared.b16 {%0,%1,%2,%3}, [%4];" : "=r"(r[0]), "=r"(r[1]), "=r"(r[2]), "=r"(r[3]) : "r"(a) : "memory"); }
__device__ __forceinline__ void ldsm4t(uint32_t* r, uint32_t a) {
  asm volatile("ldmatrix.sync.aligned.m8n8.x4.trans.shared.b16 {%0,%1,%2,%3}, [%4];" : "=r"(r[0]), "=r"(r[1]), "=r"(r[2]), "=r"(r[3]) : "r"(a) : "memory"); }
__device__ __forceinline__ void stsm4(uint32_t a, uint32_t r0, uint32_t r1, uint32_t r2, uint32_t r3) {
  asm volatile("stmatrix.sync.aligned.m8n8.x4.shared.b16 [%0], {%1,%2,%3,%4};" :: "r"(a), "r"(r0), "r"(r1), "r"(r2), "r"(r3) : "memory"); }
__device__ __forceinline__ void stsm4t(uint32_t a, uint32_t r0, uint32_t r1, uint32_t r2, uint32_t r3) {
  asm volatile("stmatrix.sync.aligned.m8n8.x4.trans.shared.b16 [%0], {%1,%2,%3,%4};" :: "r"(a), "r"(r0), "r"(r1), "r"(r2), "r"(r3) : "memory"); }
__device__ __forceinline__ uint32_t lds32(uint32_t a) { uint32_t v; asm volatile("ld.shared.b32 %0, [%1];" : "=r"(v) : "r"(a) : "memory"); return v; }
__device__ __forceinline__ void lds128(uint32_t* v, uint32_t a) { asm volatile("ld.shared.v4.b32 {%0,%1,%2,%3}, [%4];" : "=r"(v[0]), "=r"(v[1]), "=r"(v[2]), "=r"(v[3]) : "r"(a) : "memory"); }
__device__ __forceinline__ void sts32(uint32_t a, uint32_t v) { asm volatile("st.shared.b32 [%0], %1;" :: "r"(a), "r"(v) : "memory"); }
__device__ __forceinline__ void sts128(uint32_t a, uint32_t v0, uint32_t v1, uint32_t v2, uint32_t v3) {
  asm volatile("st.shared.v4.b32 [%0], {%1,%2,%3,%4};" :: "r"(a), "r"(v0), "r"(v1), "r"(v2), "r"(v3) : "memory"); }
__device__ __forceinline__ uint32_t pack_bf16(float lo, float hi) { uint32_t r; asm("cvt.rn.bf16x2.f32 %0, %1, %2;" : "=r"(r) : "f"(hi), "f"(lo)); return r; }
template <int ID = 0> __device__ __forceinline__ void sched_fence(uint32_t key) {
  asm volatile("{\n.reg .pred p;\nsetp.eq.u32 p, %0, %1;\nSF_LOOP:\n@p pmevent 1;\n@p bra.uni SF_LOOP;\n}" :: "r"(key), "n"(ID) : "memory");
}
template <int N> __device__ __forceinline__ void pinv(float* v) {
  #pragma unroll
  for (int i = 0; i < N; i++) asm volatile("" : "+f"(v[i]) :: "memory"); }
__device__ __forceinline__ uint32_t bmul2(uint32_t a, uint32_t b) { uint32_t r; asm("mul.rn.bf16x2 %0, %1, %2;" : "=r"(r) : "r"(a), "r"(b)); return r; }
__device__ __forceinline__ uint32_t badd2(uint32_t a, uint32_t b) { uint32_t r; asm("add.rn.bf16x2 %0, %1, %2;" : "=r"(r) : "r"(a), "r"(b)); return r; }
__device__ __forceinline__ void spin_until(const unsigned* p, unsigned target) {
  int n = 0;
  unsigned v;
  do { asm volatile("ld.relaxed.gpu.global.u32 %0, [%1];" : "=r"(v) : "l"(p) : "memory"); } while ((int)(v - target) < 0 && ++n < WAIT_BOUND);
  asm volatile("fence.acquire.gpu;" ::: "memory");
}
__device__ __forceinline__ void cluster_wait() { asm volatile("barrier.cluster.wait.aligned;" ::: "memory"); }
__device__ __forceinline__ void fence_gpu() { asm volatile("fence.release.gpu;" ::: "memory"); }
__device__ __forceinline__ void fence_async_global() { asm volatile("fence.proxy.async.global;" ::: "memory"); }
__device__ __forceinline__ void red_add(unsigned* p) { asm volatile(ELECT "red.relaxed.gpu.global.add.u32 [%0], 1;\n}" :: "l"(p) : "memory"); }
__device__ __forceinline__ float rcp_fast(float x) { float r; asm("rcp.approx.ftz.f32 %0, %1;" : "=f"(r) : "f"(x)); return r; }
__device__ __forceinline__ uint32_t mapa(uint32_t a, uint32_t rank) { uint32_t r; asm("mapa.shared::cluster.u32 %0, %1, %2;" : "=r"(r) : "r"(a), "r"(rank)); return r; }
__device__ __forceinline__ void st_async128(uint32_t a, uint32_t bar, uint32_t v0, uint32_t v1, uint32_t v2, uint32_t v3) {
  asm volatile("st.async.weak.shared::cluster.mbarrier::complete_tx::bytes.v4.b32 [%0], {%2,%3,%4,%5}, [%1];"
    :: "r"(a), "r"(bar), "r"(v0), "r"(v1), "r"(v2), "r"(v3) : "memory"); }
__device__ __forceinline__ int fresh_tid() { int t; asm volatile("mov.u32 %0, %%tid.x;" : "=r"(t)); return t; }
__device__ __forceinline__ void pace(uint32_t& t, uint32_t dt) {
  uint32_t c;
  while ((int)((c = uni((uint32_t)clock())) - t) < 0) __nanosleep(20);
  t = ((int)(c - t) > (int)dt ? c : t) + dt;
}
template <int LOG> __device__ __forceinline__ void unit_root(int a, float& c, float& s) {
  const float x = (float)((a << (32 - LOG)) >> (32 - LOG)) * (6.283185307179586f / (1 << LOG));
  c = __cosf(x); s = __sinf(x); }

struct D2 { uint64_t a, b; };
template <int TA, int TB> __device__ __forceinline__ void ss128p(float* d, uint64_t da, uint64_t db, int sd) {
  asm volatile("{\n.reg .pred p;\nsetp.ne.b32 p, %68, 0;\n"
    "wgmma.mma_async.sync.aligned.m64n128k16.f32.bf16.bf16 "
    "{%0, %1, %2, %3, %4, %5, %6, %7, %8, %9, %10, %11, %12, %13, %14, %15, "
    "%16, %17, %18, %19, %20, %21, %22, %23, %24, %25, %26, %27, %28, %29, %30, %31, "
    "%32, %33, %34, %35, %36, %37, %38, %39, %40, %41, %42, %43, %44, %45, %46, %47, "
    "%48, %49, %50, %51, %52, %53, %54, %55, %56, %57, %58, %59, %60, %61, %62, %63}, %64, %65, p, 1, 1, %66, %67;\n}\n"
    : "+f"(d[0]), "+f"(d[1]), "+f"(d[2]), "+f"(d[3]), "+f"(d[4]), "+f"(d[5]), "+f"(d[6]), "+f"(d[7]),
      "+f"(d[8]), "+f"(d[9]), "+f"(d[10]), "+f"(d[11]), "+f"(d[12]), "+f"(d[13]), "+f"(d[14]), "+f"(d[15]),
      "+f"(d[16]), "+f"(d[17]), "+f"(d[18]), "+f"(d[19]), "+f"(d[20]), "+f"(d[21]), "+f"(d[22]), "+f"(d[23]),
      "+f"(d[24]), "+f"(d[25]), "+f"(d[26]), "+f"(d[27]), "+f"(d[28]), "+f"(d[29]), "+f"(d[30]), "+f"(d[31]),
      "+f"(d[32]), "+f"(d[33]), "+f"(d[34]), "+f"(d[35]), "+f"(d[36]), "+f"(d[37]), "+f"(d[38]), "+f"(d[39]),
      "+f"(d[40]), "+f"(d[41]), "+f"(d[42]), "+f"(d[43]), "+f"(d[44]), "+f"(d[45]), "+f"(d[46]), "+f"(d[47]),
      "+f"(d[48]), "+f"(d[49]), "+f"(d[50]), "+f"(d[51]), "+f"(d[52]), "+f"(d[53]), "+f"(d[54]), "+f"(d[55]),
      "+f"(d[56]), "+f"(d[57]), "+f"(d[58]), "+f"(d[59]), "+f"(d[60]), "+f"(d[61]), "+f"(d[62]), "+f"(d[63])
    : "l"(da), "l"(db), "n"(TA), "n"(TB), "r"(sd));
}
template <int TA, int TB> __device__ __forceinline__ void ss128a(float* d, uint64_t da, uint64_t db) {
  asm volatile("{\n.reg .pred p;\nsetp.eq.b32 p, 0, 0;\n"
    "wgmma.mma_async.sync.aligned.m64n128k16.f32.bf16.bf16 "
    "{%0, %1, %2, %3, %4, %5, %6, %7, %8, %9, %10, %11, %12, %13, %14, %15, "
    "%16, %17, %18, %19, %20, %21, %22, %23, %24, %25, %26, %27, %28, %29, %30, %31, "
    "%32, %33, %34, %35, %36, %37, %38, %39, %40, %41, %42, %43, %44, %45, %46, %47, "
    "%48, %49, %50, %51, %52, %53, %54, %55, %56, %57, %58, %59, %60, %61, %62, %63}, %64, %65, p, 1, 1, %66, %67;\n}\n"
    : "+f"(d[0]), "+f"(d[1]), "+f"(d[2]), "+f"(d[3]), "+f"(d[4]), "+f"(d[5]), "+f"(d[6]), "+f"(d[7]),
      "+f"(d[8]), "+f"(d[9]), "+f"(d[10]), "+f"(d[11]), "+f"(d[12]), "+f"(d[13]), "+f"(d[14]), "+f"(d[15]),
      "+f"(d[16]), "+f"(d[17]), "+f"(d[18]), "+f"(d[19]), "+f"(d[20]), "+f"(d[21]), "+f"(d[22]), "+f"(d[23]),
      "+f"(d[24]), "+f"(d[25]), "+f"(d[26]), "+f"(d[27]), "+f"(d[28]), "+f"(d[29]), "+f"(d[30]), "+f"(d[31]),
      "+f"(d[32]), "+f"(d[33]), "+f"(d[34]), "+f"(d[35]), "+f"(d[36]), "+f"(d[37]), "+f"(d[38]), "+f"(d[39]),
      "+f"(d[40]), "+f"(d[41]), "+f"(d[42]), "+f"(d[43]), "+f"(d[44]), "+f"(d[45]), "+f"(d[46]), "+f"(d[47]),
      "+f"(d[48]), "+f"(d[49]), "+f"(d[50]), "+f"(d[51]), "+f"(d[52]), "+f"(d[53]), "+f"(d[54]), "+f"(d[55]),
      "+f"(d[56]), "+f"(d[57]), "+f"(d[58]), "+f"(d[59]), "+f"(d[60]), "+f"(d[61]), "+f"(d[62]), "+f"(d[63])
    : "l"(da), "l"(db), "n"(TA), "n"(TB));
}
template <int TA, int TB> __device__ __forceinline__ void ss128z(float* d, uint64_t da, uint64_t db) {
  asm volatile("{\n.reg .pred p;\nsetp.ne.b32 p, 0, 0;\n"
    "wgmma.mma_async.sync.aligned.m64n128k16.f32.bf16.bf16 "
    "{%0, %1, %2, %3, %4, %5, %6, %7, %8, %9, %10, %11, %12, %13, %14, %15, "
    "%16, %17, %18, %19, %20, %21, %22, %23, %24, %25, %26, %27, %28, %29, %30, %31, "
    "%32, %33, %34, %35, %36, %37, %38, %39, %40, %41, %42, %43, %44, %45, %46, %47, "
    "%48, %49, %50, %51, %52, %53, %54, %55, %56, %57, %58, %59, %60, %61, %62, %63}, %64, %65, p, 1, 1, %66, %67;\n}\n"
    : "=f"(d[0]), "=f"(d[1]), "=f"(d[2]), "=f"(d[3]), "=f"(d[4]), "=f"(d[5]), "=f"(d[6]), "=f"(d[7]),
      "=f"(d[8]), "=f"(d[9]), "=f"(d[10]), "=f"(d[11]), "=f"(d[12]), "=f"(d[13]), "=f"(d[14]), "=f"(d[15]),
      "=f"(d[16]), "=f"(d[17]), "=f"(d[18]), "=f"(d[19]), "=f"(d[20]), "=f"(d[21]), "=f"(d[22]), "=f"(d[23]),
      "=f"(d[24]), "=f"(d[25]), "=f"(d[26]), "=f"(d[27]), "=f"(d[28]), "=f"(d[29]), "=f"(d[30]), "=f"(d[31]),
      "=f"(d[32]), "=f"(d[33]), "=f"(d[34]), "=f"(d[35]), "=f"(d[36]), "=f"(d[37]), "=f"(d[38]), "=f"(d[39]),
      "=f"(d[40]), "=f"(d[41]), "=f"(d[42]), "=f"(d[43]), "=f"(d[44]), "=f"(d[45]), "=f"(d[46]), "=f"(d[47]),
      "=f"(d[48]), "=f"(d[49]), "=f"(d[50]), "=f"(d[51]), "=f"(d[52]), "=f"(d[53]), "=f"(d[54]), "=f"(d[55]),
      "=f"(d[56]), "=f"(d[57]), "=f"(d[58]), "=f"(d[59]), "=f"(d[60]), "=f"(d[61]), "=f"(d[62]), "=f"(d[63])
    : "l"(da), "l"(db), "n"(TA), "n"(TB));
}
template <int TA, int TB> __device__ __forceinline__ void ss64a(float* d, uint64_t da, uint64_t db) {
  asm volatile("{\n.reg .pred p;\nsetp.eq.b32 p, 0, 0;\n"
    "wgmma.mma_async.sync.aligned.m64n64k16.f32.bf16.bf16 "
    "{%0, %1, %2, %3, %4, %5, %6, %7, %8, %9, %10, %11, %12, %13, %14, %15, "
    "%16, %17, %18, %19, %20, %21, %22, %23, %24, %25, %26, %27, %28, %29, %30, %31}, %32, %33, p, 1, 1, %34, %35;\n}\n"
    : "+f"(d[0]), "+f"(d[1]), "+f"(d[2]), "+f"(d[3]), "+f"(d[4]), "+f"(d[5]), "+f"(d[6]), "+f"(d[7]),
      "+f"(d[8]), "+f"(d[9]), "+f"(d[10]), "+f"(d[11]), "+f"(d[12]), "+f"(d[13]), "+f"(d[14]), "+f"(d[15]),
      "+f"(d[16]), "+f"(d[17]), "+f"(d[18]), "+f"(d[19]), "+f"(d[20]), "+f"(d[21]), "+f"(d[22]), "+f"(d[23]),
      "+f"(d[24]), "+f"(d[25]), "+f"(d[26]), "+f"(d[27]), "+f"(d[28]), "+f"(d[29]), "+f"(d[30]), "+f"(d[31])
    : "l"(da), "l"(db), "n"(TA), "n"(TB));
}
template <int TA, int TB> __device__ __forceinline__ void ss64z(float* d, uint64_t da, uint64_t db) {
  asm volatile("{\n.reg .pred p;\nsetp.ne.b32 p, 0, 0;\n"
    "wgmma.mma_async.sync.aligned.m64n64k16.f32.bf16.bf16 "
    "{%0, %1, %2, %3, %4, %5, %6, %7, %8, %9, %10, %11, %12, %13, %14, %15, "
    "%16, %17, %18, %19, %20, %21, %22, %23, %24, %25, %26, %27, %28, %29, %30, %31}, %32, %33, p, 1, 1, %34, %35;\n}\n"
    : "=f"(d[0]), "=f"(d[1]), "=f"(d[2]), "=f"(d[3]), "=f"(d[4]), "=f"(d[5]), "=f"(d[6]), "=f"(d[7]),
      "=f"(d[8]), "=f"(d[9]), "=f"(d[10]), "=f"(d[11]), "=f"(d[12]), "=f"(d[13]), "=f"(d[14]), "=f"(d[15]),
      "=f"(d[16]), "=f"(d[17]), "=f"(d[18]), "=f"(d[19]), "=f"(d[20]), "=f"(d[21]), "=f"(d[22]), "=f"(d[23]),
      "=f"(d[24]), "=f"(d[25]), "=f"(d[26]), "=f"(d[27]), "=f"(d[28]), "=f"(d[29]), "=f"(d[30]), "=f"(d[31])
    : "l"(da), "l"(db), "n"(TA), "n"(TB));
}
__device__ __forceinline__ void ss64x4(float* d, const D2* c, int on) {
  asm volatile("{\n.reg .pred p, z, c;\nsetp.eq.b32 p, 0, 0;\nsetp.ne.b32 z, 0, 0;\nsetp.eq.b32 c, %40, 0;\n"
    "wgmma.mma_async.sync.aligned.m64n64k16.f32.bf16.bf16 "
    "{%0, %1, %2, %3, %4, %5, %6, %7, %8, %9, %10, %11, %12, %13, %14, %15, "
    "%16, %17, %18, %19, %20, %21, %22, %23, %24, %25, %26, %27, %28, %29, %30, %31}, %32, %33, z, 1, 1, 0, 1;\n"
    "wgmma.commit_group.sync.aligned;\n@c bra.uni X4_DONE;\n"
    "wgmma.mma_async.sync.aligned.m64n64k16.f32.bf16.bf16 "
    "{%0, %1, %2, %3, %4, %5, %6, %7, %8, %9, %10, %11, %12, %13, %14, %15, "
    "%16, %17, %18, %19, %20, %21, %22, %23, %24, %25, %26, %27, %28, %29, %30, %31}, %34, %35, p, 1, 1, 0, 1;\n"
    "wgmma.mma_async.sync.aligned.m64n64k16.f32.bf16.bf16 "
    "{%0, %1, %2, %3, %4, %5, %6, %7, %8, %9, %10, %11, %12, %13, %14, %15, "
    "%16, %17, %18, %19, %20, %21, %22, %23, %24, %25, %26, %27, %28, %29, %30, %31}, %36, %37, p, 1, 1, 0, 1;\n"
    "wgmma.mma_async.sync.aligned.m64n64k16.f32.bf16.bf16 "
    "{%0, %1, %2, %3, %4, %5, %6, %7, %8, %9, %10, %11, %12, %13, %14, %15, "
    "%16, %17, %18, %19, %20, %21, %22, %23, %24, %25, %26, %27, %28, %29, %30, %31}, %38, %39, p, 1, 1, 0, 1;\n"
    "wgmma.commit_group.sync.aligned;\nX4_DONE:\n}\n"
    : "=f"(d[0]), "=f"(d[1]), "=f"(d[2]), "=f"(d[3]), "=f"(d[4]), "=f"(d[5]), "=f"(d[6]), "=f"(d[7]),
      "=f"(d[8]), "=f"(d[9]), "=f"(d[10]), "=f"(d[11]), "=f"(d[12]), "=f"(d[13]), "=f"(d[14]), "=f"(d[15]),
      "=f"(d[16]), "=f"(d[17]), "=f"(d[18]), "=f"(d[19]), "=f"(d[20]), "=f"(d[21]), "=f"(d[22]), "=f"(d[23]),
      "=f"(d[24]), "=f"(d[25]), "=f"(d[26]), "=f"(d[27]), "=f"(d[28]), "=f"(d[29]), "=f"(d[30]), "=f"(d[31])
    : "l"(c[0].a), "l"(c[0].b), "l"(c[1].a), "l"(c[1].b), "l"(c[2].a), "l"(c[2].b), "l"(c[3].a), "l"(c[3].b), "r"(on));
}
template <int TB> __device__ __forceinline__ void rs32a(float* d, const uint32_t* a, uint64_t db) {
  asm volatile("{\n.reg .pred p;\nsetp.eq.b32 p, 0, 0;\n"
    "wgmma.mma_async.sync.aligned.m64n32k16.f32.bf16.bf16 "
    "{%0, %1, %2, %3, %4, %5, %6, %7, %8, %9, %10, %11, %12, %13, %14, %15}, {%16, %17, %18, %19}, %20, p, 1, 1, %21;\n}\n"
    : "+f"(d[0]), "+f"(d[1]), "+f"(d[2]), "+f"(d[3]), "+f"(d[4]), "+f"(d[5]), "+f"(d[6]), "+f"(d[7]),
      "+f"(d[8]), "+f"(d[9]), "+f"(d[10]), "+f"(d[11]), "+f"(d[12]), "+f"(d[13]), "+f"(d[14]), "+f"(d[15])
    : "r"(a[0]), "r"(a[1]), "r"(a[2]), "r"(a[3]), "l"(db), "n"(TB));
}
template <int TB> __device__ __forceinline__ void rs32z(float* d, const uint32_t* a, uint64_t db) {
  asm volatile("{\n.reg .pred p;\nsetp.ne.b32 p, 0, 0;\n"
    "wgmma.mma_async.sync.aligned.m64n32k16.f32.bf16.bf16 "
    "{%0, %1, %2, %3, %4, %5, %6, %7, %8, %9, %10, %11, %12, %13, %14, %15}, {%16, %17, %18, %19}, %20, p, 1, 1, %21;\n}\n"
    : "=&f"(d[0]), "=&f"(d[1]), "=&f"(d[2]), "=&f"(d[3]), "=&f"(d[4]), "=&f"(d[5]), "=&f"(d[6]), "=&f"(d[7]),
      "=&f"(d[8]), "=&f"(d[9]), "=&f"(d[10]), "=&f"(d[11]), "=&f"(d[12]), "=&f"(d[13]), "=&f"(d[14]), "=&f"(d[15])
    : "r"(a[0]), "r"(a[1]), "r"(a[2]), "r"(a[3]), "l"(db), "n"(TB));
}
template <int TB> __device__ __forceinline__ void rs40a(float* d, const uint32_t* a, uint64_t db) {
  asm volatile("{\n.reg .pred p;\nsetp.eq.b32 p, 0, 0;\n"
    "wgmma.mma_async.sync.aligned.m64n40k16.f32.bf16.bf16 "
    "{%0, %1, %2, %3, %4, %5, %6, %7, %8, %9, %10, %11, %12, %13, %14, %15, "
    "%16, %17, %18, %19}, {%20, %21, %22, %23}, %24, p, 1, 1, %25;\n}\n"
    : "+f"(d[0]), "+f"(d[1]), "+f"(d[2]), "+f"(d[3]), "+f"(d[4]), "+f"(d[5]), "+f"(d[6]), "+f"(d[7]),
      "+f"(d[8]), "+f"(d[9]), "+f"(d[10]), "+f"(d[11]), "+f"(d[12]), "+f"(d[13]), "+f"(d[14]), "+f"(d[15]),
      "+f"(d[16]), "+f"(d[17]), "+f"(d[18]), "+f"(d[19])
    : "r"(a[0]), "r"(a[1]), "r"(a[2]), "r"(a[3]), "l"(db), "n"(TB));
}
template <int TB> __device__ __forceinline__ void rs40z(float* d, const uint32_t* a, uint64_t db) {
  asm volatile("{\n.reg .pred p;\nsetp.ne.b32 p, 0, 0;\n"
    "wgmma.mma_async.sync.aligned.m64n40k16.f32.bf16.bf16 "
    "{%0, %1, %2, %3, %4, %5, %6, %7, %8, %9, %10, %11, %12, %13, %14, %15, "
    "%16, %17, %18, %19}, {%20, %21, %22, %23}, %24, p, 1, 1, %25;\n}\n"
    : "=&f"(d[0]), "=&f"(d[1]), "=&f"(d[2]), "=&f"(d[3]), "=&f"(d[4]), "=&f"(d[5]), "=&f"(d[6]), "=&f"(d[7]),
      "=&f"(d[8]), "=&f"(d[9]), "=&f"(d[10]), "=&f"(d[11]), "=&f"(d[12]), "=&f"(d[13]), "=&f"(d[14]), "=&f"(d[15]),
      "=&f"(d[16]), "=&f"(d[17]), "=&f"(d[18]), "=&f"(d[19])
    : "r"(a[0]), "r"(a[1]), "r"(a[2]), "r"(a[3]), "l"(db), "n"(TB));
}
template <int TB> __device__ __forceinline__ void rs72a(float* d, const uint32_t* a, uint64_t db) {
  asm volatile("{\n.reg .pred p;\nsetp.eq.b32 p, 0, 0;\n"
    "wgmma.mma_async.sync.aligned.m64n72k16.f32.bf16.bf16 "
    "{%0, %1, %2, %3, %4, %5, %6, %7, %8, %9, %10, %11, %12, %13, %14, %15, "
    "%16, %17, %18, %19, %20, %21, %22, %23, %24, %25, %26, %27, %28, %29, %30, %31, "
    "%32, %33, %34, %35}, {%36, %37, %38, %39}, %40, p, 1, 1, %41;\n}\n"
    : "+f"(d[0]), "+f"(d[1]), "+f"(d[2]), "+f"(d[3]), "+f"(d[4]), "+f"(d[5]), "+f"(d[6]), "+f"(d[7]),
      "+f"(d[8]), "+f"(d[9]), "+f"(d[10]), "+f"(d[11]), "+f"(d[12]), "+f"(d[13]), "+f"(d[14]), "+f"(d[15]),
      "+f"(d[16]), "+f"(d[17]), "+f"(d[18]), "+f"(d[19]), "+f"(d[20]), "+f"(d[21]), "+f"(d[22]), "+f"(d[23]),
      "+f"(d[24]), "+f"(d[25]), "+f"(d[26]), "+f"(d[27]), "+f"(d[28]), "+f"(d[29]), "+f"(d[30]), "+f"(d[31]),
      "+f"(d[32]), "+f"(d[33]), "+f"(d[34]), "+f"(d[35])
    : "r"(a[0]), "r"(a[1]), "r"(a[2]), "r"(a[3]), "l"(db), "n"(TB));
}
template <int TB> __device__ __forceinline__ void rs72z(float* d, const uint32_t* a, uint64_t db) {
  asm volatile("{\n.reg .pred p;\nsetp.ne.b32 p, 0, 0;\n"
    "wgmma.mma_async.sync.aligned.m64n72k16.f32.bf16.bf16 "
    "{%0, %1, %2, %3, %4, %5, %6, %7, %8, %9, %10, %11, %12, %13, %14, %15, "
    "%16, %17, %18, %19, %20, %21, %22, %23, %24, %25, %26, %27, %28, %29, %30, %31, "
    "%32, %33, %34, %35}, {%36, %37, %38, %39}, %40, p, 1, 1, %41;\n}\n"
    : "=&f"(d[0]), "=&f"(d[1]), "=&f"(d[2]), "=&f"(d[3]), "=&f"(d[4]), "=&f"(d[5]), "=&f"(d[6]), "=&f"(d[7]),
      "=&f"(d[8]), "=&f"(d[9]), "=&f"(d[10]), "=&f"(d[11]), "=&f"(d[12]), "=&f"(d[13]), "=&f"(d[14]), "=&f"(d[15]),
      "=&f"(d[16]), "=&f"(d[17]), "=&f"(d[18]), "=&f"(d[19]), "=&f"(d[20]), "=&f"(d[21]), "=&f"(d[22]), "=&f"(d[23]),
      "=&f"(d[24]), "=&f"(d[25]), "=&f"(d[26]), "=&f"(d[27]), "=&f"(d[28]), "=&f"(d[29]), "=&f"(d[30]), "=&f"(d[31]),
      "=&f"(d[32]), "=&f"(d[33]), "=&f"(d[34]), "=&f"(d[35])
    : "r"(a[0]), "r"(a[1]), "r"(a[2]), "r"(a[3]), "l"(db), "n"(TB));
}
template <int TB> __device__ __forceinline__ void rs128a(float* d, const uint32_t* a, uint64_t db) {
  asm volatile("{\n.reg .pred p;\nsetp.eq.b32 p, 0, 0;\n"
    "wgmma.mma_async.sync.aligned.m64n128k16.f32.bf16.bf16 "
    "{%0, %1, %2, %3, %4, %5, %6, %7, %8, %9, %10, %11, %12, %13, %14, %15, "
    "%16, %17, %18, %19, %20, %21, %22, %23, %24, %25, %26, %27, %28, %29, %30, %31, "
    "%32, %33, %34, %35, %36, %37, %38, %39, %40, %41, %42, %43, %44, %45, %46, %47, "
    "%48, %49, %50, %51, %52, %53, %54, %55, %56, %57, %58, %59, %60, %61, %62, %63}, {%64, %65, %66, %67}, %68, p, 1, 1, %69;\n}\n"
    : "+f"(d[0]), "+f"(d[1]), "+f"(d[2]), "+f"(d[3]), "+f"(d[4]), "+f"(d[5]), "+f"(d[6]), "+f"(d[7]),
      "+f"(d[8]), "+f"(d[9]), "+f"(d[10]), "+f"(d[11]), "+f"(d[12]), "+f"(d[13]), "+f"(d[14]), "+f"(d[15]),
      "+f"(d[16]), "+f"(d[17]), "+f"(d[18]), "+f"(d[19]), "+f"(d[20]), "+f"(d[21]), "+f"(d[22]), "+f"(d[23]),
      "+f"(d[24]), "+f"(d[25]), "+f"(d[26]), "+f"(d[27]), "+f"(d[28]), "+f"(d[29]), "+f"(d[30]), "+f"(d[31]),
      "+f"(d[32]), "+f"(d[33]), "+f"(d[34]), "+f"(d[35]), "+f"(d[36]), "+f"(d[37]), "+f"(d[38]), "+f"(d[39]),
      "+f"(d[40]), "+f"(d[41]), "+f"(d[42]), "+f"(d[43]), "+f"(d[44]), "+f"(d[45]), "+f"(d[46]), "+f"(d[47]),
      "+f"(d[48]), "+f"(d[49]), "+f"(d[50]), "+f"(d[51]), "+f"(d[52]), "+f"(d[53]), "+f"(d[54]), "+f"(d[55]),
      "+f"(d[56]), "+f"(d[57]), "+f"(d[58]), "+f"(d[59]), "+f"(d[60]), "+f"(d[61]), "+f"(d[62]), "+f"(d[63])
    : "r"(a[0]), "r"(a[1]), "r"(a[2]), "r"(a[3]), "l"(db), "n"(TB));
}
template <int TB> __device__ __forceinline__ void rs128z(float* d, const uint32_t* a, uint64_t db) {
  asm volatile("{\n.reg .pred p;\nsetp.ne.b32 p, 0, 0;\n"
    "wgmma.mma_async.sync.aligned.m64n128k16.f32.bf16.bf16 "
    "{%0, %1, %2, %3, %4, %5, %6, %7, %8, %9, %10, %11, %12, %13, %14, %15, "
    "%16, %17, %18, %19, %20, %21, %22, %23, %24, %25, %26, %27, %28, %29, %30, %31, "
    "%32, %33, %34, %35, %36, %37, %38, %39, %40, %41, %42, %43, %44, %45, %46, %47, "
    "%48, %49, %50, %51, %52, %53, %54, %55, %56, %57, %58, %59, %60, %61, %62, %63}, {%64, %65, %66, %67}, %68, p, 1, 1, %69;\n}\n"
    : "=&f"(d[0]), "=&f"(d[1]), "=&f"(d[2]), "=&f"(d[3]), "=&f"(d[4]), "=&f"(d[5]), "=&f"(d[6]), "=&f"(d[7]),
      "=&f"(d[8]), "=&f"(d[9]), "=&f"(d[10]), "=&f"(d[11]), "=&f"(d[12]), "=&f"(d[13]), "=&f"(d[14]), "=&f"(d[15]),
      "=&f"(d[16]), "=&f"(d[17]), "=&f"(d[18]), "=&f"(d[19]), "=&f"(d[20]), "=&f"(d[21]), "=&f"(d[22]), "=&f"(d[23]),
      "=&f"(d[24]), "=&f"(d[25]), "=&f"(d[26]), "=&f"(d[27]), "=&f"(d[28]), "=&f"(d[29]), "=&f"(d[30]), "=&f"(d[31]),
      "=&f"(d[32]), "=&f"(d[33]), "=&f"(d[34]), "=&f"(d[35]), "=&f"(d[36]), "=&f"(d[37]), "=&f"(d[38]), "=&f"(d[39]),
      "=&f"(d[40]), "=&f"(d[41]), "=&f"(d[42]), "=&f"(d[43]), "=&f"(d[44]), "=&f"(d[45]), "=&f"(d[46]), "=&f"(d[47]),
      "=&f"(d[48]), "=&f"(d[49]), "=&f"(d[50]), "=&f"(d[51]), "=&f"(d[52]), "=&f"(d[53]), "=&f"(d[54]), "=&f"(d[55]),
      "=&f"(d[56]), "=&f"(d[57]), "=&f"(d[58]), "=&f"(d[59]), "=&f"(d[60]), "=&f"(d[61]), "=&f"(d[62]), "=&f"(d[63])
    : "r"(a[0]), "r"(a[1]), "r"(a[2]), "r"(a[3]), "l"(db), "n"(TB));
}

template <int V> struct IC { static constexpr int value = V; };
struct PfType { const char* base; uint32_t gl, gh, sp, sr, su, l4, l2; };
struct Params {
  const __nv_bfloat16 *x, *w;
  uint32_t one;
  const __nv_bfloat16 *shift, *ssmD;
  __nv_bfloat16* out;
  uint4* o; float* kv; unsigned* cnt;
  const char *k, *v;
  PfType pt[6];
  uint8_t pf[32];
  uint64_t cd[18];
};

struct Tmp { float t0, t1; };
__device__ __forceinline__ void mul2(Tmp& t, float a0, float b0, float a1, float b1) {
  asm volatile("@p_one mul.rn.f32 %0, %2, %3;\n@p_one mul.rn.f32 %1, %4, %5;" : "+f"(t.t0), "+f"(t.t1) : "f"(a0), "f"(b0), "f"(a1), "f"(b1)); }
__device__ __forceinline__ void add2(Tmp& t, float a0, float b0, float a1, float b1) {
  asm volatile("@p_one add.rn.f32 %0, %2, %3;\n@p_one add.rn.f32 %1, %4, %5;" : "+f"(t.t0), "+f"(t.t1) : "f"(a0), "f"(b0), "f"(a1), "f"(b1)); }
__device__ __forceinline__ void fma2(Tmp& t, float a0, float b0, float a1, float b1) { t.t0 = fmaf(a0, b0, t.t0); t.t1 = fmaf(a1, b1, t.t1); }
__device__ __forceinline__ uint32_t bfma2(uint32_t a, uint32_t b, uint32_t c) { uint32_t r; asm("fma.rn.bf16x2 %0, %1, %2, %3;" : "=r"(r) : "r"(a), "r"(b), "r"(c)); return r; }
struct Tw { uint32_t c[2], s[2], ns[2]; };
__device__ __forceinline__ void rot(uint32_t& u, uint32_t& v, const Tw& w, int k) {
  asm("{\n.reg .b32 a, b;\nmul.rn.bf16x2 a, %0, %2;\nmul.rn.bf16x2 b, %0, %3;\nfma.rn.bf16x2 %0, %1, %4, a;\nfma.rn.bf16x2 %1, %1, %2, b;\n}"
    : "+r"(u), "+r"(v) : "r"(w.c[k]), "r"(w.s[k]), "r"(w.ns[k]));
}
__device__ __forceinline__ void pack_fwd(uint32_t (&f)[2][2][4], const float* a) {
  #pragma unroll
  for (int j = 0; j < 16; j++) f[j >> 3][(j >> 1) & 1][2 * (j & 1) + ((j >> 2) & 1)] = fresh(pack_bf16(a[2 * j], a[2 * j + 1]));
}
__device__ __forceinline__ void rot_fwd(uint32_t (&f)[2][2][4], const Tw& w) {
  #pragma unroll
  for (int j = 0; j < 8; j++) rot(f[j >> 2][j & 1][(j >> 1) & 1], f[j >> 2][j & 1][2 + ((j >> 1) & 1)], w, j & 1);
}
__device__ __forceinline__ void add_skip(float* h, float d) {
  asm volatile("add.rn.f32 %0, %0, %4;\nadd.rn.f32 %1, %1, %4;\nadd.rn.f32 %2, %2, %4;\nadd.rn.f32 %3, %3, %4;" : "+f"(h[0]), "+f"(h[1]), "+f"(h[4]), "+f"(h[5]) : "f"(d)); }
__device__ __forceinline__ void dft16h(float* d, const uint32_t (&f)[2][4], const D2& dF) { rs32z<0>(d, f[0], dF.a); rs32a<0>(d, f[1], dF.b); }
#define SP(h, p, im, k) (((p) >> 1 ? hi : lo) + 16 * (h) + 8 * (im) + 4 * (k) + 2 * ((p) & 1))
template <int PH, int G0 = 0, int G1 = 8> __device__ __forceinline__ void prod(Tmp& t, uint32_t (&f)[2][4], const float* lo, const float* hi) {
  #pragma unroll
  for (int g = G0; g < G1; g++) {
    const int p = 2 * PH + 1 - (g >> 2), k = (g >> 1) & 1, im = g & 1;
    #pragma unroll
    for (int q = 0; q <= p; q++) {
      const float *hr = SP(1, q, 0, k), *hi_ = SP(1, q, 1, k), *xa = SP(0, p - q, im, k), *xb = SP(0, p - q, 1 - im, k);
      if (q == 0) mul2(t, hr[0], xa[0], hr[1], xa[1]); else fma2(t, hr[0], xa[0], hr[1], xa[1]);
      if (im) fma2(t, hi_[0], xb[0], hi_[1], xb[1]); else fma2(t, -hi_[0], xb[0], -hi_[1], xb[1]);
    }
    f[k][2 * (1 - im) + (p & 1)] = pack_bf16(t.t0, t.t1);
  }
}

constexpr uint64_t dA = cdesc(A_OFF, 2048, 128, 0), dAi = cdesc(A_OFF, 128, 1024, 0), dF0 = cdesc(F_OFF, 128, 512, 0),
                   dT0 = cdesc(T_OFF, 1024, 128, 0), dH0 = cdesc(H_OFF, 1024, 256, 3), dX0 = cdesc(X_OFF, 1024, 128, 0);
#define CONV_DESC dF0, dF0 + 16, dAi, dT0, dAi + 16, dT0 + 128, dAi + 32, dT0 + 256, dAi + 48, dT0 + 384, dA, dH0, dA + 256, dH0 + 32, dA, dX0, dA + 256, dX0 + 128
__device__ __forceinline__ void make_tw(Tw& tw, int ht) {
  #pragma unroll
  for (int i = 0; i < 2; i++) {
    float c0, s0, c1, s1;
    unit_root<11>((4 * (ht >> 2) + 1) * (i * 8 + 2 * (ht & 3)), c0, s0);
    unit_root<11>((4 * (ht >> 2) + 1) * (i * 8 + 2 * (ht & 3) + 1), c1, s1);
    tw.c[i] = pack_bf16(c0, c1); tw.s[i] = pack_bf16(s0, s1); tw.ns[i] = fresh(tw.s[i] ^ 0x80008000u);
  }
}
template <bool COMMIT = true> __device__ __forceinline__ void dft32_h(float* r, const D2* d) {
  ss64z<1, 1>(r, d[0].a, d[0].b); ss64a<1, 1>(r, d[1].a, d[1].b);
  if (COMMIT) wg_commit();
}
template <bool COMMIT = true> __device__ __forceinline__ void dft32_x(float* r, D2* d) {
  ss64z<1, 0>(r, d[0].a, d[0].b); ss64a<1, 0>(r, d[1].a, d[1].b);
  if (COMMIT) wg_commit();
  d[0].b = dofs(d[0].b, XS); d[1].b = dofs(d[1].b, XS);
}
__device__ __forceinline__ void pack_inv(uint32_t (&u)[2][2][4], const float* r) {
  #pragma unroll
  for (int j = 0; j < 16; j++) u[j >> 3][(j >> 2) & 1][2 * (j & 1) + ((j >> 1) & 1)] = fresh(pack_bf16(r[2 * j], r[2 * j + 1]));
}
__device__ __forceinline__ void rot_inv(uint32_t (&u)[2][2][4], const Tw& tw, uint32_t ta) {
  #pragma unroll
  for (int m = 0; m < 2; m++) {
    #pragma unroll
    for (int j = 0; j < 4; j++) rot(u[m][0][j], u[m][1][j], tw, j & 1);
    stsm4(ta + m * 512, u[m][1][0], u[m][1][1], u[m][1][2], u[m][1][3]);
    stsm4(ta + 1024 + m * 512, u[m][0][0], u[m][0][1], u[m][0][2], u[m][0][3]);
  }
}
__device__ __forceinline__ void idft32(float* r, const D2* d) {
  wg_fence();
  ss64z<0, 1>(r, d[0].a, d[0].b);
  #pragma unroll
  for (int j = 1; j < 4; j++) ss64a<0, 1>(r, d[j].a, d[j].b);
  wg_commit();
}
__device__ __forceinline__ void finish(Tmp& t, const float* r, int ch, int ht, int rank, uint32_t y0, uint32_t y1) {
  const uint32_t ya = X_OFF + ch * XS + (ch & 1) * 16, yb = BAR_OFF + (B_YR + ch) * 8;
  uint32_t y[8];
  #pragma unroll
  for (int j = 0; j < 8; j++) {
    if (j >= 2) add2(t, r[4 * j], r[4 * j - 6], r[4 * j + 1], r[4 * j - 5]);
    y[j] = j < 2 ? pack_bf16(r[4 * j], r[4 * j + 1]) : pack_bf16(t.t0, t.t1);
  }
  st_async128(y0 + ya + (ht ^ (rank * 4)) * 16 + rank * (YX - XS), y0 + yb, y[0], y[1], y[2], y[3]);
  st_async128(y1 + ya + (ht ^ (rank * 4) ^ 4) * 16 + (rank ^ 1) * (YX - XS), y1 + yb, y[4], y[5], y[6], y[7]);
}

struct Team { uint32_t bars, rel, wofs; bool lead; };
template <bool M> __device__ __forceinline__ void mid_wait() { if (M) { wg_commit(); wg_wait<0>(); wg_fence(); } }
template <int J, bool M = false> __device__ __forceinline__ void kv_issue(float* aK, float* aV, uint32_t xo, int sd) {
  constexpr uint64_t dw = cdesc(W_OFF + J * 8192, 8192, 1024, 1);
  const uint64_t dx = dofs(cdesc((J & 1) * 64, 16, 1024, 1), xo);
  wg_fence();
  ss128p<1, 0>(aV, dw + (4096 >> 4), dx, sd);
  ss128p<1, 0>(aK, dw, dx, sd);
  mid_wait<M>();
  ss128a<1, 0>(aV, dw + (6144 >> 4), dofs(dx, 32));
  ss128a<1, 0>(aK, dw + (2048 >> 4), dofs(dx, 32));
  wg_commit();
}
template <int O, int J, int H> __device__ __forceinline__ void g2_half(float* acc, const Team& c) {
  constexpr uint64_t db = cdesc(J * SLOT + 16384 + H * 4096, 8192, 1024, 1);
  const uint64_t da = dofs(O ? cdesc(J * SLOT + H * 4096, 16, 512, 2) : cdesc(J * SLOT + H * 64, 16, 1024, 1), c.wofs);
  wg_fence();
  ss128a<0, 1>(acc, da, db);
  ss128a<0, 1>(acc, dofs(da, 32), db + (2048 >> 4));
  wg_commit();
}
template <int O, int J, bool M = false, bool FIRST = false> __device__ __forceinline__ void g2_issue(float* acc, const Team& c) {
  constexpr uint64_t db = cdesc(J * SLOT + 16384, 8192, 1024, 1);
  const uint64_t da = dofs(O ? cdesc(J * SLOT, 16, 512, 2) : cdesc(J * SLOT, 16, 1024, 1), c.wofs);
  wg_fence();
  if (FIRST) ss128z<0, 1>(acc, da, db); else ss128a<0, 1>(acc, da, db);
  ss128a<0, 1>(acc, dofs(da, 32), db + (2048 >> 4));
  mid_wait<M>();
  ss128a<0, 1>(acc, dofs(da, O ? 4096 : 64), db + (4096 >> 4));
  ss128a<0, 1>(acc, dofs(da, O ? 4128 : 96), db + (6144 >> 4));
  wg_commit();
}
template <bool DEEP, bool AB = false, class F>
__device__ __forceinline__ void ring_step(const Team& c, int fb, uint32_t ph, int eb, bool rel, F issue, uint32_t ab = 0, uint32_t aph = 0) {
  uint32_t ok = mbar_try(c.bars + fb * 8, ph);
  if (AB) ok &= mbar_try(ab, aph);
  if (!ok) {
    wg_wait<0>();
    arrive_at(c.rel + eb * 8, rel);
    rel = false;
    mbar_wait(c.bars + fb * 8, ph);
    if (AB) mbar_wait(ab, aph);
  }
  if (!DEEP) { wg_wait<0>(); arrive_at(c.rel + eb * 8, rel); }
  issue();
  if (DEEP) { wg_wait<1>(); arrive_at(c.rel + eb * 8, rel); }
}
template <int N, int I = 0, class R> __device__ __forceinline__ void tail_release(R rel) {
  if constexpr (I <= N) { wg_wait<N - I>(); rel(I - 1); tail_release<N, I + 1>(rel); }
}
template <int N, class F, class R> __device__ __forceinline__ void skew_tail(const Team& c, int ph, F issue, R rel) {
  if (c.wofs) { wg_wait<0>(); rel(-1); mbar_wait(c.bars + B_SK * 8, ph); }
  issue();
  arrive_at(c.bars + B_SK * 8, fresh_tid() == 0);
  tail_release<N>([&](int i) { if (i >= 0 || !c.wofs) rel(i); });
}
__device__ __forceinline__ void phi_a(float* a, uint32_t* f) {
  #pragma unroll
  for (int i = 0; i < 8; i++) {
    asm("cvt.rn.relu.bf16x2.f32 %0, %1, %2;" : "=r"(f[i]) : "f"(a[2 * i + 1]), "f"(a[2 * i]));
    asm("ex2.approx.ftz.f32 %0, %1;" : "=f"(a[2 * i]) : "f"(a[2 * i] * 1.4426950408889634f));
    asm("ex2.approx.ftz.f32 %0, %1;" : "=f"(a[2 * i + 1]) : "f"(a[2 * i + 1] * 1.4426950408889634f));
  }
  pinv<16>(a);
}
__device__ __forceinline__ void phi_s(float* a, uint32_t* f) {
  #pragma unroll
  for (int i = 0; i < 8; i++) {
    asm("cvt.rn.relu.bf16x2.f32 %0, %1, %2;" : "=r"(f[i]) : "f"(a[2 * i + 1]), "f"(a[2 * i]));
    a[2 * i] *= 1.4426950408889634f; a[2 * i + 1] *= 1.4426950408889634f;
  }
  pinv<16>(a);
}
__device__ __forceinline__ void phi_e(float* a) {
  #pragma unroll
  for (int i = 0; i < 16; i++) asm("ex2.approx.ftz.f32 %0, %0;" : "+f"(a[i]));
  pinv<16>(a);
}
__device__ __forceinline__ void phi_b(const float* e, uint32_t* f) {
  #pragma unroll
  for (int i = 0; i < 8; i++) f[i] = badd2(f[i], pack_bf16(__saturatef(e[2 * i] + 1e-6f), __saturatef(e[2 * i + 1] + 1e-6f)));
}
__device__ __forceinline__ int g2_k(int st, int n2) {
  if (!ORD) return (st >> 1) == n2 ? st & 1 : st;
  const int j = (st >> 1) - 1;
  return 2 * (j == 0 ? n2 == 0 : (j == max(n2, 1) ? 7 : j)) + (st & 1);
}

__global__ void __cluster_dims__(2, 1, 1) __launch_bounds__(NTHREADS, 1)
fused_kernel(const __grid_constant__ Params P, const __grid_constant__ CUtensorMap mX, const __grid_constant__ CUtensorMap mW,
             const __grid_constant__ CUtensorMap mWq, const __grid_constant__ CUtensorMap mWo,
             const __grid_constant__ CUtensorMap mK, const __grid_constant__ CUtensorMap mV, const __grid_constant__ CUtensorMap mH,
             const __grid_constant__ CUtensorMap mQ, const __grid_constant__ CUtensorMap mOut, const __grid_constant__ CUtensorMap mOutA,
             const __grid_constant__ CUtensorMap mWp) {
  extern __shared__ __align__(1024) uint8_t smem[];
  asm volatile(".reg .pred p_one;");
  if (__shfl_sync(0xffffffffu, threadIdx.x >> 5, 0) == 0) {
    asm volatile(ELECT "prefetch.tensormap [%0];\n}" :: "l"(&mW) : "memory");
    asm volatile(ELECT "prefetch.tensormap [%0];\n}" :: "l"(&mX) : "memory");
  }
  {
    const uint32_t t = threadIdx.x, bb = blockIdx.x;
    asm volatile("{\n.reg .pred p, q;\nsetp.eq.u32 p, %2, 2;\nsetp.eq.u32 q, %3, 8;\n@p prefetch.global.L2 [%0];\n@q prefetch.global.L2 [%1];\n}"
      :: "l"(reinterpret_cast<const char*>(P.x) + ((bb * 16 + t - 32) * 2048)),
         "l"(reinterpret_cast<const char*>(P.w) + ((bb >> 2) * 2048 + bb * 1024 + t * 128 - 6144)), "r"(t >> 4), "r"(t >> 3));
  }
  const uint32_t sb = uni(smem_u32(smem));
  const uint32_t bars = sb + BAR_OFF;
  const int tid = threadIdx.x, lane = tid & 31;
  const int warp = __shfl_sync(0xffffffffu, tid >> 5, 0);
  const uint32_t ids = uni(cta_ids());
#define IDS(w) const int b = (w) & 127, rank = (w) & 1, g = ((w) >> 8) & 7, mb = (w) >> 12, hp = g * 2 + rank, m2 = hp, n2 = mb, \
                         cp = g * 8 + mb; (void)b; (void)hp; (void)m2; (void)n2; (void)cp
  IDS(ids);

  if (warp == 0) {
    mbar_init(bars + (B_XF + 2) * 8, 1); mbar_init(bars + B_F0 * 8, 1); mbar_init(bars + B_FULL * 8, 1);
    mbar_expect_tx(bars + B_FULL * 8, 8192);
    tma3d(sb + W_OFF, &mW, hp * 64, 0, 1, bars + B_FULL * 8);
    mbar_expect_tx(bars + (B_XF + 2) * 8, 16384);
    tma2d(sb + 2 * SLOT, &mX, 0, mb * 256, bars + (B_XF + 2) * 8);
    mbar_expect_tx(bars + B_F0 * 8, 16384);
    tma2d(sb + 2 * SLOT + 16384, &mX, 0, mb * 256 + 128, bars + B_F0 * 8);
    #pragma unroll
    for (int i = 1; i < 4; i++) mbar_init(bars + (B_FULL + i) * 8, 1);
    mbar_init(bars + B_XF * 8, 1); mbar_init(bars + (B_XF + 1) * 8, 1);
    #pragma unroll
    for (int i = 1; i < 4; i++) {
      mbar_expect_tx(bars + (B_FULL + i) * 8, 8192);
      tma3d(sb + W_OFF + i * 8192, &mW, hp * 64, i * 32, 1, bars + (B_FULL + i) * 8);
    }
  } else if (warp >= 6) {
    const uint32_t cnt = warp < 12 || warp == 15 ? 1 : 4, b0 = bars + (warp - 4) * 32;
    #pragma unroll
    for (int i = 0; i < 4; i++) mbar_init(b0 + i * 8, i == 3 && warp == 15 ? 4 : cnt);
    if (warp == 8 || warp == 9) {
      #pragma unroll
      for (int i = 0; i < 4; i++) mbar_expect_tx(b0 + i * 8, 4096);
    } else if (warp == 13) {
      mbar_expect_tx(bars + B_KVB * 8, 5120);
    }
  }
  asm volatile("fence.mbarrier_init.release.cluster;" ::: "memory");
  __syncwarp();
  asm volatile("barrier.cluster.arrive.relaxed.aligned;" ::: "memory");

  if (warp < 8) {
    asm volatile("setmaxnreg.inc.sync.aligned.u32 %0;" :: "n"(160));
    const int wg = warp >> 2;
    Team c;
    c.bars = bars; c.rel = mapa(bars, tid & 1); c.wofs = wg * 8192; c.lead = (tid & 127) < 2;
    uint32_t key = P.one;
    auto gemm2 = [&](float* a, auto O_, auto SK_, auto last) {
      constexpr int O = O_.value, SK = SK_.value;
      static_assert(SK >= 1 && SK <= 3, "tail");
      uint32_t ph = 1;
      const uint32_t ab = bars + B_FA * 8 + wg * 32;
      #pragma unroll 1
      for (int it = 1; it < 4; it++, ph ^= 1) {
        ring_step<false, O>(c, B_FULL2, ph ^ O, B_EMPTY2 + 3, c.lead, [&]() { g2_issue<O, 0, (MID >> (1 + O)) & 1>(a, c); }, ab, ph ^ 1);
        if (!O && (tid & 127) == 0) OSTAMP(55 + wg * 4 + it);
        if (O && (tid & 127) == 0) OSTAMP(40 + wg * 4 + it);
        if (SK == 3 && it == 3) break;
        ring_step<false, O>(c, B_FULL2 + 1, ph, B_EMPTY2, c.lead && (!O || it < 3), [&]() { g2_issue<O, 1, (MID >> (1 + O)) & 1>(a, c); }, ab + 8, ph);
        if (SK == 2 && it == 3) break;
        ring_step<false, O>(c, B_FULL2 + 2, ph, B_EMPTY2 + 1, c.lead && (!O || it < 3), [&]() { g2_issue<O, 2, (MID >> (1 + O)) & 1>(a, c); }, ab + 16, ph);
        if (SK == 1 && it == 3) break;
        ring_step<false, O>(c, B_FULL2 + 3, ph, B_EMPTY2 + 2, c.lead, [&]() { g2_issue<O, 3, (MID >> (1 + O)) & 1>(a, c); }, ab + 24, ph);
      }
      if (!O && HT) {
        auto rel = [&](int jj, bool on) { arrive_at(c.rel + (B_EMPTY2 + jj) * 8, c.lead && on); };
        if (wg) { wg_wait<0>(); rel(3 - SK, true); mbar_wait(bars + B_SK * 8, 1); }
        auto st = [&](auto J_) {
          constexpr int J = J_.value;
          mbar_wait(bars + (B_FULL2 + J) * 8, 1);
          g2_half<0, J, 0>(a, c);
          wg_wait<1>(); rel(J - 1, J > 4 - SK || !wg);
          g2_half<0, J, 1>(a, c);
          if (J < 3) wg_wait<1>();
        };
        if (SK >= 3) st(IC<1>());
        if (SK >= 2) st(IC<2>());
        st(IC<3>());
        arrive_at(bars + B_SK * 8, fresh_tid() == 0);
        last();
        wg_wait<0>(); rel(3, true);
      } else
      skew_tail<SK>(c, O ^ 1,
        [&]() {
          auto full = [&](int jj) { mbar_wait(bars + (B_FULL2 + jj) * 8, 1); if (O) mbar_wait(ab + jj * 8, 1); };
          if (SK >= 3) { full(1); g2_issue<O, 1>(a, c); }
          if (SK >= 2) { full(2); g2_issue<O, 2>(a, c); }
          full(3); g2_issue<O, 3>(a, c);
          last();
        },
        [&](int i) { if (!O) arrive_at(c.rel + (B_EMPTY2 + ((16 - SK + i) & 3)) * 8, c.lead); });
      pinv<64>(a);
    };
    float aq[64];
    {
      float aK[64], aV[64];
      if (wg == 0) { kv_issue<0>(aK, aV, 0, 0); wg_wait<0>(); }
      cluster_wait();
      if (wg == 1) mbar_wait(bars + B_F0 * 8, 0);
      static_assert(SK1 >= 1 && SK1 <= 3, "tail");
      uint32_t ph = 0, xs = 2, xp = 0;
      auto next_x = [&]() { if (xs == 1) xp ^= 1; xs = xs == 2 ? 0 : xs + 1; };
      #pragma unroll 1
      for (int it = 0; it < 8; it++, ph ^= 1) {
        uint32_t xo = xs * SLOT + wg * 16384;
        ring_step<false, true>(c, B_FULL, ph, B_EMPTY + 3, c.lead && it > 0, [&]() { kv_issue<0, MID & 1>(aK, aV, xo, it); if (tid == 0 && it == 0) OSTAMP(1); }, bars + (B_XF + xs) * 8, xp);
        if (SK1 == 3 && it == 7) break;
        next_x();
        ring_step<false>(c, B_FULL + 1, ph, B_EMPTY, c.lead, [&]() { kv_issue<1, MID & 1>(aK, aV, xo, 1); });
        if (SK1 == 2 && it == 7) break;
        xo = xs * SLOT + wg * 16384;
        ring_step<false, true>(c, B_FULL + 2, ph, B_EMPTY + 1, c.lead, [&]() { kv_issue<2, MID & 1>(aK, aV, xo, 1); }, bars + (B_XF + xs) * 8, xp);
        if (SK1 == 1 && it == 7) break;
        next_x();
        ring_step<false>(c, B_FULL + 3, ph, B_EMPTY + 2, c.lead, [&]() { kv_issue<3, MID & 1>(aK, aV, xo, 1); });
      }
      skew_tail<SK1>(c, 0,
        [&]() {
          auto wait = [&](uint32_t a) { mbar_wait(a, 1); };
          if (SK1 >= 3) { wait(bars + (B_FULL + 1) * 8); kv_issue<1>(aK, aV, SLOT + wg * 16384, 1); }
          if (SK1 >= 2) { wait(bars + (B_FULL + 2) * 8); wait(bars + (B_XF + 2) * 8); kv_issue<2>(aK, aV, 2 * SLOT + wg * 16384, 1); }
          wait(bars + (B_FULL + 3) * 8); kv_issue<3>(aK, aV, 2 * SLOT + wg * 16384, 1);
        },
        [&](int i) { arrive_at(c.rel + (B_EMPTY + ((32 - SK1 + i) & 3)) * 8, c.lead); });
      pinv<64>(aV); pinv<64>(aK);
      if (tid == 128) OSTAMP(3);
      const uint32_t vb = sb + M_OFF + wg * VT;
      float kv[36];
      uint32_t kf[4][8];
      const uint64_t dv = dofs(cdesc(M_OFF, 1152, 128, 0), wg * VT);
      const int t = fresh_tid();
      const uint32_t va = vb + ((t >> 4) & 1) * 1152 + ((t >> 5) & 3) * 256 + (t & 15) * 16;
      mbar_wait(bars + B_X * 8, 0);
      #pragma unroll
      for (int i = 0; i < 8; i++) {
        const float* a = aV + 8 * i;
        stsm4(va + i * 2304, pack_bf16(a[0], a[1]), pack_bf16(a[2], a[3]), pack_bf16(a[4], a[5]), pack_bf16(a[6], a[7]));
      }
      phi_a(aK + 48, kf[3]);
      mbar_wait(bars + B_FULL2 * 8, 0);
      if ((tid & 127) == 0) OSTAMP(50 + wg);
      g2_issue<0, 0, false, true>(aq, c);
      sts128(vb + ((t & 127) >> 3) * 1152 + 1024 + (t & 7) * 16, 0x3f803f80u, 0x3f803f80u, 0x3f803f80u, 0x3f803f80u);
      phi_a(aK + 32, kf[2]); phi_b(aK + 48, kf[3]);
      sched_fence(key++);
      ring_step<true>(c, B_FULL2 + 1, 0, B_EMPTY2, c.lead, [&]() { g2_issue<0, 1>(aq, c); });
      phi_a(aK + 16, kf[1]); phi_b(aK + 32, kf[2]);
      sched_fence(key++);
      ring_step<true>(c, B_FULL2 + 2, 0, B_EMPTY2 + 1, c.lead, [&]() { g2_issue<0, 2>(aq, c); });
      phi_a(aK, kf[0]); phi_b(aK + 16, kf[1]);
      sched_fence(key++);
      fence_async_smem(); bar_sync(1 + wg, 128);
      phi_b(aK, kf[0]);
      sched_fence(key++);
      wg_fence();
      #pragma unroll
      for (int ks = 0; ks < 8; ks++) {
        if (ks == 0) rs72z<0>(kv, kf[0], dv); else rs72a<0>(kv, kf[ks >> 1] + 4 * (ks & 1), dofs(dv, ks * 2304));
      }
      wg_commit();
      wg_wait<1>();
      arrive_at(c.rel + (B_EMPTY2 + 2) * 8, c.lead);
      mbar_wait(bars + (B_FULL2 + 3) * 8, 0);
      g2_issue<0, 3>(aq, c);
      wg_wait<1>();
      pinv<36>(kv);
      const int a = fresh_tid() & 127;
      const bool hi = a >= 64;
      #pragma unroll
      for (int u = 0; u < 4; u++) {
        const int o = (u & 1) * 8 + (u & 2);
        sts128(vb + (a ^ ((a >> 3) & 3)) * 16 + u * 2048, __float_as_uint(hi ? kv[16 + o] : kv[o]), __float_as_uint(hi ? kv[17 + o] : kv[o + 1]),
               __float_as_uint(hi ? kv[20 + o] : kv[o + 4]), __float_as_uint(hi ? kv[21 + o] : kv[o + 5]));
      }
      if ((a & 3) < 2) sts32(vb + 8192 + ((a >> 5) * 16 + ((a & 31) >> 2) + (a & 1) * 8) * 4, __float_as_uint((a & 1) ? kv[34] : kv[32]));
      bar_arrive(4, 352);
    }
    if (tid == 0) OSTAMP(4);
    if (tid == 128) OSTAMP(5);
    float acc[64];
    {
      uint32_t kvok, gen, far;
      gemm2(aq, IC<0>(), IC<SK2>(), [&]() {
        kvok = OS ? mbar_try(bars + B_KVB * 8, 0) : 0;
        if (kvok) fence_async_smem();
      });
      if (tid == 0) OSTAMP(6);
      if (tid == 128) OSTAMP(7);
      constexpr uint64_t dk = cdesc(KVB_OFF, 640, 128, 0);
      const uint32_t id2 = fresh(ids); IDS(id2);
      float nu[4][20];
      uint32_t pq[4][8], o[4][2][4];
      const int t2 = fresh_tid();
      const uint32_t oo = (t2 & 96) * 32 + (t2 & 28) * 16 + ((t2 ^ (t2 >> 3)) & 3) * 16;
      uint4* og = P.o + ((m2 * 8 + n2) * 4 + wg) * 512 + (oo >> 4);
      auto o_put = [&](int h, int e) {
        if (AB & 8) return;
        asm volatile("st.global.v4.b32 [%0], {%1,%2,%3,%4};" :: "l"(og + (h >> 1) * 1024 + (h & 1) * 256 + e * 32),
          "r"(o[h][e][0]), "r"(o[h][e][1]), "r"(o[h][e][2]), "r"(o[h][e][3]) : "memory");
      };
      auto o_out = [&](int h) {
        pinv<20>(nu[h]);
        #pragma unroll
        for (int e = 0; e < 2; e++) {
          const float* n = nu[h] + 2 * e;
          const float iv = rcp_fast(n[16] + 1e-6f);
          #pragma unroll
          for (int i = 0; i < 4; i++) o[h][e][i] = pack_bf16(n[4 * i] * iv, n[4 * i + 1] * iv);
          o_put(h, e);
        }
      };
      auto o_mma = [&](int h) {
        wg_fence();
        rs40z<1>(nu[h], pq[h], dk + h * (2560 >> 4));
        rs40a<1>(nu[h], pq[h] + 4, dk + h * (2560 >> 4) + (1280 >> 4));
        wg_commit();
      };
#define QSTAMP(i) do { if ((t2 & 127) == 0) TSTAMP(6, wg * 16 + (i)); } while (0)
      QSTAMP(0);
      if (PAUSE) arrive_at(bars + B_P0 * 8, t2 == (PAUSE & 16 ? 128 : 0));
      if (OS) {
        phi_s(aq, pq[0]); phi_e(aq);
        if (OS & 4) phi_s(aq + 16, pq[1]);
        if (!kvok) { mbar_wait(bars + B_KVB * 8, 0); fence_async_smem(); }
        gen = lds32(sb + D_OFF + 40); far = lds32(sb + D_OFF + 48);
        QSTAMP(1);
        #pragma unroll
        for (int u = 0; u < 4; u++) {
          if (OS & 4) {
            if (u < 3) phi_e(aq + 16 * u + 16);
            phi_b(aq + 16 * u, pq[u]);
            o_mma(u);
            if (u < 2) phi_s(aq + 16 * u + 32, pq[u + 2]);
          } else {
            if (u > 0) { phi_s(aq + 16 * u, pq[u]); phi_e(aq + 16 * u); }
            phi_b(aq + 16 * u, pq[u]);
            o_mma(u);
          }
          if (u > 0) { wg_wait<1>(); o_out(u - 1); }
          if ((OS & 2) || u == 3) sched_fence(key++);
          QSTAMP(2 + u);
        }
      } else {
      #pragma unroll
      for (int u = 0; u < 5; u++) {
        if (u >= 3) { wg_wait<1>(); QSTAMP(2 * u + 1); o_out(u - 3); }
        if (u < 4) phi_a(aq + 16 * u, pq[u]);
        if (u > 0) phi_b(aq + 16 * (u - 1), pq[u - 1]);
        if (u == 1) { QSTAMP(2); if (!(AB & 16)) mbar_wait(bars + B_KVB * 8, 0); QSTAMP(3); gen = lds32(sb + D_OFF + 40); far = lds32(sb + D_OFF + 48); fence_async_smem(); } else sched_fence(key++);
        QSTAMP(u ? 2 * u + 2 : 1);
        if (u > 0) o_mma(u - 1);
        if (u == 1) QSTAMP(5);
      }
      wg_wait<1>(); QSTAMP(11); o_out(2);
      sched_fence(key++);
      }
      wg_wait<0>(); QSTAMP(12); o_out(3);
      QSTAMP(13);
      asm volatile(ELECT "st.relaxed.gpu.global.u32 [%0], %1;\n}" :: "l"(&P.cnt[(32 + m2 * 2 + wg) * 32 + n2 * 4 + (warp & 3)]), "r"(gen) : "memory");
      bar_arrive(6, 288);
      if (OWNL) arrive_at(bars + B_OD * 8, t2 == 128);
      if ((t2 & 127) == 0) OSTAMP(8 + wg * 2);
      if (OCP) {
        sched_fence(key++);
        #pragma unroll
        for (int i = 0; i < 32; i++) asm volatile("lop3.b32 %0, %1, %2, 0, 0xf0 | 0xcc;" : "=r"(o[i >> 3][(i >> 2) & 1][i & 3]) : "r"(o[i >> 3][(i >> 2) & 1][i & 3]), "r"(P.one - 1));
      }
      if (OWNL && wg == 0) mbar_wait(bars + B_OD * 8, 0);
      mbar_wait(bars + (B_FULL2 + 1) * 8, 0);
      QSTAMP(14);
      wg_fence();
      #pragma unroll
      for (int i = 0; i < 8; i++) {
        const uint32_t f[4] = {o[i >> 1][0][i & 1], o[i >> 1][1][i & 1], o[i >> 1][0][2 + (i & 1)], o[i >> 1][1][2 + (i & 1)]};
        constexpr uint64_t dw = cdesc(SLOT, 16384, 2048, 1);
        if (i == 0) rs128z<1>(acc, f, dw); else rs128a<1>(acc, f, dw + (((i >> 1) * 4096 + (i & 1) * 1024) >> 4));
      }
      wg_commit();
      if ((t2 & 127) == 0) OSTAMP(37 + wg);
      const uint32_t ab = bars + B_FA * 8 + wg * 32;
      const int k2 = g2_k(2, n2);
      const bool doubt = NEAR == 2 || (uni(far) >> (k2 >> 1)) & 1;
      auto look = [&](int j) {
        if (doubt) {
          const uint32_t a = sb + (2 + j) * SLOT + wg * 8192 + (t2 & 96) * 32;
          if (__any_sync(0xffffffffu, lds32(a + (t2 & 16) * 256 + (t2 & 15) * 64 + (t2 & 30) * 2) == ~0u)) {
            const uint4* src = P.o + (m2 * 16 + k2 + j) * 1024 + wg * 512 + (t2 & 96) * 2 + (t2 & 31);
            if ((t2 & 31) == 0) OSTAMP(34);
            #pragma unroll 1
            for (int i = 0; i < 4; i++) {
              uint32_t v[4];
              int n = 0;
              do asm volatile("ld.relaxed.gpu.global.v4.u32 {%0,%1,%2,%3}, [%4];" : "=r"(v[0]), "=r"(v[1]), "=r"(v[2]), "=r"(v[3]) : "l"(src + (i & 1) * 32 + (i >> 1) * 256) : "memory");
              while (__any_sync(0xffffffffu, v[0] == ~0u) && ++n < 64);
              sts128(a + (t2 & 31) * 16 + (i & 1) * 512 + (i >> 1) * 4096, v[0], v[1], v[2], v[3]);
            }
            fence_async_smem();
            __syncwarp();
          }
        }
      };
      ring_step<true, true>(c, B_FULL2 + 2, 0, B_EMPTY2 + 1, c.lead, [&]() { look(0); if ((t2 & 127) == 0) OSTAMP(11 + wg * 24); g2_issue<1, 2>(acc, c); }, ab + 16, 0);
      ring_step<true, true>(c, B_FULL2 + 3, 0, B_EMPTY2 + 2, c.lead, [&]() { look(1); g2_issue<1, 3>(acc, c); }, ab + 24, 0);
    }
    gemm2(acc, IC<1>(), IC<SK3>(), []() {});
    if (tid == 0) OSTAMP(13);
    if (tid == 128) OSTAMP(14);
    {
      const uint32_t id2 = fresh(ids); IDS(id2);
      const int t2 = fresh_tid();
      const int row = ((t2 >> 5) & 3) * 16 + (t2 & 15);
      const int cq = (t2 >> 4) & 1, sw = t2 & 7;
      const uint32_t stg = sb + (EHI ? T_OFF : 0) + wg * 8192;
      constexpr uint32_t HS = EHI ? 16384 : SLOT;
      if (EHI) mbar_wait(bars + B_CD * 8, 0);
      #pragma unroll 1
      for (int pass = 0;; pass++) {
      const bool bad = acc[0] != acc[0] || acc[2] != acc[2];
      #pragma unroll
      for (int hf = 0; hf < 2; hf++) {
        #pragma unroll
        for (int jj = 0; jj < 4; jj++) {
          const int o = hf * 32 + jj * 8;
          stsm4(stg + hf * HS + row * 128 + (((2 * jj + cq) ^ sw) << 4),
                pack_bf16(acc[o], acc[o + 1]), pack_bf16(acc[o + 2], acc[o + 3]),
                pack_bf16(acc[o + 4], acc[o + 5]), pack_bf16(acc[o + 6], acc[o + 7]));
        }
        fence_async_smem();
        __syncwarp();
        if (!(AB & 1) && !((AB & 32) && wg == 0)) tma2d_store(&mOut, 1024 + n2 * 128 + hf * 64, m2 * 128 + warp * 16, sb + (EHI ? T_OFF : 0) + hf * HS + warp * 2048);
      }
      bulk_commit();
      uint32_t redo;
      asm volatile("{\n.reg .pred p, q;\nsetp.ne.b32 p, %1, 0;\nbar.red.or.pred q, %2, 128, p;\nselp.u32 %0, 1, 0, q;\n}" : "=r"(redo) : "r"((uint32_t)bad), "r"(1 + wg) : "memory");
      if (!uni(redo) || pass) break;
      if ((t2 & 127) == 0) OSTAMP(48 + wg);
      asm volatile("cp.async.bulk.wait_group 0;" ::: "memory");
      spin_until(&P.cnt[(16 + m2) * 32 + (t2 & 7)], lds32(sb + D_OFF + 40));
      fence_async_global();
      const uint32_t ab = bars + B_FA * 8 + wg * 32;
      #pragma unroll 1
      for (int k = 0; k < 16; k++) {
        bar_sync(1 + wg, 128);
        if ((warp & 3) == 0) {
          mbar_expect_tx(ab, 24576);
          bulk_load(sb + c.wofs, P.o + (m2 * 16 + k) * 1024 + wg * 512, 8192, ab);
          tma2d(sb + SLOT + c.wofs, &mWo, n2 * 128, k * 64, ab);
          tma2d(sb + 2 * SLOT + c.wofs, &mWo, n2 * 128 + 64, k * 64, ab);
        }
        mbar_wait(ab, ~k & 1);
        const uint64_t da = dofs(cdesc(0, 16, 512, 2), c.wofs), db = dofs(cdesc(SLOT, SLOT, 1024, 1), c.wofs);
        wg_fence();
        ss128p<0, 1>(acc, da, db, k);
        ss128a<0, 1>(acc, dofs(da, 32), dofs(db, 2048));
        ss128a<0, 1>(acc, dofs(da, 4096), dofs(db, 4096));
        ss128a<0, 1>(acc, dofs(da, 4128), dofs(db, 6144));
        wg_commit();
        wg_wait<0>(); pinv<64>(acc);
      }
      }
      bulk_wait_read();
    }
  } else if (warp < 12) {
    asm volatile("setmaxnreg.inc.sync.aligned.u32 %0;" :: "n"(160));
    const uint32_t id2 = fresh(ids); IDS(id2);
    const int ht = tid - 256, w = warp - 8;
    const int kap = w & 1;
    uint32_t w0, w1, w2, w3;
    {
      const uint4 s = *reinterpret_cast<const uint4*>(P.shift + (cp * 16 + kap * 8 + 2 * (lane & 3)) * 4);
      w0 = __byte_perm(s.x, s.z, 0x5410); w1 = __byte_perm(s.x, s.z, 0x7632);
      w2 = __byte_perm(s.y, s.w, 0x5410); w3 = __byte_perm(s.y, s.w, 0x7632);
      float dv = 0.f;
      if (ht < 8) dv = __bfloat162float(P.ssmD[cp * 16 + rank * 8 + ht]) * 0.125f;
      uint32_t c4[4], s4[4];
      #pragma unroll
      for (int i = 0; i < 4; i++) {
        float c0, s0, c1, s1;
        unit_root<7>((32 * (ht & 3) + 8 * i + 1) * (ht >> 2), c0, s0);
        unit_root<7>((32 * (ht & 3) + 8 * i + 5) * (ht >> 2), c1, s1);
        c4[i] = pack_bf16(c0 * 0.125f, c1 * 0.125f); s4[i] = pack_bf16(s0 * 0.125f, s1 * 0.125f);
      }
      const uint32_t aa = sb + A_OFF + w * 2048 + (ht & 3) * 256 + ((ht >> 2) & 7) * 16;
      sts128(aa, c4[0], c4[1], c4[2], c4[3]);
      sts128(aa + 128, s4[0], s4[1], s4[2], s4[3]);
      sts128(aa + 1024, s4[0] ^ 0x80008000u, s4[1] ^ 0x80008000u, s4[2] ^ 0x80008000u, s4[3] ^ 0x80008000u);
      sts128(aa + 1024 + 128, c4[0], c4[1], c4[2], c4[3]);
      float c0, s0, c1, s1;
      unit_root<4>((ht >> 3) * (2 * (ht & 7)), c0, s0);
      unit_root<4>((ht >> 3) * (2 * (ht & 7) + 1), c1, s1);
      const uint32_t fa = sb + F_OFF + (ht >> 6) * 512 + ((ht >> 2) & 1) * 256 + ((ht >> 3) & 7) * 16 + (ht & 3) * 4;
      const uint32_t cc = pack_bf16(c0, c1), ss = pack_bf16(s0, s1);
      sts32(fa, cc); sts32(fa + 128, ss ^ 0x80008000u); sts32(fa + 1024, ss); sts32(fa + 1024 + 128, cc);
      if (ht < 8) sts32(sb + D_OFF + ht * 4, __float_as_uint(dv));
    }
    Tw tw;
    make_tw(tw, ht);
    D2 cd[9];
    {
      const uint64_t v = P.cd[min(lane, 17)];
      #pragma unroll
      for (int i = 0; i < 9; i++) { cd[i].a = __shfl_sync(0xffffffffu, v, 2 * i); cd[i].b = __shfl_sync(0xffffffffu, v, 2 * i + 1); }
    }
    const D2 &dF = cd[0], *dT = cd + 1, *dH = cd + 5;
    D2* dX = cd + 7;
#define CFENCE(n) sched_fence<n>((uint32_t)dF.a)
    cluster_wait();
    const uint32_t psb = uni(mapa(sb, rank ^ 1));
    if (ht == 0) OSTAMP(20);
    {
      const int m = lane >> 3, n1 = (w >> 1) * 8 + (lane & 7);
      const int rk = 17 * m + n1 + 1, rh = 17 * (12 + m) + n1, rv = 16 * m + n1;
      const uint32_t ka = rk * 32 + ((kap ^ (rk >> 2)) & 1) * 16, ha = rh * 32 + ((kap ^ (rh >> 2)) & 1) * 16;
      const uint32_t va = rv * 32 + ((kap ^ (rv >> 2)) & 1) * 16;
      const uint32_t po = sb + T_OFF + (w >> 1) * 2176;
      #pragma unroll 1
      for (int rd = 0; rd < 4; rd++) {
        const uint32_t kb = sb + M_OFF + (rd & 1) * KB, vb = sb + M_OFF + 2 * KB + (rd & 1) * 8192;
        const uint32_t xo = X_OFF + ((rd & 1) * 2 + (w >> 1)) * 1024 + (2 * rank + (rd >> 1)) * 256;
        const uint32_t xa = (kap == rank ? sb + xo + (lane & 7) * XS : po + (lane & 7) * 272) + m * 16;
        mbar_wait(bars + (B_STG + (rd & 1) * 2) * 8, rd >> 1);
        uint32_t kk[20], vv[16];
        const uint32_t zero = P.one - 1;
        ldsm4(kk, kb + ha);
        ldsm4(kk + 4, kb + ka);
        #pragma unroll
        for (int i = 0; i < 16; i++) {
          if ((i & 3) == 0 && i < 12) ldsm4(kk + 8 + i, kb + (ka ^ ((~i & 4) * 4)) + (i + 4) * 544 + (kk[i + 4] & zero));
          uint32_t t = bmul2(kk[i + 1], w3);
          t = badd2(t, bmul2(kk[i + 2], w2));
          t = badd2(t, bmul2(kk[i + 3], w1));
          kk[i] = badd2(t, bmul2(kk[i + 4], w0));
          asm volatile("" : "+r"(kk[i]));
        }
        mbar_wait(bars + (B_STG + (rd & 1) * 2 + 1) * 8, rd >> 1);
        ldsm4(vv, vb + va);
        #pragma unroll
        for (int i = 0; i < 16; i += 4) {
          if (i < 12) ldsm4(vv + 4 + i, vb + va + (i + 4) * 512 + (i == 4 ? vv[0] & zero : 0));
          stsm4t(xa + (i >> 2) * 64, bmul2(kk[i], vv[i]), bmul2(kk[i + 1], vv[i + 1]), bmul2(kk[i + 2], vv[i + 2]), bmul2(kk[i + 3], vv[i + 3]));
        }
        if (rd < 2) {
          fence_async_smem();
          __syncwarp();
          mbar_arrive(bars + (B_SFREE + (rd & 1)) * 8);
        }
        __syncwarp();
        if (kap != rank) {
          #pragma unroll
          for (int i = 0; i < 4; i++) lds128(vv + 4 * i, po + (2 * i + (lane >> 4)) * 272 + (lane & 15) * 16);
          #pragma unroll
          for (int i = 0; i < 4; i++)
            st_async128(psb + xo + (2 * i + (lane >> 4)) * XS + (lane & 15) * 16, psb + BAR_OFF + B_X * 8, vv[4 * i], vv[4 * i + 1], vv[4 * i + 2], vv[4 * i + 3]);
          __syncwarp();
        }
      }
    }
    bar_sync(3, 128);
    if (w == 0) mbar_expect_tx(bars + B_X * 8, 16384);
    {
      constexpr int NC = 8;
      Tmp t; t.t0 = 0.f; t.t1 = 0.f;
      asm volatile("setp.ne.b32 p_one, %0, 0;" :: "r"(lds32(sb + F_OFF)));
      float ra[32], lo[32], hi[32];
      uint32_t fa[2][2][4], fb[2][2][4];
      const uint32_t ta = sb + T_OFF + w * 2048 + lane * 16;
      const uint32_t y0 = rank ? psb : sb, y1 = rank ? sb : psb;
      auto fin = [&](int ch) {
        if (ch > 0) mbar_wait(bars + (B_YR + ch - 1) * 8, 0);
        finish(t, ra, ch, ht, rank, y0, y1);
      };
      auto load_h = [&](int i) {
        mbar_expect_tx(bars + B_H * 8, 4096);
        tma2d(sb + H_OFF, &mH, 0, (cp * 16 + rank * 8 + i) * 128, bars + B_H * 8);
      };
      auto skip = [&](int i) {
        const float dn = __uint_as_float(lds32(sb + D_OFF + i * 4));
        return dn;
      };
      mbar_wait(bars + B_H * 8, 0);
      wg_fence();
      dft32_h(lo, dH);
      mbar_wait(bars + B_X * 8, 0);
      fence_async_smem();
      if (ht == 0) OSTAMP(21);
      wg_fence();
      dft32_x(hi, dX);
      float dn = skip(0);
      wg_wait<1>(); pinv<32>(lo);
      if (w == 0) load_h(1);
      pack_fwd(fa, lo); CFENCE(0); rot_fwd(fa, tw); CFENCE(1);
      wg_wait<0>(); pinv<32>(hi);
      pack_fwd(fb, hi); CFENCE(2); rot_fwd(fb, tw); CFENCE(3);
      wg_fence();
      dft16h(hi, fb[1], dF); dft16h(hi + 16, fa[1], dF); dft16h(lo, fb[0], dF); dft16h(lo + 16, fa[0], dF);
      wg_commit();
      wg_wait<0>(); pinv<32>(lo); pinv<32>(hi);
#define CSTAMP(n) do {} while (0)
      #pragma unroll 1
      for (int i = 0;; i++) {
        CSTAMP(0);
        auto pause = [&](uint32_t on) { if (on) mbar_wait(bars + B_OD * 8, 0); };
        if (PAUSE & 1) pause(mbar_try(bars + B_P0 * 8, 0));
        add_skip(lo + 16, dn);
        prod<1, 0, FG>(t, fa[1], lo, hi);
        CFENCE(4);
        CSTAMP(1);
        fence_async_smem();
        bar_sync(3, 128);
        CSTAMP(2);
        float rg[32];
        if (DRY) idft32(rg, dT); else { wg_fence(); ss64x4(rg, dT, i); }
        CFENCE(5);
        CSTAMP(3);
        const uint32_t yr = bars + (i < 2 ? B_X : B_YR + i - 2) * 8;
        const uint32_t oky = mbar_try(yr, 0);
        dn = skip(i + 1);
        prod<1, FG, 8>(t, fa[1], lo, hi);
        pinv<32>(lo);
        if (!oky) mbar_wait(yr, 0);
        if (PAUSE & 2) pause(mbar_try(bars + B_P0 * 8, 0));
        CSTAMP(4);
        wg_wait<0>(); pinv<32>(rg);
        if (i > 0) finish(t, rg, i - 1, ht, rank, y0, y1);
        if (i == NC - 1) break;
        CSTAMP(5);
        wg_fence();
        dft32_x<false>(hi, dX);
        if (HINT & 1) { asm volatile("@!p_one mov.b32 %0, %1;" : "+f"(t.t1) : "f"(rg[0])); if (SF & 16) CFENCE(6); wg_fence(); }
        dft16h(ra + 16, fa[1], dF);
        wg_commit();
        CFENCE(7);
        CSTAMP(6);
        const uint32_t okh = mbar_try(bars + B_H * 8, (i + 1) & 1);
        prod<0>(t, fa[0], lo, lo);
        if ((AB & 128) && i == 4) mbar_wait(bars + B_GO * 8, 0);
        if (!okh) mbar_wait(bars + B_H * 8, (i + 1) & 1);
        if (PAUSE & 4) pause(mbar_try(bars + B_P0 * 8, 0));
        CSTAMP(7);
        wg_fence();
        dft32_h<false>(lo, dH);
        if (HINT & 2) { asm volatile("@!p_one mov.b32 %0, %1;" : "+f"(t.t0) : "f"(rg[31])); if (SF & 8) CFENCE(8); wg_fence(); }
        dft16h(ra, fa[0], dF);
        wg_commit();
        wg_wait<1>(); pinv<32>(hi);
        if (ht == 64) OSTAMP(22 + i);
        CSTAMP(8);
        pack_fwd(fb, hi); CFENCE(9); rot_fwd(fb, tw); CFENCE(10);
        CSTAMP(9);
        wg_wait<0>(); pinv<32>(lo); pinv<32>(ra);
        CSTAMP(10);
        if (w == HW && i < NC - 2) load_h(i + 2);
        if (PAUSE & 8) pause(mbar_try(bars + B_P0 * 8, 0));
        pack_fwd(fa, lo);
        if (SF & 32) CFENCE(11);
        wg_fence();
        dft16h(hi, fb[1], dF); dft16h(lo, fb[0], dF);
        wg_commit();
        CFENCE(12);
        rot_fwd(fa, tw);
        uint32_t u[2][2][4];
        if (CX) { CFENCE(13); pack_inv(u, ra); }
        if (SF & 64) CFENCE(14);
        CSTAMP(11);
        wg_fence();
        dft16h(hi + 16, fa[1], dF); dft16h(lo + 16, fa[0], dF);
        wg_commit();
        CFENCE(15);
        CSTAMP(12);
        if (!CX) { pack_inv(u, ra); CFENCE(13); }
        rot_inv(u, tw, ta);
        CSTAMP(13);
        if (SF & 1) CFENCE(16);
        wg_wait<0>(); pinv<32>(lo); pinv<32>(hi);
        CSTAMP(14);
      }
      wg_fence();
      dft16h(hi + 16, fa[1], dF);
      wg_commit();
      CFENCE(17);
      prod<0>(t, fa[0], lo, lo);
      CFENCE(18);
      wg_fence();
      dft16h(hi, fa[0], dF);
      wg_commit();
      if (ht == 64) OSTAMP(29);
      wg_wait<0>(); pinv<32>(hi);
      pack_inv(fb, hi); CFENCE(19); rot_inv(fb, tw, ta);
      fence_async_smem();
      bar_sync(3, 128);
      idft32(ra, dT);
      const int l3 = fresh_tid() & 31;
      uint32_t qa = sb + M_OFF + ((l3 >> 4) * 512 + w * 128 + (l3 & 8) + ((l3 >> 2) & 1) + (l3 & 2)) * 32 + (l3 & 1) * 16;
      uint32_t yb = sb + X_OFF + (l3 & 1) * (XS + 16) + w * 512
                    + (((l3 >> 1) & 1) == rank ? (l3 >> 2) * 16 : YX - XS + ((l3 >> 2) ^ 4) * 16);
      mbar_wait(bars + B_Q * 8, 0);
      wg_wait<0>(); pinv<32>(ra);
      fin(NC - 1);
      if (ht == 64) OSTAMP(30);
      uint32_t t0 = 0, dt = 0;
      #pragma unroll 1
      for (int sg = 0; sg < 4; sg++, qa += 1024, yb += 128) {
        uint32_t qv[4][4], yv[4][4];
        #pragma unroll
        for (int i = 0; i < 4; i++) lds128(qv[i], qa + (i >> 1) * 512 + (i & 1) * 128);
        #pragma unroll
        for (int m = 0; m < 4; m++) {
          if (m == 3 && sg == 0) mbar_wait(bars + (B_YR + NC - 1) * 8, 0);
          ldsm4t(yv[m], yb + 2 * m * XS);
        }
        #pragma unroll
        for (int i = 0; i < 4; i++)
          sts128(qa + (i >> 1) * 512 + (i & 1) * 128, bmul2(qv[i][0], yv[0][i]), bmul2(qv[i][1], yv[1][i]), bmul2(qv[i][2], yv[2][i]), bmul2(qv[i][3], yv[3][i]));
        if (sg == 3) mbar_arrive(bars + B_CD * 8);
        fence_async_smem();
        __syncwarp();
        if (sg == 0) {
          mbar_wait(bars + B_GO * 8, 0);
          t0 = uni((uint32_t)clock());
          dt = uni(min(max((int)(lds32(sb + D_OFF + 44) + OA_END - t0) >> 2, 4 * OA_MIN), 4 * OA_MAX));
          t0 += w * (dt >> 2);
        }
        pace(t0, dt);
        #pragma unroll
        for (int hf = 0; hf < 2; hf++) {
          const int r = w * 128 + sg * 32 + hf * 512;
          if (!(AB & 2)) tma2d_store(&mOutA, cp * 16, rank * 1024 + r, sb + M_OFF + r * 32);
        }
      }
      bulk_commit(); bulk_wait_read();
      if (ht == 0) OSTAMP(31);
    }
  } else {
    asm volatile("setmaxnreg.dec.sync.aligned.u32 %0;" :: "n"(32));
    const uint32_t id2 = fresh(ids); IDS(id2);
    const uint32_t t_pf = (uint32_t)clock();
    if (warp == 14)
      asm volatile("prefetch.global.L2 [%0];" :: "l"(((lane & 1) ? P.v : P.k) + (rank * 2097152 + cp * 32 + (lane >> 1) * 131072)));
    if (warp != 15) cluster_wait();
    auto reduce_kv = [&](int i0, int i1) {
      float* kr = P.kv + hp * KV_PER_HP;
      mbar_wait(bars + B_Z * 8, 0);
      bar_sync(4, 352);
      #pragma unroll 1
      for (; i0 < i1; i0 += 2) {
        uint32_t p[2][4], q[2][4];
        const int i = (i0 + 2 * mb) & 15;
        const uint32_t pa = sb + M_OFF + (i & 3) * 2048 + (i >> 2) * 512 + (lane & 7) * 64 + (((lane >> 3) ^ (lane >> 1)) & 3) * 16;
        lds128(p[0], pa); lds128(q[0], pa + VT); lds128(p[1], pa + 2048); lds128(q[1], pa + VT + 2048);
        #pragma unroll
        for (int j = 0; j < 2; j++)
          asm volatile("red.relaxed.gpu.global.add.v4.f32 [%0], {%1,%2,%3,%4};" :: "l"(kr + (i >> 3) * 32 + (i + j) * 128 + lane * 4),
            "f"(__uint_as_float(p[j][0]) + __uint_as_float(q[j][0])), "f"(__uint_as_float(p[j][1]) + __uint_as_float(q[j][1])),
            "f"(__uint_as_float(p[j][2]) + __uint_as_float(q[j][2])), "f"(__uint_as_float(p[j][3]) + __uint_as_float(q[j][3])) : "memory");
      }
      if (i1 == 4) {
        const uint32_t za = sb + M_OFF + 8192 + lane * 4;
        #pragma unroll
        for (int h = 0; h < 2; h++)
          asm volatile("red.relaxed.gpu.global.add.f32 [%0], %1;" :: "l"(kr + h * 1056 + 1024 + lane),
            "f"(__uint_as_float(lds32(za + h * 128)) + __uint_as_float(lds32(za + h * 128 + VT))) : "memory");
      }
      bar_sync(5, 96);
    };
    auto convert_kv = [&](int u0, auto N_) {
      constexpr int N = N_.value;
      const float* kg = P.kv + (2 * n2 + rank) * KV_PER_HP;
      const uint32_t psb = uni(mapa(sb, rank ^ 1));
      auto put = [&](uint32_t o, uint32_t v0, uint32_t v1, uint32_t v2, uint32_t v3) {
        st_async128(psb + o, psb + BAR_OFF + B_KVB * 8, v0, v1, v2, v3);
        sts128(sb + o, v0, v1, v2, v3);
      };
      mbar_wait(bars + B_KVL * 8, 0);
      spin_until(&P.cnt[(2 * n2 + rank) * 32 + 1], uni(lds32(sb + D_OFF + 40)) * 8);
      float4 v[N][2];
      float z[2];
      #pragma unroll
      for (int j = 0; j < N; j++) {
        const float4* kr = reinterpret_cast<const float4*>(kg + ((u0 + j) >> 2) * 32 + (u0 + j) * 256) + lane;
        v[j][0] = __ldcg(kr); v[j][1] = __ldcg(kr + 32);
      }
      if (N == 2) { z[0] = __ldcg(kg + 1024 + lane); z[1] = __ldcg(kg + 2080 + lane); }
      #pragma unroll
      for (int j = 0; j < N; j++)
        put(KVB_OFF + (rank * 8 + u0 + j) * 640 + lane * 16,
            pack_bf16(v[j][0].x, v[j][0].y), pack_bf16(v[j][0].z, v[j][0].w), pack_bf16(v[j][1].x, v[j][1].y), pack_bf16(v[j][1].z, v[j][1].w));
      if (N == 2) {
        #pragma unroll
        for (int h = 0; h < 2; h++) {
          const uint32_t zz = pack_bf16(z[h], z[h]);
          put(KVB_OFF + (rank * 8 + h * 4 + (lane >> 3)) * 640 + 512 + (lane & 7) * 16, zz, zz, zz, zz);
        }
      }
      fence_async_smem();
      __syncwarp();
      mbar_arrive(bars + B_KVB * 8);
    };
    if (warp == 12) {
      uint32_t xs = 0;
      auto load_x = [&](int k) {
        tma2d_mc(sb + xs * SLOT + rank * 16384, &mX, k, mb * 256 + rank * 128, bars + (B_XF + xs) * 8);
        mbar_expect_tx(bars + (B_XF + xs) * 8, SLOT);
        xs = xs == 2 ? 0 : xs + 1;
      };
      load_x(64); load_x(128);
      mbar_expect_tx(bars + B_Q * 8, 32768);
      #pragma unroll 1
      for (int it = 1; it < 8; it++) {
        #pragma unroll
        for (int j = 0; j < 4; j++) {
          mbar_wait(bars + (B_EMPTY + j) * 8, (it - 1) & 1);
          TSTAMP(1, 4 * it + j);
          tma3d(sb + W_OFF + j * 8192, &mW, hp * 64, it * 128 + j * 32, 1, bars + (B_FULL + j) * 8);
          if (j == 1 || (j == 3 && it < 7)) load_x(it * 128 + j * 32 + 32);
          mbar_expect_tx(bars + (B_FULL + j) * 8, 8192);
        }
      }
      #pragma unroll 1
      for (int it = 0; it < 4; it++) {
        #pragma unroll
        for (int j = 0; j < 4; j++) {
          const uint32_t fb = bars + (B_FULL2 + j) * 8;
          if (j || it) mbar_wait(bars + (it ? B_EMPTY2 + j : B_EMPTY + (j | 1)) * 8, (it - 1) & 1);
          TSTAMP(5, 4 * it + j);
          tma2d_mc(sb + j * SLOT + 16384 + rank * 8192, &mWq, n2 * 128 + rank * 64, it * 256 + j * 64, fb);
          tma2d(sb + j * SLOT, &mX, it * 256 + j * 64, m2 * 128, fb);
          mbar_expect_tx(fb, SLOT);
          const int pc = 4 * it + j - Q_ST;
          if (pc >= 0) {
            mbar_wait(bars + B_MF * 8, 0);
            tma2d(sb + M_OFF + pc * 4096, &mQ, cp * 16, rank * 1024 + pc * 128, bars + B_Q * 8);
          }
        }
      }
      #pragma unroll 1
      for (int pc = 16 - Q_ST; pc < 8; pc++) tma2d(sb + M_OFF + pc * 4096, &mQ, cp * 16, rank * 1024 + pc * 128, bars + B_Q * 8);
      auto load_wo = [&](int st, uint32_t ph) {
        const uint32_t j = st & 3, fb = bars + (B_FULL2 + j) * 8, k = fresh(g2_k(st, n2) * 64);
        mbar_wait(bars + (B_EMPTY2 + j) * 8, ph);
        TSTAMP(5, 16 + st);
        tma2d_mc(sb + j * SLOT + 16384 + rank * 8192, &mWo, n2 * 128 + rank * 64, k, fb);
        mbar_expect_tx(fb, 16384);
      };
      load_wo(4, 1);
      mbar_wait(bars + (B_EMPTY2 + 1) * 8, 1);
      asm volatile(ELECT "cp.async.bulk.tensor.5d.shared::cluster.global.mbarrier::complete_tx::bytes.multicast::cluster [%0], [%1, {%3, %4, %4, %4, %5}], [%2], %6;\n}"
        :: "r"(sb + SLOT + rank * 16384), "l"(&mWp), "r"(bars + (B_FULL2 + 1) * 8), "r"(n2 * 128 + rank * 64), "r"(0), "r"(n2 * 4), "h"((uint16_t)3) : "memory");
      mbar_expect_tx(bars + (B_FULL2 + 1) * 8, SLOT);
      load_wo(2, 1); load_wo(3, 1);
      mbar_arrive(bars + B_QE * 8);
      #pragma unroll 1
      for (int it = 1; it < 4; it++) {
        load_wo(4 * it + 1, (it - 1) & 1); load_wo(4 * it + 2, (it - 1) & 1); load_wo(4 * it + 3, (it - 1) & 1);
        if (it < 3) load_wo(4 * it + 4, (it - 1) & 1);
      }
    } else if (warp == 13) {
      if ((sb & 0xffffff) != SB0) __trap();
      float4* zp = reinterpret_cast<float4*>(P.kv + hp * KV_PER_HP + mb * 264);
      const float4 z4 = make_float4(0.f, 0.f, 0.f, 0.f);
      zp[lane] = z4; zp[lane + 32] = z4;
      if (lane < 2) zp[lane + 64] = z4;
      if (lane == 0) P.cnt[hp * 32 + 8 + mb] = t_pf;
      if (SPEC) {
        uint4* op = P.o + m2 * 16384 + mb * (SPEC * 256) + lane;
        uint32_t t0 = t_pf + RS_T0 + mb * (RS_DT / 8);
        #pragma unroll 1
        for (int i = 0; i < 8; i++) {
          while ((int)((uint32_t)clock() - t0) < 0) __nanosleep(100);
          t0 += RS_DT;
          #pragma unroll
          for (int j = 0; j < SPEC; j++) op[(i * SPEC + j) * 32] = make_uint4(~0u, ~0u, ~0u, ~0u);
        }
      }
      fence_gpu();
      __syncwarp();
      unsigned gen = 0;
      if (lane == 0) gen = (atomicAdd(&P.cnt[hp * 32], 1u) >> 3) + 1;
      gen = uni(gen);
      sts32(sb + D_OFF + 40, gen);
      spin_until(&P.cnt[hp * 32], gen * 8);
      sts32(sb + D_OFF + 48, __ballot_sync(0xffffffffu, NEAR && __ldcg(&P.cnt[hp * 32 + 8 + (lane & 7)]) - t_pf + 4096 >= 8192));
      mbar_arrive(bars + B_Z * 8);
      reduce_kv(0, 4);
      mbar_arrive(mapa(bars, rank ^ 1) + B_KVL * 8);
      mbar_arrive(bars + B_MF * 8);
      OSTAMP(17);
      fence_gpu();
      red_add(&P.cnt[hp * 32 + 1]);
      OSTAMP(15);
      convert_kv(0, IC<2>());
      bar_sync(6, 288);
      fence_gpu();
      asm volatile(ELECT "st.relaxed.gpu.global.u32 [%0], %1;\n}" :: "l"(&P.cnt[(16 + m2) * 32 + n2]), "r"(gen) : "memory");
      OSTAMP(32);
    } else {
      if (warp == 14) {
        uint32_t t0 = t_pf + STG_T0;
        #pragma unroll 1
        for (int pc = 0; pc < 16; pc++) {
          const int rd = pc >> 2, u = pc & 3;
          const uint32_t gb = bars + (B_STG + (rd & 1) * 2 + (u >> 1)) * 8;
          if (pc == 8 || pc == 12) mbar_wait(bars + (B_SFREE + (rd & 1)) * 8, 0);
          if (!(u & 1)) mbar_expect_tx(gb, u ? 8192 : KB);
          pace(t0, STG_DT);
          TSTAMP(3, 16 + pc);
          tma3d(sb + M_OFF + (u < 2 ? (rd & 1) * KB + u * (KB / 2) : 2 * KB + (rd & 1) * 8192 + (u & 1) * 4096), u < 2 ? &mK : &mV,
                cp * 16, rank * 64 + rd * 16 - (u < 2), (u & 1) * 8, gb);
        }
        mbar_expect_tx(bars + B_H * 8, 4096);
        tma2d(sb + H_OFF, &mH, 0, (cp * 16 + rank * 8) * 128, bars + B_H * 8);
      }
      if (warp == 15) {
        uint32_t t0 = t_pf + b * 2;
        #pragma unroll 1
        for (int i = 0; i < PF_N; i++) {
          const int u = P.pf[i];
          const PfType& f = P.pt[u >> 4];
          pace(t0, i == 0 ? PF_DT0 : (i < PF_N1 ? PF_DT1 : PF_DT2));
          asm volatile("prefetch.global.L2 [%0];" :: "l"(f.base + ((g & 3) * f.gl + (g >> 2) * f.gh + mb * f.sp + rank * f.sr + (u & 15) * f.su
                                                                   + (lane >> 2) * f.l4 + ((lane >> 1) & 1) * f.l2 + (lane & 1) * 128)));
        }
        cluster_wait();
      }
      reduce_kv(warp * 6 - 80, warp * 6 - 74);
      convert_kv(warp * 3 - 40, IC<3>());
      {
        const int wg = 15 - warp;
        const unsigned gen = uni(lds32(sb + D_OFF + 40));
        const uint32_t ab = bars + B_FA * 8 + wg * 32, far = uni(lds32(sb + D_OFF + 48));
        const unsigned* fp = &P.cnt[SPEC ? (32 + m2 * 2 + wg) * 32 + lane : (16 + m2) * 32 + (lane >> 2)];
        uint32_t miss = ~0u, safe = t_pf;
        auto poll = [&]() {
          unsigned v;
          asm volatile("ld.relaxed.gpu.global.u32 %0, [%1];" : "=r"(v) : "l"(fp) : "memory");
          miss = __ballot_sync(0xffffffffu, v != gen);
        };
        mbar_arrive(ab + 8);
        mbar_wait(bars + B_QE * 8, 0);
        #pragma unroll 1
        for (int st = 2; st < 16; st += 2) {
          const int k = g2_k(st, n2), j = st & 3;
          const uint4* src = P.o + (m2 * 16 + k) * 1024 + wg * 512;
          const uint32_t eb = bars + (B_EMPTY2 + j) * 8, ph = ((st >> 2) - 1) & 1, dst = sb + j * SLOT + wg * 8192;
          if (!(AB & 4) && ((miss >> (2 * k)) & 15)) {
            #pragma unroll 1
            for (int n = 0; n < WAIT_BOUND && ((miss >> (2 * k)) & 15); n++) poll();
            if (!SPEC) asm volatile("fence.acquire.gpu;" ::: "memory");
            fence_async_global();
            safe = (uint32_t)clock() + FAR_DT;
          }
          if (st >= 4) {
            if ((far >> (k >> 1)) & 1) while ((int)(uni((uint32_t)clock()) - safe) < 0) {}
            mbar_wait(eb, j ? ph : ph ^ 1);
          }
          bulk_load(dst, src, 8192, ab + j * 8);
          mbar_expect_tx(ab + j * 8, 8192);
          if (st >= 4) mbar_wait(eb + 8, ph);
          bulk_load(dst + SLOT, src + 1024, 8192, ab + j * 8 + 8);
          mbar_expect_tx(ab + j * 8 + 8, 8192);
          if (st == 2) { OSTAMP(18 + wg * 15); if (wg) { sts32(sb + D_OFF + 44, (uint32_t)clock()); mbar_arrive(bars + B_GO * 8); } }
        }
      }
    }
  }
}

typedef CUresult (*EncodeFn)(CUtensorMap*, CUtensorMapDataType, cuuint32_t, void*, const cuuint64_t*, const cuuint64_t*,
                             const cuuint32_t*, const cuuint32_t*, CUtensorMapInterleave, CUtensorMapSwizzle,
                             CUtensorMapL2promotion, CUtensorMapFloatOOBfill);

void encode(EncodeFn fn, CUtensorMap* m, const void* ptr, int rank, const cuuint64_t* dims, const cuuint64_t* strides,
            const cuuint32_t* box, CUtensorMapSwizzle sw, CUtensorMapL2promotion pr) {
  const cuuint32_t es[5] = {1, 1, 1, 1, 1};
  fn(m, CU_TENSOR_MAP_DATA_TYPE_BFLOAT16, rank, const_cast<void*>(ptr), dims, strides, box, es,
     CU_TENSOR_MAP_INTERLEAVE_NONE, sw, pr, CU_TENSOR_MAP_FLOAT_OOB_FILL_NONE);
}

}

extern "C" void kernel_launch(void* const* d_in, const int* in_sizes, int n_in, void* d_out, int out_size) {
  (void)in_sizes; (void)n_in; (void)out_size;
  static EncodeFn fn = nullptr;
  static void *po, *pkv, *pcnt;
  if (!fn) {
    void* p = nullptr; cudaDriverEntryPointQueryResult qr;
    cudaGetDriverEntryPoint("cuTensorMapEncodeTiled", &p, cudaEnableDefault, &qr);
    fn = (EncodeFn)p;
    cudaGetSymbolAddress(&po, g_O); cudaGetSymbolAddress(&pkv, g_kv); cudaGetSymbolAddress(&pcnt, g_cnt);
    cudaFuncSetAttribute(fused_kernel, cudaFuncAttributeMaxDynamicSharedMemorySize, SMEM_BYTES);
  }
  const CUtensorMapL2promotion P128 = CU_TENSOR_MAP_L2_PROMOTION_L2_128B, P0 = CU_TENSOR_MAP_L2_PROMOTION_NONE;
  CUtensorMap mX, mW, mWq, mWo, mK, mV, mH, mQ, mOut, mOutA, mWp;
  { cuuint64_t d[2] = {1024, 2048}, s[1] = {2048}; cuuint32_t bx[2] = {64, 128}, bq[2] = {16, 128};
    encode(fn, &mX, d_in[6], 2, d, s, bx, CU_TENSOR_MAP_SWIZZLE_128B, P128);
    encode(fn, &mQ, d_in[0], 2, d, s, bq, CU_TENSOR_MAP_SWIZZLE_NONE, P128); }
  { cuuint64_t d[3] = {1024, 1024, 3}, s[2] = {6144, 2048}; cuuint32_t bx[3] = {64, 32, 2};
    encode(fn, &mW, d_in[7], 3, d, s, bx, CU_TENSOR_MAP_SWIZZLE_128B, P128); }
  { cuuint64_t d[2] = {1024, 1024}, s[1] = {6144}, so[1] = {2048}; cuuint32_t bx[2] = {64, 64};
    encode(fn, &mWq, d_in[7], 2, d, s, bx, CU_TENSOR_MAP_SWIZZLE_128B, P128);
    encode(fn, &mWo, d_in[8], 2, d, so, bx, CU_TENSOR_MAP_SWIZZLE_128B, P128); }
  { cuuint64_t d[5] = {1024, 2, 4, 4, 32}, s[4] = {2048, 16384, 4096, 65536}; cuuint32_t bx[5] = {64, 2, 4, 4, 4};
    encode(fn, &mWp, d_in[8], 5, d, s, bx, CU_TENSOR_MAP_SWIZZLE_128B, P128); }
  { cuuint64_t d[3] = {1024, 128, 16}, s[2] = {32768, 2048}; cuuint32_t bk[3] = {16, 17, 8}, bv[3] = {16, 16, 8};
    encode(fn, &mK, d_in[1], 3, d, s, bk, CU_TENSOR_MAP_SWIZZLE_32B, P128);
    encode(fn, &mV, d_in[2], 3, d, s, bv, CU_TENSOR_MAP_SWIZZLE_32B, P128); }
  { cuuint64_t d[2] = {16, 131072}, s[1] = {32}; cuuint32_t bx[2] = {16, 128};
    encode(fn, &mH, d_in[4], 2, d, s, bx, CU_TENSOR_MAP_SWIZZLE_32B, CU_TENSOR_MAP_L2_PROMOTION_L2_256B); }
  { cuuint64_t d[2] = {2048, 2048}, s[1] = {4096}; cuuint32_t bx[2] = {64, 16}, ba[2] = {16, 32};
    encode(fn, &mOut, d_out, 2, d, s, bx, CU_TENSOR_MAP_SWIZZLE_128B, P0);
    encode(fn, &mOutA, d_out, 2, d, s, ba, CU_TENSOR_MAP_SWIZZLE_NONE, P0); }
  Params P;
  P.shift = (const __nv_bfloat16*)d_in[3]; P.ssmD = (const __nv_bfloat16*)d_in[5];
  P.x = (const __nv_bfloat16*)d_in[6]; P.w = (const __nv_bfloat16*)d_in[7]; P.out = (__nv_bfloat16*)d_out; P.one = 1;
  P.o = (uint4*)po; P.kv = (float*)pkv; P.cnt = (unsigned*)pcnt;
  P.k = (const char*)d_in[1]; P.v = (const char*)d_in[2];
  P.pt[0] = {(const char*)d_in[6], 16 * 32768, 64 * 32768, 65536, 32768, 256, 4096, 2048};
  P.pt[1] = {(const char*)d_in[7] + 2048, 256, 1024, 16 * 6144, 8 * 6144, 128 * 6144, 6144, 2048};
  P.pt[2] = {(const char*)d_in[7], 512, 128 * 6144, 16 * 6144, 8 * 6144, 256 * 6144, 6144, 256};
  P.pt[3] = {(const char*)d_in[8], 512, 128 * 2048, 16 * 2048, 8 * 2048, 256 * 2048, 2048, 256};
  P.pt[4] = {(const char*)d_in[0], 256, 1024, 32768, 2097152, 262144, 4096, 2048};
  P.pt[5] = {(const char*)d_in[4], 16 * 32768, 64 * 32768, 65536, 32768, 4096, 512, 256};
  const uint8_t pf[32] = {PF_LIST};
  for (int i = 0; i < 32; i++) P.pf[i] = pf[i];
  const uint64_t cd[18] = {CONV_DESC};
  for (int i = 0; i < 18; i++) P.cd[i] = cd[i];
  fused_kernel<<<NCTA, NTHREADS, SMEM_BYTES, cudaStreamPerThread>>>(P, mX, mW, mWq, mWo, mK, mV, mH, mQ, mOut, mOutA, mWp);
}
```

```cpp
#include <cuda_runtime.h>
#include <cuda_bf16.h>
#include <cuda.h>
#include <stdint.h>

#define PARAM(name, value) constexpr int name = value
#define TUNE
namespace dflt {
PARAM(SK1, 2); PARAM(SK2, 3); PARAM(SK3, 2);
PARAM(ATW, 1); PARAM(OS, 7); PARAM(HT, 1); PARAM(PERM, 0x76154032); PARAM(ORD, 1); PARAM(OWNL, 1); PARAM(OCP, 1); PARAM(SMAP, 1); PARAM(NEAR, 1); PARAM(FAR_DT, 500); PARAM(SPEC, 8); PARAM(RS_T0, 12000); PARAM(RS_DT, 1000); PARAM(CI, 1); PARAM(CW, 2); PARAM(SF, 97); PARAM(CX, 1); PARAM(DRY, 0); PARAM(FG, 2); PARAM(HINT, 0); PARAM(HW, 0); PARAM(AB, 0); PARAM(EHI, 0); PARAM(MID, 3);
PARAM(STG_T0, 1300); PARAM(STG_DT, 540);
PARAM(QD, 0x80000); PARAM(QW, 0);
PARAM(OA_END, 7400); PARAM(OA_MIN, 200); PARAM(OA_MAX, 450);
PARAM(PF_DT0, 200); PARAM(PF_DT1, 1060); PARAM(PF_DT2, 512); PARAM(PF_N1, 9);
}
#define PF_LIST 0x01, 0x11, 0x02, 0x12, 0x03, 0x13, 0x04, 0x14, 0x05, 0x15, 0x51, 0x06, 0x16, 0x20, 0x07, 0x17, 0x21, 0x22, 0x23, \
                0x40, 0x41, 0x42, 0x43, 0x44, 0x45, 0x46, 0x47, 0x30, 0x31, 0x32, 0x33
#define PF_N 31
#define WAIT_BOUND 262144

namespace {
using namespace dflt;
TUNE

constexpr int S_LEN = 2048;
constexpr int DM    = 1024;
constexpr int NCTA  = 128;
constexpr int NTHREADS = 512;
constexpr int SLOT  = 32768;
constexpr int W_OFF = 3 * SLOT;
constexpr int M_OFF = 4 * SLOT;
constexpr int VT    = 16 * 1152;
constexpr int T_OFF = M_OFF + 43008;
constexpr int XS    = 4096 + 16;
constexpr int YX    = 2048 + 16;
constexpr int X_OFF = T_OFF + 8192 + 2176;
constexpr int H_OFF = X_OFF + 8 * XS;
constexpr int A_OFF = H_OFF + 4096;
constexpr int F_OFF = A_OFF + 8192;
constexpr int BAR_OFF = F_OFF + 2048;
constexpr int D_OFF = BAR_OFF + 384;
constexpr int SMEM_BYTES = D_OFF + 64 + 256;
constexpr int KB = 8704;
constexpr int KVB_OFF = M_OFF + 32768;
static_assert(H_OFF % 256 == 0 && X_OFF % 128 == 0 && SMEM_BYTES <= 232448, "layout");
constexpr int B_XF = 0, B_F0 = 3, B_FULL = 4, B_FA = 4, B_FULL2 = 25, B_KVL = 24, B_STG = 8, B_X = 12, B_Z = 13, B_H = 14, B_Q = 15, B_YR = 16,
              B_SK = 29, B_GO = 30, B_QE = 31,
              B_EMPTY = 32, B_KVB = 36, B_EMPTY2 = 37, B_SFREE = 41, B_CD = 43, B_MF = 44, B_OD = 45, B_EX = 46;
constexpr int KV_PER_HP = 2 * 1056;

__device__ __align__(1024) uint4 g_O[S_LEN * DM / 8];
__device__ __align__(128) float g_kv[16 * KV_PER_HP];
__device__ __align__(128) unsigned g_cnt[81 * 32];

#define OSTAMP(i) do {} while (0)
#define TSTAMP(k, i) do {} while (0)

__device__ __forceinline__ uint32_t wanted_job() {
  uint32_t t;
  asm("mov.u32 %0, %%smid;" : "=r"(t));
  if (SMAP == 0) t = blockIdx.x < 8 ? blockIdx.x + 124 : blockIdx.x - 8;
  if (SMAP == 2) t = t * 3 % 100;
  t >>= 1;
  const uint32_t q = ((t - 32) * 37) >> 8;
  uint32_t r;
  asm("{\n.reg .pred p, q;\nsetp.lt.u32 p, %3, 32;\nsetp.lt.u32 q, %3, 62;\nselp.u32 %0, %1, %2, q;\nselp.u32 %0, %3, %0, p;\n}" : "=&r"(r) : "r"(t + 1 + q), "r"((t - 58) * 8), "r"(t));
  return (r & 7) | ((((r & 7 ? PERM : 0x76543012) >> ((r >> 1) & 28)) & 7) << 3);
}

#define ELECT "{\n.reg .pred e;\nelect.sync _|e, 0xffffffff;\n@e "
__device__ __forceinline__ uint32_t uni(uint32_t v) { return __shfl_sync(0xffffffffu, v, 0); }
__device__ __forceinline__ uint32_t fresh(uint32_t v) { asm volatile("" : "+r"(v)); return v; }
__device__ __forceinline__ uint32_t smem_u32(const void* p) { return (uint32_t)__cvta_generic_to_shared(p); }
__device__ __forceinline__ void mbar_init(uint32_t b, uint32_t c) { asm volatile(ELECT "mbarrier.init.shared::cta.b64 [%0], %1;\n}" :: "r"(b), "r"(c) : "memory"); }
__device__ __forceinline__ void mbar_expect_tx(uint32_t b, uint32_t bytes) { asm volatile(ELECT "mbarrier.arrive.expect_tx.shared::cta.b64 _, [%0], %1;\n}" :: "r"(b), "r"(bytes) : "memory"); }
__device__ __forceinline__ void mbar_arrive(uint32_t b) { asm volatile(ELECT "mbarrier.arrive.shared::cluster.b64 _, [%0];\n}" :: "r"(b) : "memory"); }
__device__ __forceinline__ void mbar_wait(uint32_t b, uint32_t ph) {
  asm volatile("{\n.reg .pred p;\nWAIT_LOOP:\nmbarrier.try_wait.parity.shared::cta.b64 p, [%0], %1;\n@!p bra.uni WAIT_LOOP;\n}" :: "r"(b), "r"(ph) : "memory");
}
__device__ __forceinline__ void tma2d(uint32_t dst, const CUtensorMap* m, int c0, int c1, uint32_t bar) {
  asm volatile(ELECT "cp.async.bulk.tensor.2d.shared::cluster.global.mbarrier::complete_tx::bytes [%0], [%1, {%3, %4}], [%2];\n}"
    :: "r"(dst), "l"(m), "r"(bar), "r"(c0), "r"(c1) : "memory"); }
__device__ __forceinline__ void tma2d_mc(uint32_t dst, const CUtensorMap* m, int c0, int c1, uint32_t bar) {
  asm volatile(ELECT "cp.async.bulk.tensor.2d.shared::cluster.global.mbarrier::complete_tx::bytes.multicast::cluster [%0], [%1, {%3, %4}], [%2], %5;\n}"
    :: "r"(dst), "l"(m), "r"(bar), "r"(c0), "r"(c1), "h"((uint16_t)3) : "memory"); }
__device__ __forceinline__ void tma3d(uint32_t dst, const CUtensorMap* m, int c0, int c1, int c2, uint32_t bar) {
  asm volatile(ELECT "cp.async.bulk.tensor.3d.shared::cluster.global.mbarrier::complete_tx::bytes [%0], [%1, {%3, %4, %5}], [%2];\n}"
    :: "r"(dst), "l"(m), "r"(bar), "r"(c0), "r"(c1), "r"(c2) : "memory"); }
__device__ __forceinline__ void tma2d_store(const CUtensorMap* m, int c0, int c1, uint32_t src) {
  asm volatile(ELECT "cp.async.bulk.tensor.2d.global.shared::cta.bulk_group [%0, {%2, %3}], [%1];\n}"
    :: "l"(m), "r"(src), "r"(c0), "r"(c1) : "memory"); }
__device__ __forceinline__ void bulk_load(uint32_t dst, const void* src, uint32_t bytes, uint32_t bar) {
  asm volatile(ELECT "cp.async.bulk.shared::cluster.global.mbarrier::complete_tx::bytes [%0], [%1], %2, [%3];\n}"
    :: "r"(dst), "l"(src), "r"(bytes), "r"(bar) : "memory"); }
__device__ __forceinline__ void bulk_commit() { asm volatile("cp.async.bulk.commit_group;" ::: "memory"); }
__device__ __forceinline__ void bulk_wait_read() { asm volatile("cp.async.bulk.wait_group.read 0;" ::: "memory"); }
__device__ __forceinline__ void fence_async_smem() { asm volatile("fence.proxy.async.shared::cta;" ::: "memory"); }
__device__ __forceinline__ void bar_sync(int id, int n) { asm volatile("bar.sync %0, %1;" :: "r"(id), "r"(n) : "memory"); }
__device__ __forceinline__ void bar_arrive(int id, int n) { asm volatile("bar.arrive %0, %1;" :: "r"(id), "r"(n) : "memory"); }
__device__ __forceinline__ void wg_fence() { asm volatile("wgmma.fence.sync.aligned;" ::: "memory"); }
__device__ __forceinline__ void wg_commit() { asm volatile("wgmma.commit_group.sync.aligned;" ::: "memory"); }
template <int N> __device__ __forceinline__ void wg_wait() { asm volatile("wgmma.wait_group.sync.aligned %0;" :: "n"(N) : "memory"); }
constexpr uint32_t SB0 = 1024;
__host__ __device__ constexpr uint64_t cdesc(uint32_t off, uint32_t lbo, uint32_t sbo, uint32_t swz) {
  return (uint64_t)((SB0 + off) >> 4) | ((uint64_t)(lbo >> 4) << 16) | ((uint64_t)(sbo >> 4) << 32) | ((uint64_t)swz << 62); }
__device__ __forceinline__ uint64_t dofs(uint64_t d, uint32_t bytes) { return (d & 0xffffffff00000000ull) | (uint32_t)((uint32_t)d + (bytes >> 4)); }
__device__ __forceinline__ uint32_t mbar_try(uint32_t b, uint32_t ph) {
  uint32_t ok;
  asm volatile("{\n.reg .pred p;\nmbarrier.test_wait.parity.shared::cta.b64 p, [%1], %2;\nselp.u32 %0, 1, 0, p;\n}" : "=r"(ok) : "r"(b), "r"(ph) : "memory");
  return ok; }
__device__ __forceinline__ void arrive_at(uint32_t a, bool on) {
  asm volatile("{\n.reg .pred p;\nsetp.ne.b32 p, %1, 0;\n@p mbarrier.arrive.shared::cluster.b64 _, [%0];\n}" :: "r"(a), "r"((uint32_t)on) : "memory"); }
__device__ __forceinline__ void ldsm4(uint32_t* r, uint32_t a) {
  asm volatile("ldmatrix.sync.aligned.m8n8.x4.shared.b16 {%0,%1,%2,%3}, [%4];" : "=r"(r[0]), "=r"(r[1]), "=r"(r[2]), "=r"(r[3]) : "r"(a) : "memory"); }
__device__ __forceinline__ void ldsm4t(uint32_t* r, uint32_t a) {
  asm volatile("ldmatrix.sync.aligned.m8n8.x4.trans.shared.b16 {%0,%1,%2,%3}, [%4];" : "=r"(r[0]), "=r"(r[1]), "=r"(r[2]), "=r"(r[3]) : "r"(a) : "memory"); }
__device__ __forceinline__ void stsm4(uint32_t a, uint32_t r0, uint32_t r1, uint32_t r2, uint32_t r3) {
  asm volatile("stmatrix.sync.aligned.m8n8.x4.shared.b16 [%0], {%1,%2,%3,%4};" :: "r"(a), "r"(r0), "r"(r1), "r"(r2), "r"(r3) : "memory"); }
__device__ __forceinline__ void stsm4t(uint32_t a, uint32_t r0, uint32_t r1, uint32_t r2, uint32_t r3) {
  asm volatile("stmatrix.sync.aligned.m8n8.x4.trans.shared.b16 [%0], {%1,%2,%3,%4};" :: "r"(a), "r"(r0), "r"(r1), "r"(r2), "r"(r3) : "memory"); }
__device__ __forceinline__ uint32_t lds32(uint32_t a) { uint32_t v; asm volatile("ld.shared.b32 %0, [%1];" : "=r"(v) : "r"(a) : "memory"); return v; }
__device__ __forceinline__ void lds128(uint32_t* v, uint32_t a) { asm volatile("ld.shared.v4.b32 {%0,%1,%2,%3}, [%4];" : "=r"(v[0]), "=r"(v[1]), "=r"(v[2]), "=r"(v[3]) : "r"(a) : "memory"); }
__device__ __forceinline__ void sts32(uint32_t a, uint32_t v) { asm volatile("st.shared.b32 [%0], %1;" :: "r"(a), "r"(v) : "memory"); }
__device__ __forceinline__ void sts128(uint32_t a, uint32_t v0, uint32_t v1, uint32_t v2, uint32_t v3) {
  asm volatile("st.shared.v4.b32 [%0], {%1,%2,%3,%4};" :: "r"(a), "r"(v0), "r"(v1), "r"(v2), "r"(v3) : "memory"); }
__device__ __forceinline__ uint32_t pack_bf16(float lo, float hi) { uint32_t r; asm("cvt.rn.bf16x2.f32 %0, %1, %2;" : "=r"(r) : "f"(hi), "f"(lo)); return r; }
template <int ID = 0> __device__ __forceinline__ void sched_fence(uint32_t key) {
  asm volatile("{\n.reg .pred p;\nsetp.eq.u32 p, %0, %1;\nSF_LOOP:\n@p pmevent 1;\n@p bra.uni SF_LOOP;\n}" :: "r"(key), "n"(ID) : "memory");
}
template <int N> __device__ __forceinline__ void pinv(float* v) {
  #pragma unroll
  for (int i = 0; i < N; i++) asm volatile("" : "+f"(v[i]) :: "memory"); }
__device__ __forceinline__ uint32_t bmul2(uint32_t a, uint32_t b) { uint32_t r; asm("mul.rn.bf16x2 %0, %1, %2;" : "=r"(r) : "r"(a), "r"(b)); return r; }
__device__ __forceinline__ uint32_t badd2(uint32_t a, uint32_t b) { uint32_t r; asm("add.rn.bf16x2 %0, %1, %2;" : "=r"(r) : "r"(a), "r"(b)); return r; }
__device__ __forceinline__ void spin_until(const unsigned* p, unsigned target) {
  int n = 0;
  unsigned v;
  do { asm volatile("ld.relaxed.gpu.global.u32 %0, [%1];" : "=r"(v) : "l"(p) : "memory"); } while ((int)(v - target) < 0 && ++n < WAIT_BOUND);
  asm volatile("fence.acquire.gpu;" ::: "memory");
}
__device__ __forceinline__ void cluster_wait() { asm volatile("barrier.cluster.wait.aligned;" ::: "memory"); }
__device__ __forceinline__ void fence_gpu() { asm volatile("fence.release.gpu;" ::: "memory"); }
__device__ __forceinline__ void fence_async_global() { asm volatile("fence.proxy.async.global;" ::: "memory"); }
__device__ __forceinline__ void red_add(unsigned* p) { asm volatile(ELECT "red.relaxed.gpu.global.add.u32 [%0], 1;\n}" :: "l"(p) : "memory"); }
__device__ __forceinline__ float rcp_fast(float x) { float r; asm("rcp.approx.ftz.f32 %0, %1;" : "=f"(r) : "f"(x)); return r; }
__device__ __forceinline__ uint32_t mapa(uint32_t a, uint32_t rank) { uint32_t r; asm("mapa.shared::cluster.u32 %0, %1, %2;" : "=r"(r) : "r"(a), "r"(rank)); return r; }
__device__ __forceinline__ void st_async128(uint32_t a, uint32_t bar, uint32_t v0, uint32_t v1, uint32_t v2, uint32_t v3) {
  asm volatile("st.async.weak.shared::cluster.mbarrier::complete_tx::bytes.v4.b32 [%0], {%2,%3,%4,%5}, [%1];"
    :: "r"(a), "r"(bar), "r"(v0), "r"(v1), "r"(v2), "r"(v3) : "memory"); }
__device__ __forceinline__ int fresh_tid() { int t; asm volatile("mov.u32 %0, %%tid.x;" : "=r"(t)); return t; }
__device__ __forceinline__ void pace(uint32_t& t, uint32_t dt) {
  uint32_t c;
  while ((int)((c = uni((uint32_t)clock())) - t) < 0) __nanosleep(20);
  t = ((int)(c - t) > (int)dt ? c : t) + dt;
}
template <int LOG> __device__ __forceinline__ void unit_root(int a, float& c, float& s) {
  const float x = (float)((a << (32 - LOG)) >> (32 - LOG)) * (6.283185307179586f / (1 << LOG));
  c = __cosf(x); s = __sinf(x); }

struct D2 { uint64_t a, b; };
template <int TA, int TB> __device__ __forceinline__ void ss128p(float* d, uint64_t da, uint64_t db, int sd) {
  asm volatile("{\n.reg .pred p;\nsetp.ne.b32 p, %68, 0;\n"
    "wgmma.mma_async.sync.aligned.m64n128k16.f32.bf16.bf16 "
    "{%0, %1, %2, %3, %4, %5, %6, %7, %8, %9, %10, %11, %12, %13, %14, %15, "
    "%16, %17, %18, %19, %20, %21, %22, %23, %24, %25, %26, %27, %28, %29, %30, %31, "
    "%32, %33, %34, %35, %36, %37, %38, %39, %40, %41, %42, %43, %44, %45, %46, %47, "
    "%48, %49, %50, %51, %52, %53, %54, %55, %56, %57, %58, %59, %60, %61, %62, %63}, %64, %65, p, 1, 1, %66, %67;\n}\n"
    : "+f"(d[0]), "+f"(d[1]), "+f"(d[2]), "+f"(d[3]), "+f"(d[4]), "+f"(d[5]), "+f"(d[6]), "+f"(d[7]),
      "+f"(d[8]), "+f"(d[9]), "+f"(d[10]), "+f"(d[11]), "+f"(d[12]), "+f"(d[13]), "+f"(d[14]), "+f"(d[15]),
      "+f"(d[16]), "+f"(d[17]), "+f"(d[18]), "+f"(d[19]), "+f"(d[20]), "+f"(d[21]), "+f"(d[22]), "+f"(d[23]),
      "+f"(d[24]), "+f"(d[25]), "+f"(d[26]), "+f"(d[27]), "+f"(d[28]), "+f"(d[29]), "+f"(d[30]), "+f"(d[31]),
      "+f"(d[32]), "+f"(d[33]), "+f"(d[34]), "+f"(d[35]), "+f"(d[36]), "+f"(d[37]), "+f"(d[38]), "+f"(d[39]),
      "+f"(d[40]), "+f"(d[41]), "+f"(d[42]), "+f"(d[43]), "+f"(d[44]), "+f"(d[45]), "+f"(d[46]), "+f"(d[47]),
      "+f"(d[48]), "+f"(d[49]), "+f"(d[50]), "+f"(d[51]), "+f"(d[52]), "+f"(d[53]), "+f"(d[54]), "+f"(d[55]),
      "+f"(d[56]), "+f"(d[57]), "+f"(d[58]), "+f"(d[59]), "+f"(d[60]), "+f"(d[61]), "+f"(d[62]), "+f"(d[63])
    : "l"(da), "l"(db), "n"(TA), "n"(TB), "r"(sd));
}
template <int TA, int TB> __device__ __forceinline__ void ss128a(float* d, uint64_t da, uint64_t db) {
  asm volatile("{\n.reg .pred p;\nsetp.eq.b32 p, 0, 0;\n"
    "wgmma.mma_async.sync.aligned.m64n128k16.f32.bf16.bf16 "
    "{%0, %1, %2, %3, %4, %5, %6, %7, %8, %9, %10, %11, %12, %13, %14, %15, "
    "%16, %17, %18, %19, %20, %21, %22, %23, %24, %25, %26, %27, %28, %29, %30, %31, "
    "%32, %33, %34, %35, %36, %37, %38, %39, %40, %41, %42, %43, %44, %45, %46, %47, "
    "%48, %49, %50, %51, %52, %53, %54, %55, %56, %57, %58, %59, %60, %61, %62, %63}, %64, %65, p, 1, 1, %66, %67;\n}\n"
    : "+f"(d[0]), "+f"(d[1]), "+f"(d[2]), "+f"(d[3]), "+f"(d[4]), "+f"(d[5]), "+f"(d[6]), "+f"(d[7]),
      "+f"(d[8]), "+f"(d[9]), "+f"(d[10]), "+f"(d[11]), "+f"(d[12]), "+f"(d[13]), "+f"(d[14]), "+f"(d[15]),
      "+f"(d[16]), "+f"(d[17]), "+f"(d[18]), "+f"(d[19]), "+f"(d[20]), "+f"(d[21]), "+f"(d[22]), "+f"(d[23]),
      "+f"(d[24]), "+f"(d[25]), "+f"(d[26]), "+f"(d[27]), "+f"(d[28]), "+f"(d[29]), "+f"(d[30]), "+f"(d[31]),
      "+f"(d[32]), "+f"(d[33]), "+f"(d[34]), "+f"(d[35]), "+f"(d[36]), "+f"(d[37]), "+f"(d[38]), "+f"(d[39]),
      "+f"(d[40]), "+f"(d[41]), "+f"(d[42]), "+f"(d[43]), "+f"(d[44]), "+f"(d[45]), "+f"(d[46]), "+f"(d[47]),
      "+f"(d[48]), "+f"(d[49]), "+f"(d[50]), "+f"(d[51]), "+f"(d[52]), "+f"(d[53]), "+f"(d[54]), "+f"(d[55]),
      "+f"(d[56]), "+f"(d[57]), "+f"(d[58]), "+f"(d[59]), "+f"(d[60]), "+f"(d[61]), "+f"(d[62]), "+f"(d[63])
    : "l"(da), "l"(db), "n"(TA), "n"(TB));
}
template <int TA, int TB> __device__ __forceinline__ void ss128z(float* d, uint64_t da, uint64_t db) {
  asm volatile("{\n.reg .pred p;\nsetp.ne.b32 p, 0, 0;\n"
    "wgmma.mma_async.sync.aligned.m64n128k16.f32.bf16.bf16 "
    "{%0, %1, %2, %3, %4, %5, %6, %7, %8, %9, %10, %11, %12, %13, %14, %15, "
    "%16, %17, %18, %19, %20, %21, %22, %23, %24, %25, %26, %27, %28, %29, %30, %31, "
    "%32, %33, %34, %35, %36, %37, %38, %39, %40, %41, %42, %43, %44, %45, %46, %47, "
    "%48, %49, %50, %51, %52, %53, %54, %55, %56, %57, %58, %59, %60, %61, %62, %63}, %64, %65, p, 1, 1, %66, %67;\n}\n"
    : "=f"(d[0]), "=f"(d[1]), "=f"(d[2]), "=f"(d[3]), "=f"(d[4]), "=f"(d[5]), "=f"(d[6]), "=f"(d[7]),
      "=f"(d[8]), "=f"(d[9]), "=f"(d[10]), "=f"(d[11]), "=f"(d[12]), "=f"(d[13]), "=f"(d[14]), "=f"(d[15]),
      "=f"(d[16]), "=f"(d[17]), "=f"(d[18]), "=f"(d[19]), "=f"(d[20]), "=f"(d[21]), "=f"(d[22]), "=f"(d[23]),
      "=f"(d[24]), "=f"(d[25]), "=f"(d[26]), "=f"(d[27]), "=f"(d[28]), "=f"(d[29]), "=f"(d[30]), "=f"(d[31]),
      "=f"(d[32]), "=f"(d[33]), "=f"(d[34]), "=f"(d[35]), "=f"(d[36]), "=f"(d[37]), "=f"(d[38]), "=f"(d[39]),
      "=f"(d[40]), "=f"(d[41]), "=f"(d[42]), "=f"(d[43]), "=f"(d[44]), "=f"(d[45]), "=f"(d[46]), "=f"(d[47]),
      "=f"(d[48]), "=f"(d[49]), "=f"(d[50]), "=f"(d[51]), "=f"(d[52]), "=f"(d[53]), "=f"(d[54]), "=f"(d[55]),
      "=f"(d[56]), "=f"(d[57]), "=f"(d[58]), "=f"(d[59]), "=f"(d[60]), "=f"(d[61]), "=f"(d[62]), "=f"(d[63])
    : "l"(da), "l"(db), "n"(TA), "n"(TB));
}
template <int TA, int TB> __device__ __forceinline__ void ss64a(float* d, uint64_t da, uint64_t db) {
  asm volatile("{\n.reg .pred p;\nsetp.eq.b32 p, 0, 0;\n"
    "wgmma.mma_async.sync.aligned.m64n64k16.f32.bf16.bf16 "
    "{%0, %1, %2, %3, %4, %5, %6, %7, %8, %9, %10, %11, %12, %13, %14, %15, "
    "%16, %17, %18, %19, %20, %21, %22, %23, %24, %25, %26, %27, %28, %29, %30, %31}, %32, %33, p, 1, 1, %34, %35;\n}\n"
    : "+f"(d[0]), "+f"(d[1]), "+f"(d[2]), "+f"(d[3]), "+f"(d[4]), "+f"(d[5]), "+f"(d[6]), "+f"(d[7]),
      "+f"(d[8]), "+f"(d[9]), "+f"(d[10]), "+f"(d[11]), "+f"(d[12]), "+f"(d[13]), "+f"(d[14]), "+f"(d[15]),
      "+f"(d[16]), "+f"(d[17]), "+f"(d[18]), "+f"(d[19]), "+f"(d[20]), "+f"(d[21]), "+f"(d[22]), "+f"(d[23]),
      "+f"(d[24]), "+f"(d[25]), "+f"(d[26]), "+f"(d[27]), "+f"(d[28]), "+f"(d[29]), "+f"(d[30]), "+f"(d[31])
    : "l"(da), "l"(db), "n"(TA), "n"(TB));
}
template <int TA, int TB> __device__ __forceinline__ void ss64z(float* d, uint64_t da, uint64_t db) {
  asm volatile("{\n.reg .pred p;\nsetp.ne.b32 p, 0, 0;\n"
    "wgmma.mma_async.sync.aligned.m64n64k16.f32.bf16.bf16 "
    "{%0, %1, %2, %3, %4, %5, %6, %7, %8, %9, %10, %11, %12, %13, %14, %15, "
    "%16, %17, %18, %19, %20, %21, %22, %23, %24, %25, %26, %27, %28, %29, %30, %31}, %32, %33, p, 1, 1, %34, %35;\n}\n"
    : "=f"(d[0]), "=f"(d[1]), "=f"(d[2]), "=f"(d[3]), "=f"(d[4]), "=f"(d[5]), "=f"(d[6]), "=f"(d[7]),
      "=f"(d[8]), "=f"(d[9]), "=f"(d[10]), "=f"(d[11]), "=f"(d[12]), "=f"(d[13]), "=f"(d[14]), "=f"(d[15]),
      "=f"(d[16]), "=f"(d[17]), "=f"(d[18]), "=f"(d[19]), "=f"(d[20]), "=f"(d[21]), "=f"(d[22]), "=f"(d[23]),
      "=f"(d[24]), "=f"(d[25]), "=f"(d[26]), "=f"(d[27]), "=f"(d[28]), "=f"(d[29]), "=f"(d[30]), "=f"(d[31])
    : "l"(da), "l"(db), "n"(TA), "n"(TB));
}
__device__ __forceinline__ void ss64x4(float* d, const D2* c, int on) {
  asm volatile("{\n.reg .pred p, z, c;\nsetp.eq.b32 p, 0, 0;\nsetp.ne.b32 z, 0, 0;\nsetp.eq.b32 c, %40, 0;\n"
    "wgmma.mma_async.sync.aligned.m64n64k16.f32.bf16.bf16 "
    "{%0, %1, %2, %3, %4, %5, %6, %7, %8, %9, %10, %11, %12, %13, %14, %15, "
    "%16, %17, %18, %19, %20, %21, %22, %23, %24, %25, %26, %27, %28, %29, %30, %31}, %32, %33, z, 1, 1, 0, 1;\n"
    "wgmma.commit_group.sync.aligned;\n@c bra.uni X4_DONE;\n"
    "wgmma.mma_async.sync.aligned.m64n64k16.f32.bf16.bf16 "
    "{%0, %1, %2, %3, %4, %5, %6, %7, %8, %9, %10, %11, %12, %13, %14, %15, "
    "%16, %17, %18, %19, %20, %21, %22, %23, %24, %25, %26, %27, %28, %29, %30, %31}, %34, %35, p, 1, 1, 0, 1;\n"
    "wgmma.mma_async.sync.aligned.m64n64k16.f32.bf16.bf16 "
    "{%0, %1, %2, %3, %4, %5, %6, %7, %8, %9, %10, %11, %12, %13, %14, %15, "
    "%16, %17, %18, %19, %20, %21, %22, %23, %24, %25, %26, %27, %28, %29, %30, %31}, %36, %37, p, 1, 1, 0, 1;\n"
    "wgmma.mma_async.sync.aligned.m64n64k16.f32.bf16.bf16 "
    "{%0, %1, %2, %3, %4, %5, %6, %7, %8, %9, %10, %11, %12, %13, %14, %15, "
    "%16, %17, %18, %19, %20, %21, %22, %23, %24, %25, %26, %27, %28, %29, %30, %31}, %38, %39, p, 1, 1, 0, 1;\n"
    "wgmma.commit_group.sync.aligned;\nX4_DONE:\n}\n"
    : "=f"(d[0]), "=f"(d[1]), "=f"(d[2]), "=f"(d[3]), "=f"(d[4]), "=f"(d[5]), "=f"(d[6]), "=f"(d[7]),
      "=f"(d[8]), "=f"(d[9]), "=f"(d[10]), "=f"(d[11]), "=f"(d[12]), "=f"(d[13]), "=f"(d[14]), "=f"(d[15]),
      "=f"(d[16]), "=f"(d[17]), "=f"(d[18]), "=f"(d[19]), "=f"(d[20]), "=f"(d[21]), "=f"(d[22]), "=f"(d[23]),
      "=f"(d[24]), "=f"(d[25]), "=f"(d[26]), "=f"(d[27]), "=f"(d[28]), "=f"(d[29]), "=f"(d[30]), "=f"(d[31])
    : "l"(c[0].a), "l"(c[0].b), "l"(c[1].a), "l"(c[1].b), "l"(c[2].a), "l"(c[2].b), "l"(c[3].a), "l"(c[3].b), "r"(on));
}
template <int TB> __device__ __forceinline__ void rs32a(float* d, const uint32_t* a, uint64_t db) {
  asm volatile("{\n.reg .pred p;\nsetp.eq.b32 p, 0, 0;\n"
    "wgmma.mma_async.sync.aligned.m64n32k16.f32.bf16.bf16 "
    "{%0, %1, %2, %3, %4, %5, %6, %7, %8, %9, %10, %11, %12, %13, %14, %15}, {%16, %17, %18, %19}, %20, p, 1, 1, %21;\n}\n"
    : "+f"(d[0]), "+f"(d[1]), "+f"(d[2]), "+f"(d[3]), "+f"(d[4]), "+f"(d[5]), "+f"(d[6]), "+f"(d[7]),
      "+f"(d[8]), "+f"(d[9]), "+f"(d[10]), "+f"(d[11]), "+f"(d[12]), "+f"(d[13]), "+f"(d[14]), "+f"(d[15])
    : "r"(a[0]), "r"(a[1]), "r"(a[2]), "r"(a[3]), "l"(db), "n"(TB));
}
template <int TB> __device__ __forceinline__ void rs32z(float* d, const uint32_t* a, uint64_t db) {
  asm volatile("{\n.reg .pred p;\nsetp.ne.b32 p, 0, 0;\n"
    "wgmma.mma_async.sync.aligned.m64n32k16.f32.bf16.bf16 "
    "{%0, %1, %2, %3, %4, %5, %6, %7, %8, %9, %10, %11, %12, %13, %14, %15}, {%16, %17, %18, %19}, %20, p, 1, 1, %21;\n}\n"
    : "=&f"(d[0]), "=&f"(d[1]), "=&f"(d[2]), "=&f"(d[3]), "=&f"(d[4]), "=&f"(d[5]), "=&f"(d[6]), "=&f"(d[7]),
      "=&f"(d[8]), "=&f"(d[9]), "=&f"(d[10]), "=&f"(d[11]), "=&f"(d[12]), "=&f"(d[13]), "=&f"(d[14]), "=&f"(d[15])
    : "r"(a[0]), "r"(a[1]), "r"(a[2]), "r"(a[3]), "l"(db), "n"(TB));
}
template <int TB> __device__ __forceinline__ void rs40a(float* d, const uint32_t* a, uint64_t db) {
  asm volatile("{\n.reg .pred p;\nsetp.eq.b32 p, 0, 0;\n"
    "wgmma.mma_async.sync.aligned.m64n40k16.f32.bf16.bf16 "
    "{%0, %1, %2, %3, %4, %5, %6, %7, %8, %9, %10, %11, %12, %13, %14, %15, "
    "%16, %17, %18, %19}, {%20, %21, %22, %23}, %24, p, 1, 1, %25;\n}\n"
    : "+f"(d[0]), "+f"(d[1]), "+f"(d[2]), "+f"(d[3]), "+f"(d[4]), "+f"(d[5]), "+f"(d[6]), "+f"(d[7]),
      "+f"(d[8]), "+f"(d[9]), "+f"(d[10]), "+f"(d[11]), "+f"(d[12]), "+f"(d[13]), "+f"(d[14]), "+f"(d[15]),
      "+f"(d[16]), "+f"(d[17]), "+f"(d[18]), "+f"(d[19])
    : "r"(a[0]), "r"(a[1]), "r"(a[2]), "r"(a[3]), "l"(db), "n"(TB));
}
template <int TB> __device__ __forceinline__ void rs40z(float* d, const uint32_t* a, uint64_t db) {
  asm volatile("{\n.reg .pred p;\nsetp.ne.b32 p, 0, 0;\n"
    "wgmma.mma_async.sync.aligned.m64n40k16.f32.bf16.bf16 "
    "{%0, %1, %2, %3, %4, %5, %6, %7, %8, %9, %10, %11, %12, %13, %14, %15, "
    "%16, %17, %18, %19}, {%20, %21, %22, %23}, %24, p, 1, 1, %25;\n}\n"
    : "=&f"(d[0]), "=&f"(d[1]), "=&f"(d[2]), "=&f"(d[3]), "=&f"(d[4]), "=&f"(d[5]), "=&f"(d[6]), "=&f"(d[7]),
      "=&f"(d[8]), "=&f"(d[9]), "=&f"(d[10]), "=&f"(d[11]), "=&f"(d[12]), "=&f"(d[13]), "=&f"(d[14]), "=&f"(d[15]),
      "=&f"(d[16]), "=&f"(d[17]), "=&f"(d[18]), "=&f"(d[19])
    : "r"(a[0]), "r"(a[1]), "r"(a[2]), "r"(a[3]), "l"(db), "n"(TB));
}
template <int TB> __device__ __forceinline__ void rs72a(float* d, const uint32_t* a, uint64_t db) {
  asm volatile("{\n.reg .pred p;\nsetp.eq.b32 p, 0, 0;\n"
    "wgmma.mma_async.sync.aligned.m64n72k16.f32.bf16.bf16 "
    "{%0, %1, %2, %3, %4, %5, %6, %7, %8, %9, %10, %11, %12, %13, %14, %15, "
    "%16, %17, %18, %19, %20, %21, %22, %23, %24, %25, %26, %27, %28, %29, %30, %31, "
    "%32, %33, %34, %35}, {%36, %37, %38, %39}, %40, p, 1, 1, %41;\n}\n"
    : "+f"(d[0]), "+f"(d[1]), "+f"(d[2]), "+f"(d[3]), "+f"(d[4]), "+f"(d[5]), "+f"(d[6]), "+f"(d[7]),
      "+f"(d[8]), "+f"(d[9]), "+f"(d[10]), "+f"(d[11]), "+f"(d[12]), "+f"(d[13]), "+f"(d[14]), "+f"(d[15]),
      "+f"(d[16]), "+f"(d[17]), "+f"(d[18]), "+f"(d[19]), "+f"(d[20]), "+f"(d[21]), "+f"(d[22]), "+f"(d[23]),
      "+f"(d[24]), "+f"(d[25]), "+f"(d[26]), "+f"(d[27]), "+f"(d[28]), "+f"(d[29]), "+f"(d[30]), "+f"(d[31]),
      "+f"(d[32]), "+f"(d[33]), "+f"(d[34]), "+f"(d[35])
    : "r"(a[0]), "r"(a[1]), "r"(a[2]), "r"(a[3]), "l"(db), "n"(TB));
}
template <int TB> __device__ __forceinline__ void rs72z(float* d, const uint32_t* a, uint64_t db) {
  asm volatile("{\n.reg .pred p;\nsetp.ne.b32 p, 0, 0;\n"
    "wgmma.mma_async.sync.aligned.m64n72k16.f32.bf16.bf16 "
    "{%0, %1, %2, %3, %4, %5, %6, %7, %8, %9, %10, %11, %12, %13, %14, %15, "
    "%16, %17, %18, %19, %20, %21, %22, %23, %24, %25, %26, %27, %28, %29, %30, %31, "
    "%32, %33, %34, %35}, {%36, %37, %38, %39}, %40, p, 1, 1, %41;\n}\n"
    : "=&f"(d[0]), "=&f"(d[1]), "=&f"(d[2]), "=&f"(d[3]), "=&f"(d[4]), "=&f"(d[5]), "=&f"(d[6]), "=&f"(d[7]),
      "=&f"(d[8]), "=&f"(d[9]), "=&f"(d[10]), "=&f"(d[11]), "=&f"(d[12]), "=&f"(d[13]), "=&f"(d[14]), "=&f"(d[15]),
      "=&f"(d[16]), "=&f"(d[17]), "=&f"(d[18]), "=&f"(d[19]), "=&f"(d[20]), "=&f"(d[21]), "=&f"(d[22]), "=&f"(d[23]),
      "=&f"(d[24]), "=&f"(d[25]), "=&f"(d[26]), "=&f"(d[27]), "=&f"(d[28]), "=&f"(d[29]), "=&f"(d[30]), "=&f"(d[31]),
      "=&f"(d[32]), "=&f"(d[33]), "=&f"(d[34]), "=&f"(d[35])
    : "r"(a[0]), "r"(a[1]), "r"(a[2]), "r"(a[3]), "l"(db), "n"(TB));
}
template <int TB> __device__ __forceinline__ void rs128a(float* d, const uint32_t* a, uint64_t db) {
  asm volatile("{\n.reg .pred p;\nsetp.eq.b32 p, 0, 0;\n"
    "wgmma.mma_async.sync.aligned.m64n128k16.f32.bf16.bf16 "
    "{%0, %1, %2, %3, %4, %5, %6, %7, %8, %9, %10, %11, %12, %13, %14, %15, "
    "%16, %17, %18, %19, %20, %21, %22, %23, %24, %25, %26, %27, %28, %29, %30, %31, "
    "%32, %33, %34, %35, %36, %37, %38, %39, %40, %41, %42, %43, %44, %45, %46, %47, "
    "%48, %49, %50, %51, %52, %53, %54, %55, %56, %57, %58, %59, %60, %61, %62, %63}, {%64, %65, %66, %67}, %68, p, 1, 1, %69;\n}\n"
    : "+f"(d[0]), "+f"(d[1]), "+f"(d[2]), "+f"(d[3]), "+f"(d[4]), "+f"(d[5]), "+f"(d[6]), "+f"(d[7]),
      "+f"(d[8]), "+f"(d[9]), "+f"(d[10]), "+f"(d[11]), "+f"(d[12]), "+f"(d[13]), "+f"(d[14]), "+f"(d[15]),
      "+f"(d[16]), "+f"(d[17]), "+f"(d[18]), "+f"(d[19]), "+f"(d[20]), "+f"(d[21]), "+f"(d[22]), "+f"(d[23]),
      "+f"(d[24]), "+f"(d[25]), "+f"(d[26]), "+f"(d[27]), "+f"(d[28]), "+f"(d[29]), "+f"(d[30]), "+f"(d[31]),
      "+f"(d[32]), "+f"(d[33]), "+f"(d[34]), "+f"(d[35]), "+f"(d[36]), "+f"(d[37]), "+f"(d[38]), "+f"(d[39]),
      "+f"(d[40]), "+f"(d[41]), "+f"(d[42]), "+f"(d[43]), "+f"(d[44]), "+f"(d[45]), "+f"(d[46]), "+f"(d[47]),
      "+f"(d[48]), "+f"(d[49]), "+f"(d[50]), "+f"(d[51]), "+f"(d[52]), "+f"(d[53]), "+f"(d[54]), "+f"(d[55]),
      "+f"(d[56]), "+f"(d[57]), "+f"(d[58]), "+f"(d[59]), "+f"(d[60]), "+f"(d[61]), "+f"(d[62]), "+f"(d[63])
    : "r"(a[0]), "r"(a[1]), "r"(a[2]), "r"(a[3]), "l"(db), "n"(TB));
}
template <int TB> __device__ __forceinline__ void rs128z(float* d, const uint32_t* a, uint64_t db) {
  asm volatile("{\n.reg .pred p;\nsetp.ne.b32 p, 0, 0;\n"
    "wgmma.mma_async.sync.aligned.m64n128k16.f32.bf16.bf16 "
    "{%0, %1, %2, %3, %4, %5, %6, %7, %8, %9, %10, %11, %12, %13, %14, %15, "
    "%16, %17, %18, %19, %20, %21, %22, %23, %24, %25, %26, %27, %28, %29, %30, %31, "
    "%32, %33, %34, %35, %36, %37, %38, %39, %40, %41, %42, %43, %44, %45, %46, %47, "
    "%48, %49, %50, %51, %52, %53, %54, %55, %56, %57, %58, %59, %60, %61, %62, %63}, {%64, %65, %66, %67}, %68, p, 1, 1, %69;\n}\n"
    : "=&f"(d[0]), "=&f"(d[1]), "=&f"(d[2]), "=&f"(d[3]), "=&f"(d[4]), "=&f"(d[5]), "=&f"(d[6]), "=&f"(d[7]),
      "=&f"(d[8]), "=&f"(d[9]), "=&f"(d[10]), "=&f"(d[11]), "=&f"(d[12]), "=&f"(d[13]), "=&f"(d[14]), "=&f"(d[15]),
      "=&f"(d[16]), "=&f"(d[17]), "=&f"(d[18]), "=&f"(d[19]), "=&f"(d[20]), "=&f"(d[21]), "=&f"(d[22]), "=&f"(d[23]),
      "=&f"(d[24]), "=&f"(d[25]), "=&f"(d[26]), "=&f"(d[27]), "=&f"(d[28]), "=&f"(d[29]), "=&f"(d[30]), "=&f"(d[31]),
      "=&f"(d[32]), "=&f"(d[33]), "=&f"(d[34]), "=&f"(d[35]), "=&f"(d[36]), "=&f"(d[37]), "=&f"(d[38]), "=&f"(d[39]),
      "=&f"(d[40]), "=&f"(d[41]), "=&f"(d[42]), "=&f"(d[43]), "=&f"(d[44]), "=&f"(d[45]), "=&f"(d[46]), "=&f"(d[47]),
      "=&f"(d[48]), "=&f"(d[49]), "=&f"(d[50]), "=&f"(d[51]), "=&f"(d[52]), "=&f"(d[53]), "=&f"(d[54]), "=&f"(d[55]),
      "=&f"(d[56]), "=&f"(d[57]), "=&f"(d[58]), "=&f"(d[59]), "=&f"(d[60]), "=&f"(d[61]), "=&f"(d[62]), "=&f"(d[63])
    : "r"(a[0]), "r"(a[1]), "r"(a[2]), "r"(a[3]), "l"(db), "n"(TB));
}

template <int V> struct IC { static constexpr int value = V; };
struct PfType { const char* base; uint32_t gl, gh, sp, sr, su, l4, l2; };
struct Params {
  const __nv_bfloat16 *x, *w;
  unsigned* cnt;
  uint32_t one;
  const __nv_bfloat16 *shift, *ssmD;
  __nv_bfloat16* out;
  uint4* o; float* kv;
  const char *k, *v;
  PfType pt[6];
  uint8_t pf[32];
  uint64_t cd[18];
};

struct Tmp { float t0, t1; };
__device__ __forceinline__ void mul2(Tmp& t, float a0, float b0, float a1, float b1) {
  asm volatile("@p_one mul.rn.f32 %0, %2, %3;\n@p_one mul.rn.f32 %1, %4, %5;" : "+f"(t.t0), "+f"(t.t1) : "f"(a0), "f"(b0), "f"(a1), "f"(b1)); }
__device__ __forceinline__ void add2(Tmp& t, float a0, float b0, float a1, float b1) {
  asm volatile("@p_one add.rn.f32 %0, %2, %3;\n@p_one add.rn.f32 %1, %4, %5;" : "+f"(t.t0), "+f"(t.t1) : "f"(a0), "f"(b0), "f"(a1), "f"(b1)); }
__device__ __forceinline__ void fma2(Tmp& t, float a0, float b0, float a1, float b1) { t.t0 = fmaf(a0, b0, t.t0); t.t1 = fmaf(a1, b1, t.t1); }
__device__ __forceinline__ uint32_t bfma2(uint32_t a, uint32_t b, uint32_t c) { uint32_t r; asm("fma.rn.bf16x2 %0, %1, %2, %3;" : "=r"(r) : "r"(a), "r"(b), "r"(c)); return r; }
struct Tw { uint32_t c[2], s[2], ns[2]; };
__device__ __forceinline__ void rot(uint32_t& u, uint32_t& v, const Tw& w, int k) {
  asm("{\n.reg .b32 a, b;\nmul.rn.bf16x2 a, %0, %2;\nmul.rn.bf16x2 b, %0, %3;\nfma.rn.bf16x2 %0, %1, %4, a;\nfma.rn.bf16x2 %1, %1, %2, b;\n}"
    : "+r"(u), "+r"(v) : "r"(w.c[k]), "r"(w.s[k]), "r"(w.ns[k]));
}
__device__ __forceinline__ void pack_fwd(uint32_t (&f)[2][2][4], const float* a) {
  #pragma unroll
  for (int j = 0; j < 16; j++) f[j >> 3][(j >> 1) & 1][2 * (j & 1) + ((j >> 2) & 1)] = fresh(pack_bf16(a[2 * j], a[2 * j + 1]));
}
__device__ __forceinline__ void rot_fwd(uint32_t (&f)[2][2][4], const Tw& w) {
  #pragma unroll
  for (int j = 0; j < 8; j++) rot(f[j >> 2][j & 1][(j >> 1) & 1], f[j >> 2][j & 1][2 + ((j >> 1) & 1)], w, j & 1);
}
__device__ __forceinline__ void add_skip(float* h, float d) {
  asm volatile("add.rn.f32 %0, %0, %4;\nadd.rn.f32 %1, %1, %4;\nadd.rn.f32 %2, %2, %4;\nadd.rn.f32 %3, %3, %4;" : "+f"(h[0]), "+f"(h[1]), "+f"(h[4]), "+f"(h[5]) : "f"(d)); }
__device__ __forceinline__ void dft16h(float* d, const uint32_t (&f)[2][4], const D2& dF) { rs32z<0>(d, f[0], dF.a); rs32a<0>(d, f[1], dF.b); }
#define SP(h, p, im, k) (((p) >> 1 ? hi : lo) + 16 * (h) + 8 * (im) + 4 * (k) + 2 * ((p) & 1))
template <int PH, int G0 = 0, int G1 = 8> __device__ __forceinline__ void prod(Tmp& t, uint32_t (&f)[2][4], const float* lo, const float* hi) {
  #pragma unroll
  for (int g = G0; g < G1; g++) {
    const int p = 2 * PH + 1 - (g >> 2), k = (g >> 1) & 1, im = g & 1;
    #pragma unroll
    for (int q = 0; q <= p; q++) {
      const float *hr = SP(1, q, 0, k), *hi_ = SP(1, q, 1, k), *xa = SP(0, p - q, im, k), *xb = SP(0, p - q, 1 - im, k);
      if (q == 0) mul2(t, hr[0], xa[0], hr[1], xa[1]); else fma2(t, hr[0], xa[0], hr[1], xa[1]);
      if (im) fma2(t, hi_[0], xb[0], hi_[1], xb[1]); else fma2(t, -hi_[0], xb[0], -hi_[1], xb[1]);
    }
    f[k][2 * (1 - im) + (p & 1)] = pack_bf16(t.t0, t.t1);
  }
}

constexpr uint64_t dA = cdesc(A_OFF, 2048, 128, 0), dAi = cdesc(A_OFF, 128, 1024, 0), dF0 = cdesc(F_OFF, 128, 512, 0),
                   dT0 = cdesc(T_OFF, 1024, 128, 0), dH0 = cdesc(H_OFF, 1024, 256, 3), dX0 = cdesc(X_OFF, 1024, 128, 0);
#define CONV_DESC dF0, dF0 + 16, dAi, dT0, dAi + 16, dT0 + 128, dAi + 32, dT0 + 256, dAi + 48, dT0 + 384, dA, dH0, dA + 256, dH0 + 32, dA, dX0, dA + 256, dX0 + 128
__device__ __forceinline__ void make_tw(Tw& tw, int ht) {
  #pragma unroll
  for (int i = 0; i < 2; i++) {
    float c0, s0, c1, s1;
    unit_root<11>((4 * (ht >> 2) + 1) * (i * 8 + 2 * (ht & 3)), c0, s0);
    unit_root<11>((4 * (ht >> 2) + 1) * (i * 8 + 2 * (ht & 3) + 1), c1, s1);
    tw.c[i] = pack_bf16(c0, c1); tw.s[i] = pack_bf16(s0, s1); tw.ns[i] = fresh(tw.s[i] ^ 0x80008000u);
  }
}
template <bool COMMIT = true> __device__ __forceinline__ void dft32_h(float* r, const D2* d) {
  ss64z<1, 1>(r, d[0].a, d[0].b); ss64a<1, 1>(r, d[1].a, d[1].b);
  if (COMMIT) wg_commit();
}
template <bool COMMIT = true> __device__ __forceinline__ void dft32_x(float* r, D2* d) {
  ss64z<1, 0>(r, d[0].a, d[0].b); ss64a<1, 0>(r, d[1].a, d[1].b);
  if (COMMIT) wg_commit();
  d[0].b = dofs(d[0].b, XS); d[1].b = dofs(d[1].b, XS);
}
__device__ __forceinline__ void pack_inv(uint32_t (&u)[2][2][4], const float* r) {
  #pragma unroll
  for (int j = 0; j < 16; j++) u[j >> 3][(j >> 2) & 1][2 * (j & 1) + ((j >> 1) & 1)] = fresh(pack_bf16(r[2 * j], r[2 * j + 1]));
}
__device__ __forceinline__ void rot_inv(uint32_t (&u)[2][2][4], const Tw& tw, uint32_t ta) {
  #pragma unroll
  for (int m = 0; m < 2; m++) {
    #pragma unroll
    for (int j = 0; j < 4; j++) rot(u[m][0][j], u[m][1][j], tw, j & 1);
    stsm4(ta + m * 512, u[m][1][0], u[m][1][1], u[m][1][2], u[m][1][3]);
    stsm4(ta + 1024 + m * 512, u[m][0][0], u[m][0][1], u[m][0][2], u[m][0][3]);
  }
}
__device__ __forceinline__ void idft32(float* r, const D2* d) {
  wg_fence();
  ss64z<0, 1>(r, d[0].a, d[0].b);
  #pragma unroll
  for (int j = 1; j < 4; j++) ss64a<0, 1>(r, d[j].a, d[j].b);
  wg_commit();
}
__device__ __forceinline__ void finish(Tmp& t, const float* r, int ch, int ht, int rank, uint32_t y0, uint32_t y1) {
  const uint32_t ya = X_OFF + ch * XS + (ch & 1) * 16, yb = BAR_OFF + (B_YR + ch) * 8;
  uint32_t y[8];
  #pragma unroll
  for (int j = 0; j < 8; j++) {
    if (j >= 2) add2(t, r[4 * j], r[4 * j - 6], r[4 * j + 1], r[4 * j - 5]);
    y[j] = j < 2 ? pack_bf16(r[4 * j], r[4 * j + 1]) : pack_bf16(t.t0, t.t1);
  }
  st_async128(y0 + ya + (ht ^ (rank * 4)) * 16 + rank * (YX - XS), y0 + yb, y[0], y[1], y[2], y[3]);
  st_async128(y1 + ya + (ht ^ (rank * 4) ^ 4) * 16 + (rank ^ 1) * (YX - XS), y1 + yb, y[4], y[5], y[6], y[7]);
}

struct Team { uint32_t bars, rel, wofs; bool lead; };
template <bool M> __device__ __forceinline__ void mid_wait() { if (M) { wg_commit(); wg_wait<0>(); wg_fence(); } }
template <int J, bool M = false> __device__ __forceinline__ void kv_issue(float* aK, float* aV, uint32_t xo, int sd) {
  constexpr uint64_t dw = cdesc(W_OFF + J * 8192, 8192, 1024, 1);
  const uint64_t dx = dofs(cdesc((J & 1) * 64, 16, 1024, 1), xo);
  wg_fence();
  ss128p<1, 0>(aV, dw + (4096 >> 4), dx, sd);
  ss128p<1, 0>(aK, dw, dx, sd);
  mid_wait<M>();
  ss128a<1, 0>(aV, dw + (6144 >> 4), dofs(dx, 32));
  ss128a<1, 0>(aK, dw + (2048 >> 4), dofs(dx, 32));
  wg_commit();
}
template <int O, int J, int H> __device__ __forceinline__ void g2_half(float* acc, const Team& c) {
  constexpr uint64_t db = cdesc(J * SLOT + 16384 + H * 4096, 8192, 1024, 1);
  const uint64_t da = dofs(O ? cdesc(J * SLOT + H * 4096, 16, 512, 2) : cdesc(J * SLOT + H * 64, 16, 1024, 1), c.wofs);
  wg_fence();
  ss128a<0, 1>(acc, da, db);
  ss128a<0, 1>(acc, dofs(da, 32), db + (2048 >> 4));
  wg_commit();
}
template <int O, int J, bool M = false, bool FIRST = false> __device__ __forceinline__ void g2_issue(float* acc, const Team& c) {
  constexpr uint64_t db = cdesc(J * SLOT + 16384, 8192, 1024, 1);
  const uint64_t da = dofs(O ? cdesc(J * SLOT, 16, 512, 2) : cdesc(J * SLOT, 16, 1024, 1), c.wofs);
  wg_fence();
  if (FIRST) ss128z<0, 1>(acc, da, db); else ss128a<0, 1>(acc, da, db);
  ss128a<0, 1>(acc, dofs(da, 32), db + (2048 >> 4));
  mid_wait<M>();
  ss128a<0, 1>(acc, dofs(da, O ? 4096 : 64), db + (4096 >> 4));
  ss128a<0, 1>(acc, dofs(da, O ? 4128 : 96), db + (6144 >> 4));
  wg_commit();
}
template <bool DEEP, bool AB = false, class F>
__device__ __forceinline__ void ring_step(const Team& c, int fb, uint32_t ph, int eb, bool rel, F issue, uint32_t ab = 0, uint32_t aph = 0) {
  uint32_t ok = mbar_try(c.bars + fb * 8, ph);
  if (AB) ok &= mbar_try(ab, aph);
  if (!ok) {
    wg_wait<0>();
    arrive_at(c.rel + eb * 8, rel);
    rel = false;
    mbar_wait(c.bars + fb * 8, ph);
    if (AB) mbar_wait(ab, aph);
  }
  if (!DEEP) { wg_wait<0>(); arrive_at(c.rel + eb * 8, rel); }
  issue();
  if (DEEP) { wg_wait<1>(); arrive_at(c.rel + eb * 8, rel); }
}
template <int N, int I = 0, class R> __device__ __forceinline__ void tail_release(R rel) {
  if constexpr (I <= N) { wg_wait<N - I>(); rel(I - 1); tail_release<N, I + 1>(rel); }
}
template <int N, class F, class R> __device__ __forceinline__ void skew_tail(const Team& c, int ph, F issue, R rel) {
  if (c.wofs) { wg_wait<0>(); rel(-1); mbar_wait(c.bars + B_SK * 8, ph); }
  issue();
  arrive_at(c.bars + B_SK * 8, fresh_tid() == 0);
  tail_release<N>([&](int i) { if (i >= 0 || !c.wofs) rel(i); });
}
__device__ __forceinline__ void phi_a(float* a, uint32_t* f) {
  #pragma unroll
  for (int i = 0; i < 8; i++) {
    asm("cvt.rn.relu.bf16x2.f32 %0, %1, %2;" : "=r"(f[i]) : "f"(a[2 * i + 1]), "f"(a[2 * i]));
    asm("ex2.approx.ftz.f32 %0, %1;" : "=f"(a[2 * i]) : "f"(a[2 * i] * 1.4426950408889634f));
    asm("ex2.approx.ftz.f32 %0, %1;" : "=f"(a[2 * i + 1]) : "f"(a[2 * i + 1] * 1.4426950408889634f));
  }
  pinv<16>(a);
}
__device__ __forceinline__ void phi_s(float* a, uint32_t* f) {
  #pragma unroll
  for (int i = 0; i < 8; i++) {
    asm("cvt.rn.relu.bf16x2.f32 %0, %1, %2;" : "=r"(f[i]) : "f"(a[2 * i + 1]), "f"(a[2 * i]));
    a[2 * i] *= 1.4426950408889634f; a[2 * i + 1] *= 1.4426950408889634f;
  }
  pinv<16>(a);
}
__device__ __forceinline__ void phi_e(float* a) {
  #pragma unroll
  for (int i = 0; i < 16; i++) asm("ex2.approx.ftz.f32 %0, %0;" : "+f"(a[i]));
  pinv<16>(a);
}
__device__ __forceinline__ void phi_b(const float* e, uint32_t* f) {
  #pragma unroll
  for (int i = 0; i < 8; i++) f[i] = badd2(f[i], pack_bf16(__saturatef(e[2 * i] + 1e-6f), __saturatef(e[2 * i + 1] + 1e-6f)));
}
__device__ __forceinline__ int g2_k(int st, int n2) {
  if (!ORD) return (st >> 1) == n2 ? st & 1 : st;
  const int j = (st >> 1) - 1;
  return 2 * (j == 0 ? n2 == 0 : (j == max(n2, 1) ? 7 : j)) + (st & 1);
}

__global__ void __cluster_dims__(2, 1, 1) __launch_bounds__(NTHREADS, 1)
fused_kernel(const __grid_constant__ Params P, const __grid_constant__ CUtensorMap mX, const __grid_constant__ CUtensorMap mW,
             const __grid_constant__ CUtensorMap mWq, const __grid_constant__ CUtensorMap mWo,
             const __grid_constant__ CUtensorMap mK, const __grid_constant__ CUtensorMap mV, const __grid_constant__ CUtensorMap mH,
             const __grid_constant__ CUtensorMap mQ, const __grid_constant__ CUtensorMap mOut, const __grid_constant__ CUtensorMap mOutA,
             const __grid_constant__ CUtensorMap mWp) {
  extern __shared__ __align__(1024) uint8_t smem[];
  asm volatile(".reg .pred p_one;");
  if (__shfl_sync(0xffffffffu, threadIdx.x >> 5, 0) == 0) {
    asm volatile(ELECT "prefetch.tensormap [%0];\n}" :: "l"(&mW) : "memory");
    asm volatile(ELECT "prefetch.tensormap [%0];\n}" :: "l"(&mX) : "memory");
  }
  {
    const uint32_t t = threadIdx.x, bb = blockIdx.x;
    asm volatile("{\n.reg .pred p, q;\nsetp.eq.u32 p, %2, 2;\nsetp.eq.u32 q, %3, 8;\n@p prefetch.global.L2 [%0];\n@q prefetch.global.L2 [%1];\n}"
      :: "l"(reinterpret_cast<const char*>(P.x) + ((bb * 16 + t - 32) * 2048)),
         "l"(reinterpret_cast<const char*>(P.w) + ((bb >> 2) * 2048 + bb * 1024 + t * 128 - 6144)), "r"(t >> 4), "r"(t >> 3));
  }
  const uint32_t sb = uni(smem_u32(smem));
  const uint32_t bars = sb + BAR_OFF;
  const int tid = threadIdx.x, lane = tid & 31;
  const int warp = __shfl_sync(0xffffffffu, tid >> 5, 0);
  const uint32_t ids = uni(wanted_job() * 2 + (blockIdx.x & 1));
#define IDS(w) const int rank = (w) & 1, hp = (w) & 15, g = hp >> 1, mb = (w) >> 4, m2 = hp, n2 = mb, cp = g * 8 + mb; \
               (void)rank; (void)m2; (void)n2; (void)cp
  auto job = [&]() { return (uni(lds32(sb + D_OFF + 52)) & 126) | (ids & 1); };
  auto wrong_job = [&]() {
    mbar_wait(bars + B_EX * 8, 0);
    return uni(lds32(sb + D_OFF + 52) ^ lds32(sb + D_OFF + 56)) != 1;
  };

  if (warp == 0) {
    IDS(ids);
    mbar_init(bars + (B_XF + 2) * 8, 1); mbar_init(bars + B_F0 * 8, 1); mbar_init(bars + B_FULL * 8, 1);
    mbar_expect_tx(bars + B_FULL * 8, 8192);
    tma3d(sb + W_OFF, &mW, hp * 64, 0, 1, bars + B_FULL * 8);
    mbar_expect_tx(bars + (B_XF + 2) * 8, 16384);
    tma2d(sb + 2 * SLOT, &mX, 0, mb * 256, bars + (B_XF + 2) * 8);
    mbar_expect_tx(bars + B_F0 * 8, 16384);
    tma2d(sb + 2 * SLOT + 16384, &mX, 0, mb * 256 + 128, bars + B_F0 * 8);
    #pragma unroll
    for (int i = 1; i < 4; i++) mbar_init(bars + (B_FULL + i) * 8, 1);
    #pragma unroll
    for (int i = 1; i < 4; i++) {
      mbar_expect_tx(bars + (B_FULL + i) * 8, 8192);
      tma3d(sb + W_OFF + i * 8192, &mW, hp * 64, i * 32, 1, bars + (B_FULL + i) * 8);
    }
    mbar_init(bars + B_XF * 8, 1); mbar_init(bars + (B_XF + 1) * 8, 1);
  } else if (warp >= 6) {
    const uint32_t cnt = warp < 12 || warp == 15 ? 1 : 4, b0 = bars + (warp - 4) * 32;
    #pragma unroll
    for (int i = 0; i < 4; i++) mbar_init(b0 + i * 8, i == 3 && warp == 15 ? 4 : cnt);
    if (warp == 8 || warp == 9) {
      #pragma unroll
      for (int i = 0; i < 4; i++) mbar_expect_tx(b0 + i * 8, 4096);
    } else if ((warp & 13) == 13) {
      mbar_expect_tx(bars + (warp == 13 ? B_KVB : B_EX) * 8, warp == 13 ? 5120 : 8);
    }
  }
  asm volatile("fence.mbarrier_init.release.cluster;" ::: "memory");
  __syncwarp();
  asm volatile("barrier.cluster.arrive.relaxed.aligned;" ::: "memory");

  if (warp < 8) {
    asm volatile("setmaxnreg.inc.sync.aligned.u32 %0;" :: "n"(160));
    const int wg = warp >> 2;
    Team c;
    c.bars = bars; c.rel = mapa(bars, tid & 1); c.wofs = wg * 8192; c.lead = (tid & 127) < 2;
    uint32_t key = P.one;
    auto gemm2 = [&](float* a, auto O_, auto SK_, auto last) {
      constexpr int O = O_.value, SK = SK_.value;
      static_assert(SK >= 1 && SK <= 3, "tail");
      uint32_t ph = 1;
      const uint32_t ab = bars + B_FA * 8 + wg * 32;
      #pragma unroll 1
      for (int it = 1; it < 4; it++, ph ^= 1) {
        ring_step<false, O>(c, B_FULL2, ph ^ O, B_EMPTY2 + 3, c.lead, [&]() { g2_issue<O, 0, (MID >> (1 + O)) & 1>(a, c); }, ab, ph ^ 1);
        if (!O && (tid & 127) == 0) OSTAMP(55 + wg * 4 + it);
        if (O && (tid & 127) == 0) OSTAMP(40 + wg * 4 + it);
        if (SK == 3 && it == 3) break;
        ring_step<false, O>(c, B_FULL2 + 1, ph, B_EMPTY2, c.lead && (!O || it < 3), [&]() { g2_issue<O, 1, (MID >> (1 + O)) & 1>(a, c); }, ab + 8, ph);
        if (SK == 2 && it == 3) break;
        ring_step<false, O>(c, B_FULL2 + 2, ph, B_EMPTY2 + 1, c.lead && (!O || it < 3), [&]() { g2_issue<O, 2, (MID >> (1 + O)) & 1>(a, c); }, ab + 16, ph);
        if (SK == 1 && it == 3) break;
        ring_step<false, O>(c, B_FULL2 + 3, ph, B_EMPTY2 + 2, c.lead, [&]() { g2_issue<O, 3, (MID >> (1 + O)) & 1>(a, c); }, ab + 24, ph);
      }
      if (!O && HT) {
        auto rel = [&](int jj, bool on) { arrive_at(c.rel + (B_EMPTY2 + jj) * 8, c.lead && on); };
        if (wg) { wg_wait<0>(); rel(3 - SK, true); mbar_wait(bars + B_SK * 8, 1); }
        auto st = [&](auto J_) {
          constexpr int J = J_.value;
          mbar_wait(bars + (B_FULL2 + J) * 8, 1);
          g2_half<0, J, 0>(a, c);
          wg_wait<1>(); rel(J - 1, J > 4 - SK || !wg);
          g2_half<0, J, 1>(a, c);
          if (J < 3) wg_wait<1>();
        };
        if (SK >= 3) st(IC<1>());
        if (SK >= 2) st(IC<2>());
        st(IC<3>());
        arrive_at(bars + B_SK * 8, fresh_tid() == 0);
        last();
        wg_wait<0>(); rel(3, true);
      } else
      skew_tail<SK>(c, O ^ 1,
        [&]() {
          auto full = [&](int jj) { mbar_wait(bars + (B_FULL2 + jj) * 8, 1); if (O) mbar_wait(ab + jj * 8, 1); };
          if (SK >= 3) { full(1); g2_issue<O, 1>(a, c); }
          if (SK >= 2) { full(2); g2_issue<O, 2>(a, c); }
          full(3); g2_issue<O, 3>(a, c);
          last();
        },
        [&](int i) { if (!O) arrive_at(c.rel + (B_EMPTY2 + ((16 - SK + i) & 3)) * 8, c.lead); });
      pinv<64>(a);
    };
    float aq[64];
    {
      float aK[64], aV[64];
      if (wg == 0) { kv_issue<0>(aK, aV, 0, 0); wg_wait<0>(); }
      cluster_wait();
      if (wg == 1) mbar_wait(bars + B_F0 * 8, 0);
      static_assert(SK1 >= 1 && SK1 <= 3, "tail");
      uint32_t ph = 0, xs = 2, xp = 0;
      auto next_x = [&]() { if (xs == 1) xp ^= 1; xs = xs == 2 ? 0 : xs + 1; };
      bool rel = false;
      int look = 5;
      #pragma unroll 1
      for (int it = 0; it < 8; it++, ph ^= 1) {
        uint32_t xo = xs * SLOT + wg * 16384;
        ring_step<false, true>(c, B_FULL, ph, B_EMPTY + 3, rel, [&]() { kv_issue<0, MID & 1>(aK, aV, xo, it); if (tid == 0 && it == 0) OSTAMP(1); }, bars + (B_XF + xs) * 8, xp);
        if (SK1 == 3 && it == 7) break;
        next_x();
        ring_step<false>(c, B_FULL + 1, ph, B_EMPTY, c.lead, [&]() { kv_issue<1, MID & 1>(aK, aV, xo, 1); });
        if (SK1 == 2 && it == 7) break;
        xo = xs * SLOT + wg * 16384;
        ring_step<false, true>(c, B_FULL + 2, ph, B_EMPTY + 1, c.lead, [&]() { kv_issue<2, MID & 1>(aK, aV, xo, 1); }, bars + (B_XF + xs) * 8, xp);
        if (SK1 == 1 && it == 7) break;
        next_x();
        ring_step<false>(c, B_FULL + 3, ph, B_EMPTY + 2, c.lead, [&]() { kv_issue<3, MID & 1>(aK, aV, xo, 1); });
        rel = c.lead;
        if (it == look && wrong_job()) it = look = -1;
      }
      skew_tail<SK1>(c, 0,
        [&]() {
          auto wait = [&](uint32_t a) { mbar_wait(a, 1); };
          if (SK1 >= 3) { wait(bars + (B_FULL + 1) * 8); kv_issue<1>(aK, aV, SLOT + wg * 16384, 1); }
          if (SK1 >= 2) { wait(bars + (B_FULL + 2) * 8); wait(bars + (B_XF + 2) * 8); kv_issue<2>(aK, aV, 2 * SLOT + wg * 16384, 1); }
          wait(bars + (B_FULL + 3) * 8); kv_issue<3>(aK, aV, 2 * SLOT + wg * 16384, 1);
        },
        [&](int i) { arrive_at(c.rel + (B_EMPTY + ((32 - SK1 + i) & 3)) * 8, c.lead); });
      pinv<64>(aV); pinv<64>(aK);
      if (tid == 128) OSTAMP(3);
      const uint32_t vb = sb + M_OFF + wg * VT;
      float kv[36];
      uint32_t kf[4][8];
      const uint64_t dv = dofs(cdesc(M_OFF, 1152, 128, 0), wg * VT);
      const int t = fresh_tid();
      const uint32_t va = vb + ((t >> 4) & 1) * 1152 + ((t >> 5) & 3) * 256 + (t & 15) * 16;
      mbar_wait(bars + B_X * 8, 0);
      #pragma unroll
      for (int i = 0; i < 8; i++) {
        const float* a = aV + 8 * i;
        stsm4(va + i * 2304, pack_bf16(a[0], a[1]), pack_bf16(a[2], a[3]), pack_bf16(a[4], a[5]), pack_bf16(a[6], a[7]));
      }
      phi_a(aK + 48, kf[3]);
      mbar_wait(bars + B_FULL2 * 8, 0);
      if ((tid & 127) == 0) OSTAMP(50 + wg);
      g2_issue<0, 0, false, true>(aq, c);
      sts128(vb + ((t & 127) >> 3) * 1152 + 1024 + (t & 7) * 16, 0x3f803f80u, 0x3f803f80u, 0x3f803f80u, 0x3f803f80u);
      phi_a(aK + 32, kf[2]); phi_b(aK + 48, kf[3]);
      sched_fence(key++);
      ring_step<true>(c, B_FULL2 + 1, 0, B_EMPTY2, c.lead, [&]() { g2_issue<0, 1>(aq, c); });
      phi_a(aK + 16, kf[1]); phi_b(aK + 32, kf[2]);
      sched_fence(key++);
      ring_step<true>(c, B_FULL2 + 2, 0, B_EMPTY2 + 1, c.lead, [&]() { g2_issue<0, 2>(aq, c); });
      phi_a(aK, kf[0]); phi_b(aK + 16, kf[1]);
      sched_fence(key++);
      fence_async_smem(); bar_sync(1 + wg, 128);
      phi_b(aK, kf[0]);
      sched_fence(key++);
      wg_fence();
      #pragma unroll
      for (int ks = 0; ks < 8; ks++) {
        if (ks == 0) rs72z<0>(kv, kf[0], dv); else rs72a<0>(kv, kf[ks >> 1] + 4 * (ks & 1), dofs(dv, ks * 2304));
      }
      wg_commit();
      wg_wait<1>();
      arrive_at(c.rel + (B_EMPTY2 + 2) * 8, c.lead);
      mbar_wait(bars + (B_FULL2 + 3) * 8, 0);
      g2_issue<0, 3>(aq, c);
      wg_wait<1>();
      pinv<36>(kv);
      const int a = fresh_tid() & 127;
      const bool hi = a >= 64;
      #pragma unroll
      for (int u = 0; u < 4; u++) {
        const int o = (u & 1) * 8 + (u & 2);
        sts128(vb + (a ^ ((a >> 3) & 3)) * 16 + u * 2048, __float_as_uint(hi ? kv[16 + o] : kv[o]), __float_as_uint(hi ? kv[17 + o] : kv[o + 1]),
               __float_as_uint(hi ? kv[20 + o] : kv[o + 4]), __float_as_uint(hi ? kv[21 + o] : kv[o + 5]));
      }
      if ((a & 3) < 2) sts32(vb + 8192 + ((a >> 5) * 16 + ((a & 31) >> 2) + (a & 1) * 8) * 4, __float_as_uint((a & 1) ? kv[34] : kv[32]));
      bar_arrive(4, 352);
    }
    if (tid == 0) OSTAMP(4);
    if (tid == 128) OSTAMP(5);
    float acc[64];
    {
      uint32_t kvok, gen, far;
      gemm2(aq, IC<0>(), IC<SK2>(), [&]() {
        kvok = OS ? mbar_try(bars + B_KVB * 8, 0) : 0;
        if (kvok) fence_async_smem();
      });
      if (tid == 0) OSTAMP(6);
      if (tid == 128) OSTAMP(7);
      constexpr uint64_t dk = cdesc(KVB_OFF, 640, 128, 0);
      const uint32_t id2 = job(); IDS(id2);
      float nu[4][20];
      uint32_t pq[4][8], o[4][2][4];
      const int t2 = fresh_tid();
      const uint32_t oo = (t2 & 96) * 32 + (t2 & 28) * 16 + ((t2 ^ (t2 >> 3)) & 3) * 16;
      uint4* og = P.o + ((m2 * 8 + n2) * 4 + wg) * 512 + (oo >> 4);
      auto o_put = [&](int h, int e) {
        if (AB & 8) return;
        asm volatile("st.global.v4.b32 [%0], {%1,%2,%3,%4};" :: "l"(og + (h >> 1) * 1024 + (h & 1) * 256 + e * 32),
          "r"(o[h][e][0]), "r"(o[h][e][1]), "r"(o[h][e][2]), "r"(o[h][e][3]) : "memory");
      };
      auto o_out = [&](int h) {
        pinv<20>(nu[h]);
        #pragma unroll
        for (int e = 0; e < 2; e++) {
          const float* n = nu[h] + 2 * e;
          const float iv = rcp_fast(n[16] + 1e-6f);
          #pragma unroll
          for (int i = 0; i < 4; i++) o[h][e][i] = pack_bf16(n[4 * i] * iv, n[4 * i + 1] * iv);
          o_put(h, e);
        }
      };
      auto o_mma = [&](int h) {
        wg_fence();
        rs40z<1>(nu[h], pq[h], dk + h * (2560 >> 4));
        rs40a<1>(nu[h], pq[h] + 4, dk + h * (2560 >> 4) + (1280 >> 4));
        wg_commit();
      };
#define QSTAMP(i) do { if ((t2 & 127) == 0) TSTAMP(6, wg * 16 + (i)); } while (0)
      QSTAMP(0);
      if (OS) {
        phi_s(aq, pq[0]); phi_e(aq);
        if (OS & 4) phi_s(aq + 16, pq[1]);
        if (!kvok) { mbar_wait(bars + B_KVB * 8, 0); fence_async_smem(); }
        gen = lds32(sb + D_OFF + 40); far = lds32(sb + D_OFF + 48);
        QSTAMP(1);
        #pragma unroll
        for (int u = 0; u < 4; u++) {
          if (OS & 4) {
            if (u < 3) phi_e(aq + 16 * u + 16);
            phi_b(aq + 16 * u, pq[u]);
            o_mma(u);
            if (u < 2) phi_s(aq + 16 * u + 32, pq[u + 2]);
          } else {
            if (u > 0) { phi_s(aq + 16 * u, pq[u]); phi_e(aq + 16 * u); }
            phi_b(aq + 16 * u, pq[u]);
            o_mma(u);
          }
          if (u > 0) { wg_wait<1>(); o_out(u - 1); }
          if ((OS & 2) || u == 3) sched_fence(key++);
          QSTAMP(2 + u);
        }
      } else {
      #pragma unroll
      for (int u = 0; u < 5; u++) {
        if (u >= 3) { wg_wait<1>(); QSTAMP(2 * u + 1); o_out(u - 3); }
        if (u < 4) phi_a(aq + 16 * u, pq[u]);
        if (u > 0) phi_b(aq + 16 * (u - 1), pq[u - 1]);
        if (u == 1) { QSTAMP(2); if (!(AB & 16)) mbar_wait(bars + B_KVB * 8, 0); QSTAMP(3); gen = lds32(sb + D_OFF + 40); far = lds32(sb + D_OFF + 48); fence_async_smem(); } else sched_fence(key++);
        QSTAMP(u ? 2 * u + 2 : 1);
        if (u > 0) o_mma(u - 1);
        if (u == 1) QSTAMP(5);
      }
      wg_wait<1>(); QSTAMP(11); o_out(2);
      sched_fence(key++);
      }
      wg_wait<0>(); QSTAMP(12); o_out(3);
      QSTAMP(13);
      asm volatile(ELECT "st.relaxed.gpu.global.u32 [%0], %1;\n}" :: "l"(&P.cnt[(32 + m2 * 2 + wg) * 32 + n2 * 4 + (warp & 3)]), "r"(gen) : "memory");
      bar_arrive(6, 288);
      if (OWNL) arrive_at(bars + B_OD * 8, t2 == 128);
      if ((t2 & 127) == 0) OSTAMP(8 + wg * 2);
      if (OCP) {
        sched_fence(key++);
        #pragma unroll
        for (int i = 0; i < 32; i++) asm volatile("lop3.b32 %0, %1, %2, 0, 0xf0 | 0xcc;" : "=r"(o[i >> 3][(i >> 2) & 1][i & 3]) : "r"(o[i >> 3][(i >> 2) & 1][i & 3]), "r"(P.one - 1));
      }
      if (OWNL && wg == 0) mbar_wait(bars + B_OD * 8, 0);
      mbar_wait(bars + (B_FULL2 + 1) * 8, 0);
      QSTAMP(14);
      wg_fence();
      #pragma unroll
      for (int i = 0; i < 8; i++) {
        const uint32_t f[4] = {o[i >> 1][0][i & 1], o[i >> 1][1][i & 1], o[i >> 1][0][2 + (i & 1)], o[i >> 1][1][2 + (i & 1)]};
        constexpr uint64_t dw = cdesc(SLOT, 16384, 2048, 1);
        if (i == 0) rs128z<1>(acc, f, dw); else rs128a<1>(acc, f, dw + (((i >> 1) * 4096 + (i & 1) * 1024) >> 4));
      }
      wg_commit();
      if ((t2 & 127) == 0) OSTAMP(37 + wg);
      const uint32_t ab = bars + B_FA * 8 + wg * 32;
      const int k2 = g2_k(2, n2);
      const bool doubt = NEAR == 2 || (uni(far) >> (k2 >> 1)) & 1;
      auto look = [&](int j) {
        if (doubt) {
          const uint32_t a = sb + (2 + j) * SLOT + wg * 8192 + (t2 & 96) * 32;
          if (__any_sync(0xffffffffu, lds32(a + (t2 & 16) * 256 + (t2 & 15) * 64 + (t2 & 30) * 2) == ~0u)) {
            const uint4* src = P.o + (m2 * 16 + k2 + j) * 1024 + wg * 512 + (t2 & 96) * 2 + (t2 & 31);
            if ((t2 & 31) == 0) OSTAMP(34);
            #pragma unroll 1
            for (int i = 0; i < 4; i++) {
              uint32_t v[4];
              int n = 0;
              do asm volatile("ld.relaxed.gpu.global.v4.u32 {%0,%1,%2,%3}, [%4];" : "=r"(v[0]), "=r"(v[1]), "=r"(v[2]), "=r"(v[3]) : "l"(src + (i & 1) * 32 + (i >> 1) * 256) : "memory");
              while (__any_sync(0xffffffffu, v[0] == ~0u) && ++n < 64);
              sts128(a + (t2 & 31) * 16 + (i & 1) * 512 + (i >> 1) * 4096, v[0], v[1], v[2], v[3]);
            }
            fence_async_smem();
            __syncwarp();
          }
        }
      };
      ring_step<true, true>(c, B_FULL2 + 2, 0, B_EMPTY2 + 1, c.lead, [&]() { look(0); if ((t2 & 127) == 0) OSTAMP(11 + wg * 24); g2_issue<1, 2>(acc, c); }, ab + 16, 0);
      ring_step<true, true>(c, B_FULL2 + 3, 0, B_EMPTY2 + 2, c.lead, [&]() { look(1); g2_issue<1, 3>(acc, c); }, ab + 24, 0);
    }
    gemm2(acc, IC<1>(), IC<SK3>(), []() {});
    if (tid == 0) OSTAMP(13);
    if (tid == 128) OSTAMP(14);
    {
      const uint32_t id2 = job(); IDS(id2);
      const int t2 = fresh_tid();
      const int row = ((t2 >> 5) & 3) * 16 + (t2 & 15);
      const int cq = (t2 >> 4) & 1, sw = t2 & 7;
      const uint32_t stg = sb + (EHI ? T_OFF : 0) + wg * 8192;
      constexpr uint32_t HS = EHI ? 16384 : SLOT;
      if (EHI) mbar_wait(bars + B_CD * 8, 0);
      #pragma unroll 1
      for (int pass = 0;; pass++) {
      const bool bad = acc[0] != acc[0] || acc[2] != acc[2];
      #pragma unroll
      for (int hf = 0; hf < 2; hf++) {
        #pragma unroll
        for (int jj = 0; jj < 4; jj++) {
          const int o = hf * 32 + jj * 8;
          stsm4(stg + hf * HS + row * 128 + (((2 * jj + cq) ^ sw) << 4),
                pack_bf16(acc[o], acc[o + 1]), pack_bf16(acc[o + 2], acc[o + 3]),
                pack_bf16(acc[o + 4], acc[o + 5]), pack_bf16(acc[o + 6], acc[o + 7]));
        }
        fence_async_smem();
        __syncwarp();
        if (!(AB & 1) && !((AB & 32) && wg == 0)) tma2d_store(&mOut, 1024 + n2 * 128 + hf * 64, m2 * 128 + warp * 16, sb + (EHI ? T_OFF : 0) + hf * HS + warp * 2048);
      }
      bulk_commit();
      uint32_t redo;
      asm volatile("{\n.reg .pred p, q;\nsetp.ne.b32 p, %1, 0;\nbar.red.or.pred q, %2, 128, p;\nselp.u32 %0, 1, 0, q;\n}" : "=r"(redo) : "r"((uint32_t)bad), "r"(1 + wg) : "memory");
      if (!uni(redo) || pass) break;
      if ((t2 & 127) == 0) OSTAMP(48 + wg);
      asm volatile("cp.async.bulk.wait_group 0;" ::: "memory");
      spin_until(&P.cnt[(16 + m2) * 32 + (t2 & 7)], lds32(sb + D_OFF + 40));
      fence_async_global();
      const uint32_t ab = bars + B_FA * 8 + wg * 32;
      #pragma unroll 1
      for (int k = 0; k < 16; k++) {
        bar_sync(1 + wg, 128);
        if ((warp & 3) == 0) {
          mbar_expect_tx(ab, 24576);
          bulk_load(sb + c.wofs, P.o + (m2 * 16 + k) * 1024 + wg * 512, 8192, ab);
          tma2d(sb + SLOT + c.wofs, &mWo, n2 * 128, k * 64, ab);
          tma2d(sb + 2 * SLOT + c.wofs, &mWo, n2 * 128 + 64, k * 64, ab);
        }
        mbar_wait(ab, ~k & 1);
        const uint64_t da = dofs(cdesc(0, 16, 512, 2), c.wofs), db = dofs(cdesc(SLOT, SLOT, 1024, 1), c.wofs);
        wg_fence();
        ss128p<0, 1>(acc, da, db, k);
        ss128a<0, 1>(acc, dofs(da, 32), dofs(db, 2048));
        ss128a<0, 1>(acc, dofs(da, 4096), dofs(db, 4096));
        ss128a<0, 1>(acc, dofs(da, 4128), dofs(db, 6144));
        wg_commit();
        wg_wait<0>(); pinv<64>(acc);
      }
      }
      bulk_wait_read();
    }
  } else if (warp < 12) {
    asm volatile("setmaxnreg.inc.sync.aligned.u32 %0;" :: "n"(160));
    const int ht = tid - 256, w = warp - 8;
    const int kap = w & 1;
    {
      uint32_t c4[4], s4[4];
      #pragma unroll
      for (int i = 0; i < 4; i++) {
        float c0, s0, c1, s1;
        unit_root<7>((32 * (ht & 3) + 8 * i + 1) * (ht >> 2), c0, s0);
        unit_root<7>((32 * (ht & 3) + 8 * i + 5) * (ht >> 2), c1, s1);
        c4[i] = pack_bf16(c0 * 0.125f, c1 * 0.125f); s4[i] = pack_bf16(s0 * 0.125f, s1 * 0.125f);
      }
      const uint32_t aa = sb + A_OFF + w * 2048 + (ht & 3) * 256 + ((ht >> 2) & 7) * 16;
      sts128(aa, c4[0], c4[1], c4[2], c4[3]);
      sts128(aa + 128, s4[0], s4[1], s4[2], s4[3]);
      sts128(aa + 1024, s4[0] ^ 0x80008000u, s4[1] ^ 0x80008000u, s4[2] ^ 0x80008000u, s4[3] ^ 0x80008000u);
      sts128(aa + 1024 + 128, c4[0], c4[1], c4[2], c4[3]);
      float c0, s0, c1, s1;
      unit_root<4>((ht >> 3) * (2 * (ht & 7)), c0, s0);
      unit_root<4>((ht >> 3) * (2 * (ht & 7) + 1), c1, s1);
      const uint32_t fa = sb + F_OFF + (ht >> 6) * 512 + ((ht >> 2) & 1) * 256 + ((ht >> 3) & 7) * 16 + (ht & 3) * 4;
      const uint32_t cc = pack_bf16(c0, c1), ss = pack_bf16(s0, s1);
      sts32(fa, cc); sts32(fa + 128, ss ^ 0x80008000u); sts32(fa + 1024, ss); sts32(fa + 1024 + 128, cc);
    }
    cluster_wait();
    mbar_wait(bars + B_EX * 8, 0);
    const uint32_t id2 = job(); IDS(id2);
    if (id2 != ids) bar_sync(8, 160);
    const uint4 sw = *reinterpret_cast<const uint4*>(P.shift + (cp * 16 + kap * 8 + 2 * (lane & 3)) * 4);
    const float dv = __bfloat162float(P.ssmD[cp * 16 + rank * 8 + (ht & 7)]) * 0.125f;
    Tw tw;
    make_tw(tw, ht);
    D2 cd[9];
    {
      const uint64_t v = P.cd[min(lane, 17)];
      #pragma unroll
      for (int i = 0; i < 9; i++) { cd[i].a = __shfl_sync(0xffffffffu, v, 2 * i); cd[i].b = __shfl_sync(0xffffffffu, v, 2 * i + 1); }
    }
    const D2 &dF = cd[0], *dT = cd + 1, *dH = cd + 5;
    D2* dX = cd + 7;
#define CFENCE(n) sched_fence<n>((uint32_t)dF.a)
    if (ht < 8) sts32(sb + D_OFF + ht * 4, __float_as_uint(dv));
    const uint32_t w0 = __byte_perm(sw.x, sw.z, 0x5410), w1 = __byte_perm(sw.x, sw.z, 0x7632);
    const uint32_t w2 = __byte_perm(sw.y, sw.w, 0x5410), w3 = __byte_perm(sw.y, sw.w, 0x7632);
    const uint32_t psb = uni(mapa(sb, rank ^ 1));
    if (ht == 0) OSTAMP(20);
    {
      const int m = lane >> 3, n1 = (w >> 1) * 8 + (lane & 7);
      const int rk = 17 * m + n1 + 1, rh = 17 * (12 + m) + n1, rv = 16 * m + n1;
      const uint32_t ka = rk * 32 + ((kap ^ (rk >> 2)) & 1) * 16, ha = rh * 32 + ((kap ^ (rh >> 2)) & 1) * 16;
      const uint32_t va = rv * 32 + ((kap ^ (rv >> 2)) & 1) * 16;
      const uint32_t po = sb + T_OFF + (w >> 1) * 2176;
      #pragma unroll 1
      for (int rd = 0; rd < 4; rd++) {
        const uint32_t kb = sb + M_OFF + (rd & 1) * KB, vb = sb + M_OFF + 2 * KB + (rd & 1) * 8192;
        const uint32_t xo = X_OFF + ((rd & 1) * 2 + (w >> 1)) * 1024 + (2 * rank + (rd >> 1)) * 256;
        const uint32_t xa = (kap == rank ? sb + xo + (lane & 7) * XS : po + (lane & 7) * 272) + m * 16;
        mbar_wait(bars + (B_STG + (rd & 1) * 2) * 8, rd >> 1);
        uint32_t kk[20], vv[16];
        const uint32_t zero = P.one - 1;
        ldsm4(kk, kb + ha);
        ldsm4(kk + 4, kb + ka);
        #pragma unroll
        for (int i = 0; i < 16; i++) {
          if ((i & 3) == 0 && i < 12) ldsm4(kk + 8 + i, kb + (ka ^ ((~i & 4) * 4)) + (i + 4) * 544 + (kk[i + 4] & zero));
          uint32_t t = bmul2(kk[i + 1], w3);
          t = badd2(t, bmul2(kk[i + 2], w2));
          t = badd2(t, bmul2(kk[i + 3], w1));
          kk[i] = badd2(t, bmul2(kk[i + 4], w0));
          asm volatile("" : "+r"(kk[i]));
        }
        mbar_wait(bars + (B_STG + (rd & 1) * 2 + 1) * 8, rd >> 1);
        ldsm4(vv, vb + va);
        #pragma unroll
        for (int i = 0; i < 16; i += 4) {
          if (i < 12) ldsm4(vv + 4 + i, vb + va + (i + 4) * 512 + (i == 4 ? vv[0] & zero : 0));
          stsm4t(xa + (i >> 2) * 64, bmul2(kk[i], vv[i]), bmul2(kk[i + 1], vv[i + 1]), bmul2(kk[i + 2], vv[i + 2]), bmul2(kk[i + 3], vv[i + 3]));
        }
        if (rd < 2) {
          fence_async_smem();
          __syncwarp();
          mbar_arrive(bars + (B_SFREE + (rd & 1)) * 8);
        }
        __syncwarp();
        if (kap != rank) {
          #pragma unroll
          for (int i = 0; i < 4; i++) lds128(vv + 4 * i, po + (2 * i + (lane >> 4)) * 272 + (lane & 15) * 16);
          #pragma unroll
          for (int i = 0; i < 4; i++)
            st_async128(psb + xo + (2 * i + (lane >> 4)) * XS + (lane & 15) * 16, psb + BAR_OFF + B_X * 8, vv[4 * i], vv[4 * i + 1], vv[4 * i + 2], vv[4 * i + 3]);
          __syncwarp();
        }
      }
    }
    bar_sync(3, 128);
    if (w == 0) mbar_expect_tx(bars + B_X * 8, 16384);
    {
      constexpr int NC = 8;
      Tmp t; t.t0 = 0.f; t.t1 = 0.f;
      asm volatile("setp.ne.b32 p_one, %0, 0;" :: "r"(lds32(sb + F_OFF)));
      float ra[32], lo[32], hi[32];
      uint32_t fa[2][2][4], fb[2][2][4];
      const uint32_t ta = sb + T_OFF + w * 2048 + lane * 16;
      const uint32_t y0 = rank ? psb : sb, y1 = rank ? sb : psb;
      auto fin = [&](int ch) {
        if (ch > 0) mbar_wait(bars + (B_YR + ch - 1) * 8, 0);
        finish(t, ra, ch, ht, rank, y0, y1);
      };
      auto load_h = [&](int i) {
        mbar_expect_tx(bars + B_H * 8, 4096);
        tma2d(sb + H_OFF, &mH, 0, (cp * 16 + rank * 8 + i) * 128, bars + B_H * 8);
      };
      auto skip = [&](int i) {
        const float dn = __uint_as_float(lds32(sb + D_OFF + i * 4));
        return dn;
      };
      mbar_wait(bars + B_H * 8, 0);
      wg_fence();
      dft32_h(lo, dH);
      mbar_wait(bars + B_X * 8, 0);
      fence_async_smem();
      if (ht == 0) OSTAMP(21);
      wg_fence();
      dft32_x(hi, dX);
      float dn = skip(0);
      wg_wait<1>(); pinv<32>(lo);
      if (w == 0) load_h(1);
      pack_fwd(fa, lo); CFENCE(0); rot_fwd(fa, tw); CFENCE(1);
      wg_wait<0>(); pinv<32>(hi);
      pack_fwd(fb, hi); CFENCE(2); rot_fwd(fb, tw); CFENCE(3);
      wg_fence();
      dft16h(hi, fb[1], dF); dft16h(hi + 16, fa[1], dF); dft16h(lo, fb[0], dF); dft16h(lo + 16, fa[0], dF);
      wg_commit();
      wg_wait<0>(); pinv<32>(lo); pinv<32>(hi);
#define CSTAMP(n) do {} while (0)
      #pragma unroll 1
      for (int i = 0;; i++) {
        CSTAMP(0);
        add_skip(lo + 16, dn);
        prod<1, 0, FG>(t, fa[1], lo, hi);
        CFENCE(4);
        CSTAMP(1);
        fence_async_smem();
        bar_sync(3, 128);
        CSTAMP(2);
        float rg[32];
        if (DRY) idft32(rg, dT); else { wg_fence(); ss64x4(rg, dT, i); }
        CFENCE(5);
        CSTAMP(3);
        const uint32_t yr = bars + (i < 2 ? B_X : B_YR + i - 2) * 8;
        const uint32_t oky = mbar_try(yr, 0);
        dn = skip(i + 1);
        prod<1, FG, 8>(t, fa[1], lo, hi);
        pinv<32>(lo);
        if (!oky) mbar_wait(yr, 0);
        CSTAMP(4);
        wg_wait<0>(); pinv<32>(rg);
        if (i > 0) finish(t, rg, i - 1, ht, rank, y0, y1);
        if (i == NC - 1) break;
        CSTAMP(5);
        wg_fence();
        dft32_x<false>(hi, dX);
        if (HINT & 1) { asm volatile("@!p_one mov.b32 %0, %1;" : "+f"(t.t1) : "f"(rg[0])); if (SF & 16) CFENCE(6); wg_fence(); }
        dft16h(ra + 16, fa[1], dF);
        wg_commit();
        CFENCE(7);
        CSTAMP(6);
        const uint32_t okh = mbar_try(bars + B_H * 8, (i + 1) & 1);
        prod<0>(t, fa[0], lo, lo);
        if ((AB & 128) && i == 4) mbar_wait(bars + B_GO * 8, 0);
        if (!okh) mbar_wait(bars + B_H * 8, (i + 1) & 1);
        CSTAMP(7);
        wg_fence();
        dft32_h<false>(lo, dH);
        if (HINT & 2) { asm volatile("@!p_one mov.b32 %0, %1;" : "+f"(t.t0) : "f"(rg[31])); if (SF & 8) CFENCE(8); wg_fence(); }
        dft16h(ra, fa[0], dF);
        wg_commit();
        wg_wait<1>(); pinv<32>(hi);
        if (ht == 64) OSTAMP(22 + i);
        CSTAMP(8);
        pack_fwd(fb, hi); CFENCE(9); rot_fwd(fb, tw); CFENCE(10);
        CSTAMP(9);
        wg_wait<0>(); pinv<32>(lo); pinv<32>(ra);
        CSTAMP(10);
        if (w == HW && i < NC - 2) load_h(i + 2);
        pack_fwd(fa, lo);
        if (SF & 32) CFENCE(11);
        wg_fence();
        dft16h(hi, fb[1], dF); dft16h(lo, fb[0], dF);
        wg_commit();
        CFENCE(12);
        rot_fwd(fa, tw);
        uint32_t u[2][2][4];
        if (CX) { CFENCE(13); pack_inv(u, ra); }
        if (SF & 64) CFENCE(14);
        CSTAMP(11);
        wg_fence();
        dft16h(hi + 16, fa[1], dF); dft16h(lo + 16, fa[0], dF);
        wg_commit();
        CFENCE(15);
        CSTAMP(12);
        if (!CX) { pack_inv(u, ra); CFENCE(13); }
        rot_inv(u, tw, ta);
        CSTAMP(13);
        if (SF & 1) CFENCE(16);
        wg_wait<0>(); pinv<32>(lo); pinv<32>(hi);
        CSTAMP(14);
      }
      wg_fence();
      dft16h(hi + 16, fa[1], dF);
      wg_commit();
      CFENCE(17);
      prod<0>(t, fa[0], lo, lo);
      CFENCE(18);
      wg_fence();
      dft16h(hi, fa[0], dF);
      wg_commit();
      if (ht == 64) OSTAMP(29);
      wg_wait<0>(); pinv<32>(hi);
      pack_inv(fb, hi); CFENCE(19); rot_inv(fb, tw, ta);
      fence_async_smem();
      bar_sync(3, 128);
      idft32(ra, dT);
      const int l3 = fresh_tid() & 31;
      uint32_t qa = sb + M_OFF + ((l3 >> 4) * 512 + w * 128 + (l3 & 8) + ((l3 >> 2) & 1) + (l3 & 2)) * 32 + (l3 & 1) * 16;
      uint32_t yb = sb + X_OFF + (l3 & 1) * (XS + 16) + w * 512
                    + (((l3 >> 1) & 1) == rank ? (l3 >> 2) * 16 : YX - XS + ((l3 >> 2) ^ 4) * 16);
      mbar_wait(bars + B_Q * 8, 0);
      wg_wait<0>(); pinv<32>(ra);
      fin(NC - 1);
      if (ht == 64) OSTAMP(30);
      uint32_t t0 = 0, dt = 0;
      #pragma unroll 1
      for (int sg = 0; sg < 4; sg++, qa += 1024, yb += 128) {
        uint32_t qv[4][4], yv[4][4];
        #pragma unroll
        for (int i = 0; i < 4; i++) lds128(qv[i], qa + (i >> 1) * 512 + (i & 1) * 128);
        #pragma unroll
        for (int m = 0; m < 4; m++) {
          if (m == 3 && sg == 0) mbar_wait(bars + (B_YR + NC - 1) * 8, 0);
          ldsm4t(yv[m], yb + 2 * m * XS);
        }
        #pragma unroll
        for (int i = 0; i < 4; i++)
          sts128(qa + (i >> 1) * 512 + (i & 1) * 128, bmul2(qv[i][0], yv[0][i]), bmul2(qv[i][1], yv[1][i]), bmul2(qv[i][2], yv[2][i]), bmul2(qv[i][3], yv[3][i]));
        if (sg == 3) mbar_arrive(bars + B_CD * 8);
        fence_async_smem();
        __syncwarp();
        if (sg == 0) {
          mbar_wait(bars + B_GO * 8, 0);
          t0 = uni((uint32_t)clock());
          dt = uni(min(max((int)(lds32(sb + D_OFF + 44) + OA_END - t0) >> 2, 4 * OA_MIN), 4 * OA_MAX));
          t0 += w * (dt >> 2);
        }
        pace(t0, dt);
        #pragma unroll
        for (int hf = 0; hf < 2; hf++) {
          const int r = w * 128 + sg * 32 + hf * 512;
          if (!(AB & 2)) tma2d_store(&mOutA, cp * 16, rank * 1024 + r, sb + M_OFF + r * 32);
        }
      }
      bulk_commit(); bulk_wait_read();
      if (ht == 0) OSTAMP(31);
    }
  } else {
    asm volatile("setmaxnreg.dec.sync.aligned.u32 %0;" :: "n"(32));
    const uint32_t t_pf = (uint32_t)clock();
    uint32_t taken = 0;
    if (ATW == 0 && tid + (ids & 1) * 512 == 416) taken = atomicExch(P.cnt + 64 * 32 + ids * 4, 1u);
    if (warp >= 14) {
      const uint32_t id2 = fresh(ids); IDS(id2);
      if (warp == 14) {
        asm volatile("prefetch.global.L2 [%0];" :: "l"(((lane & 1) ? P.v : P.k) + (rank * 2097152 + cp * 32 + (lane >> 1) * 131072)));
      } else {
        uint32_t t0 = t_pf + id2 * 2;
        #pragma unroll 1
        for (int i = 0; i < PF_N; i++) {
          const int u = P.pf[i];
          const PfType& f = P.pt[u >> 4];
          pace(t0, i == 0 ? PF_DT0 : (i < PF_N1 ? PF_DT1 : PF_DT2));
          asm volatile("prefetch.global.L2 [%0];" :: "l"(f.base + ((g & 3) * f.gl + (g >> 2) * f.gh + mb * f.sp + rank * f.sr + (u & 15) * f.su
                                                                   + (lane >> 2) * f.l4 + ((lane >> 1) & 1) * f.l2 + (lane & 1) * 128)));
        }
      }
    }
    cluster_wait();
    if (warp == 13) {
      unsigned* const asked = P.cnt + 80 * 32;
      uint32_t j = ids;
      if (ATW == 2) mbar_wait(bars + B_F0 * 8, 0);
      if (ATW && lane + (ids & 1) == 0) taken = atomicExch(P.cnt + 64 * 32 + ids * 4, 1u);
      taken = uni(taken);
      if (taken) {
        fence_gpu();
        unsigned n = 0;
        if (lane == 0) n = atomicAdd(asked, 1u);
        spin_until(asked, (uni(n) | 63) + 1);
        #pragma unroll 1
        for (j = 0; j < 126; j += 2) {
          if (lane == 0) n = atomicExch(P.cnt + 64 * 32 + j * 4, 1u);
          if (!uni(n)) break;
        }
        if (lane == 0) P.cnt[64 * 32 + j * 4] = 1;
        j |= 128;
      }
      asm volatile("{\n.reg .pred p;\nsetp.lt.u32 p, %3, 2;\n@p st.async.weak.shared::cluster.mbarrier::complete_tx::bytes.b32 [%0], %2, [%1];\n}"
        :: "r"(mapa(sb + D_OFF + 52 + (j & 1) * 4, lane & 1)), "r"(mapa(bars + B_EX * 8, lane & 1)), "r"(j), "r"(lane) : "memory");
      if (!(j & 129)) { fence_gpu(); red_add(asked); }
    }
    if (warp == 12) {
      uint32_t xs = 0, idk = fresh(ids);
      auto load_x = [&](int k) {
        IDS(idk);
        tma2d_mc(sb + xs * SLOT + rank * 16384, &mX, k, mb * 256 + rank * 128, bars + (B_XF + xs) * 8);
        mbar_expect_tx(bars + (B_XF + xs) * 8, SLOT);
        xs = xs == 2 ? 0 : xs + 1;
      };
      load_x(64); load_x(128);
      mbar_expect_tx(bars + B_Q * 8, 32768);
      int look = 5;
      #pragma unroll 1
      for (int it = 1; it < 8; it++) {
        #pragma unroll
        for (int j = 0; j < 4; j++) {
          bool again = false;
          if (j == 3 && it == look) again = wrong_job();
          mbar_wait(bars + (B_EMPTY + j) * 8, (it - 1) & 1);
          TSTAMP(1, 4 * it + j);
          tma3d(sb + W_OFF + j * 8192, &mW, (idk & 15) * 64, it * 128 + j * 32, 1, bars + (B_FULL + j) * 8);
          if (again) { it = look = -1; idk = job(); }
          if (j == 1 || (j == 3 && it < 7)) load_x(it * 128 + j * 32 + 32);
          mbar_expect_tx(bars + (B_FULL + j) * 8, 8192);
        }
      }
    }
    if (warp == 14) {
      uint32_t t0 = t_pf + STG_T0, idk = fresh(ids);
      #pragma unroll 1
      for (int pc = 0; pc < 16; pc++) {
        if (pc == 2) {
          mbar_wait(bars + B_EX * 8, 0);
          if (job() != idk) { mbar_wait(bars + B_STG * 8, 0); mbar_arrive(bars + B_STG * 8); bar_sync(8, 160); idk = job(); pc = 0; }
        }
        IDS(idk);
        const int rd = pc >> 2, u = pc & 3;
        const uint32_t gb = bars + (B_STG + (rd & 1) * 2 + (u >> 1)) * 8;
        if (pc == 8 || pc == 12) mbar_wait(bars + (B_SFREE + (rd & 1)) * 8, 0);
        if (!(u & 1)) mbar_expect_tx(gb, u ? 8192 : KB);
        pace(t0, STG_DT);
        TSTAMP(3, 16 + pc);
        tma3d(sb + M_OFF + (u < 2 ? (rd & 1) * KB + u * (KB / 2) : 2 * KB + (rd & 1) * 8192 + (u & 1) * 4096), u < 2 ? &mK : &mV,
              cp * 16, rank * 64 + rd * 16 - (u < 2), (u & 1) * 8, gb);
      }
      IDS(idk);
      mbar_expect_tx(bars + B_H * 8, 4096);
      tma2d(sb + H_OFF, &mH, 0, (cp * 16 + rank * 8) * 128, bars + B_H * 8);
    }
    mbar_wait(bars + B_EX * 8, 0);
    const uint32_t id2 = job(); IDS(id2);
    auto reduce_kv = [&](int i0, int i1) {
      float* kr = P.kv + hp * KV_PER_HP;
      mbar_wait(bars + B_Z * 8, 0);
      bar_sync(4, 352);
      #pragma unroll 1
      for (; i0 < i1; i0 += 2) {
        uint32_t p[2][4], q[2][4];
        const int i = (i0 + 2 * mb) & 15;
        const uint32_t pa = sb + M_OFF + (i & 3) * 2048 + (i >> 2) * 512 + (lane & 7) * 64 + (((lane >> 3) ^ (lane >> 1)) & 3) * 16;
        lds128(p[0], pa); lds128(q[0], pa + VT); lds128(p[1], pa + 2048); lds128(q[1], pa + VT + 2048);
        #pragma unroll
        for (int j = 0; j < 2; j++)
          asm volatile("red.relaxed.gpu.global.add.v4.f32 [%0], {%1,%2,%3,%4};" :: "l"(kr + (i >> 3) * 32 + (i + j) * 128 + lane * 4),
            "f"(__uint_as_float(p[j][0]) + __uint_as_float(q[j][0])), "f"(__uint_as_float(p[j][1]) + __uint_as_float(q[j][1])),
            "f"(__uint_as_float(p[j][2]) + __uint_as_float(q[j][2])), "f"(__uint_as_float(p[j][3]) + __uint_as_float(q[j][3])) : "memory");
      }
      if (i1 == 4) {
        const uint32_t za = sb + M_OFF + 8192 + lane * 4;
        #pragma unroll
        for (int h = 0; h < 2; h++)
          asm volatile("red.relaxed.gpu.global.add.f32 [%0], %1;" :: "l"(kr + h * 1056 + 1024 + lane),
            "f"(__uint_as_float(lds32(za + h * 128)) + __uint_as_float(lds32(za + h * 128 + VT))) : "memory");
      }
      bar_sync(5, 96);
    };
    auto convert_kv = [&](int u0, auto N_) {
      constexpr int N = N_.value;
      const float* kg = P.kv + (2 * n2 + rank) * KV_PER_HP;
      const uint32_t psb = uni(mapa(sb, rank ^ 1));
      auto put = [&](uint32_t o, uint32_t v0, uint32_t v1, uint32_t v2, uint32_t v3) {
        st_async128(psb + o, psb + BAR_OFF + B_KVB * 8, v0, v1, v2, v3);
        sts128(sb + o, v0, v1, v2, v3);
      };
      mbar_wait(bars + B_KVL * 8, 0);
      spin_until(&P.cnt[(2 * n2 + rank) * 32 + 1], uni(lds32(sb + D_OFF + 40)) * 8);
      float4 v[N][2];
      float z[2];
      #pragma unroll
      for (int j = 0; j < N; j++) {
        const float4* kr = reinterpret_cast<const float4*>(kg + ((u0 + j) >> 2) * 32 + (u0 + j) * 256) + lane;
        v[j][0] = __ldcg(kr); v[j][1] = __ldcg(kr + 32);
      }
      if (N == 2) { z[0] = __ldcg(kg + 1024 + lane); z[1] = __ldcg(kg + 2080 + lane); }
      #pragma unroll
      for (int j = 0; j < N; j++)
        put(KVB_OFF + (rank * 8 + u0 + j) * 640 + lane * 16,
            pack_bf16(v[j][0].x, v[j][0].y), pack_bf16(v[j][0].z, v[j][0].w), pack_bf16(v[j][1].x, v[j][1].y), pack_bf16(v[j][1].z, v[j][1].w));
      if (N == 2) {
        #pragma unroll
        for (int h = 0; h < 2; h++) {
          const uint32_t zz = pack_bf16(z[h], z[h]);
          put(KVB_OFF + (rank * 8 + h * 4 + (lane >> 3)) * 640 + 512 + (lane & 7) * 16, zz, zz, zz, zz);
        }
      }
      fence_async_smem();
      __syncwarp();
      mbar_arrive(bars + B_KVB * 8);
    };
    if (warp == 12) {
      #pragma unroll 1
      for (int it = 0; it < 4; it++) {
        #pragma unroll
        for (int j = 0; j < 4; j++) {
          const uint32_t fb = bars + (B_FULL2 + j) * 8;
          if (j || it) mbar_wait(bars + (it ? B_EMPTY2 + j : B_EMPTY + (j | 1)) * 8, (it - 1) & 1);
          TSTAMP(5, 4 * it + j);
          tma2d_mc(sb + j * SLOT + 16384 + rank * 8192, &mWq, n2 * 128 + rank * 64, it * 256 + j * 64, fb);
          tma2d(sb + j * SLOT, &mX, it * 256 + j * 64, m2 * 128, fb);
          mbar_expect_tx(fb, SLOT);
        }
      }
      int pc = 0;
      auto load_q = [&](int n) {
        #pragma unroll 1
        for (int i = 0; i < n; i++, pc++) tma2d(sb + M_OFF + pc * 4096, &mQ, cp * 16, rank * 1024 + pc * 128, bars + B_Q * 8);
      };
      mbar_wait(bars + B_MF * 8, 0);
      if (QW) mbar_wait(bars + (B_FULL2 + QW - 1) * 8, 1);
      load_q(QD >> 16);
      auto load_wo = [&](int st, uint32_t ph) {
        const uint32_t j = st & 3, fb = bars + (B_FULL2 + j) * 8, k = fresh(g2_k(st, n2) * 64);
        mbar_wait(bars + (B_EMPTY2 + j) * 8, ph);
        TSTAMP(5, 16 + st);
        tma2d_mc(sb + j * SLOT + 16384 + rank * 8192, &mWo, n2 * 128 + rank * 64, k, fb);
        mbar_expect_tx(fb, 16384);
      };
      load_wo(4, 1);
      load_q((QD >> 12) & 15);
      mbar_wait(bars + (B_EMPTY2 + 1) * 8, 1);
      asm volatile(ELECT "cp.async.bulk.tensor.5d.shared::cluster.global.mbarrier::complete_tx::bytes.multicast::cluster [%0], [%1, {%3, %4, %4, %4, %5}], [%2], %6;\n}"
        :: "r"(sb + SLOT + rank * 16384), "l"(&mWp), "r"(bars + (B_FULL2 + 1) * 8), "r"(n2 * 128 + rank * 64), "r"(0), "r"(n2 * 4), "h"((uint16_t)3) : "memory");
      mbar_expect_tx(bars + (B_FULL2 + 1) * 8, SLOT);
      load_q((QD >> 8) & 15);
      load_wo(2, 1);
      load_q((QD >> 4) & 15);
      load_wo(3, 1);
      mbar_arrive(bars + B_QE * 8);
      load_q(QD & 15);
      #pragma unroll 1
      for (int it = 1; it < 4; it++) {
        load_wo(4 * it + 1, (it - 1) & 1); load_wo(4 * it + 2, (it - 1) & 1); load_wo(4 * it + 3, (it - 1) & 1);
        if (it < 3) load_wo(4 * it + 4, (it - 1) & 1);
      }
    } else if (warp == 13) {
      if ((sb & 0xffffff) != SB0) __trap();
      float4* zp = reinterpret_cast<float4*>(P.kv + hp * KV_PER_HP + mb * 264);
      const float4 z4 = make_float4(0.f, 0.f, 0.f, 0.f);
      zp[lane] = z4; zp[lane + 32] = z4;
      if (lane < 2) zp[lane + 64] = z4;
      if (lane == 0) P.cnt[hp * 32 + 8 + mb] = t_pf;
      if (SPEC) {
        uint4* op = P.o + m2 * 16384 + mb * (SPEC * 256) + lane;
        uint32_t t0 = t_pf + RS_T0 + mb * (RS_DT / 8);
        #pragma unroll 1
        for (int i = 0; i < 8; i++) {
          while ((int)((uint32_t)clock() - t0) < 0) __nanosleep(100);
          t0 += RS_DT;
          #pragma unroll
          for (int j = 0; j < SPEC; j++) op[(i * SPEC + j) * 32] = make_uint4(~0u, ~0u, ~0u, ~0u);
        }
      }
      fence_gpu();
      __syncwarp();
      unsigned gen = 0;
      if (lane == 0) gen = (atomicAdd(&P.cnt[hp * 32], 1u) >> 3) + 1;
      gen = uni(gen);
      sts32(sb + D_OFF + 40, gen);
      spin_until(&P.cnt[hp * 32], gen * 8);
      sts32(sb + D_OFF + 48, __ballot_sync(0xffffffffu, NEAR && __ldcg(&P.cnt[hp * 32 + 8 + (lane & 7)]) - t_pf + 4096 >= 8192));
      mbar_arrive(bars + B_Z * 8);
      reduce_kv(0, 4);
      mbar_arrive(mapa(bars, rank ^ 1) + B_KVL * 8);
      mbar_arrive(bars + B_MF * 8);
      OSTAMP(17);
      fence_gpu();
      red_add(&P.cnt[hp * 32 + 1]);
      OSTAMP(15);
      convert_kv(0, IC<2>());
      bar_sync(6, 288);
      fence_gpu();
      asm volatile(ELECT "st.relaxed.gpu.global.u32 [%0], %1;\n}" :: "l"(&P.cnt[(16 + m2) * 32 + n2]), "r"(gen) : "memory");
      OSTAMP(32);
    } else {
      reduce_kv(warp * 6 - 80, warp * 6 - 74);
      convert_kv(warp * 3 - 40, IC<3>());
      {
        const int wg = 15 - warp;
        const unsigned gen = uni(lds32(sb + D_OFF + 40));
        const uint32_t ab = bars + B_FA * 8 + wg * 32, far = uni(lds32(sb + D_OFF + 48));
        const unsigned* fp = &P.cnt[SPEC ? (32 + m2 * 2 + wg) * 32 + lane : (16 + m2) * 32 + (lane >> 2)];
        uint32_t miss = ~0u, safe = t_pf;
        auto poll = [&]() {
          unsigned v;
          asm volatile("ld.relaxed.gpu.global.u32 %0, [%1];" : "=r"(v) : "l"(fp) : "memory");
          miss = __ballot_sync(0xffffffffu, v != gen);
        };
        mbar_arrive(ab + 8);
        mbar_wait(bars + B_QE * 8, 0);
        #pragma unroll 1
        for (int st = 2; st < 16; st += 2) {
          const int k = g2_k(st, n2), j = st & 3;
          const uint4* src = P.o + (m2 * 16 + k) * 1024 + wg * 512;
          const uint32_t eb = bars + (B_EMPTY2 + j) * 8, ph = ((st >> 2) - 1) & 1, dst = sb + j * SLOT + wg * 8192;
          if (!(AB & 4) && ((miss >> (2 * k)) & 15)) {
            #pragma unroll 1
            for (int n = 0; n < WAIT_BOUND && ((miss >> (2 * k)) & 15); n++) poll();
            if (!SPEC) asm volatile("fence.acquire.gpu;" ::: "memory");
            fence_async_global();
            safe = (uint32_t)clock() + FAR_DT;
          }
          if (st >= 4) {
            if ((far >> (k >> 1)) & 1) while ((int)(uni((uint32_t)clock()) - safe) < 0) {}
            mbar_wait(eb, j ? ph : ph ^ 1);
          }
          bulk_load(dst, src, 8192, ab + j * 8);
          mbar_expect_tx(ab + j * 8, 8192);
          if (st >= 4) mbar_wait(eb + 8, ph);
          bulk_load(dst + SLOT, src + 1024, 8192, ab + j * 8 + 8);
          mbar_expect_tx(ab + j * 8 + 8, 8192);
          if (st == 2) { OSTAMP(18 + wg * 15); if (wg) { sts32(sb + D_OFF + 44, (uint32_t)clock()); mbar_arrive(bars + B_GO * 8); } }
        }
        if (wg + rank + lane == 0) P.cnt[64 * 32 + id2 * 4] = 0;
      }
    }
  }
}

typedef CUresult (*EncodeFn)(CUtensorMap*, CUtensorMapDataType, cuuint32_t, void*, const cuuint64_t*, const cuuint64_t*,
                             const cuuint32_t*, const cuuint32_t*, CUtensorMapInterleave, CUtensorMapSwizzle,
                             CUtensorMapL2promotion, CUtensorMapFloatOOBfill);

void encode(EncodeFn fn, CUtensorMap* m, const void* ptr, int rank, const cuuint64_t* dims, const cuuint64_t* strides,
            const cuuint32_t* box, CUtensorMapSwizzle sw, CUtensorMapL2promotion pr) {
  const cuuint32_t es[5] = {1, 1, 1, 1, 1};
  fn(m, CU_TENSOR_MAP_DATA_TYPE_BFLOAT16, rank, const_cast<void*>(ptr), dims, strides, box, es,
     CU_TENSOR_MAP_INTERLEAVE_NONE, sw, pr, CU_TENSOR_MAP_FLOAT_OOB_FILL_NONE);
}

}

extern "C" void kernel_launch(void* const* d_in, const int* in_sizes, int n_in, void* d_out, int out_size) {
  (void)in_sizes; (void)n_in; (void)out_size;
  static EncodeFn fn = nullptr;
  static void *po, *pkv, *pcnt;
  if (!fn) {
    void* p = nullptr; cudaDriverEntryPointQueryResult qr;
    cudaGetDriverEntryPoint("cuTensorMapEncodeTiled", &p, cudaEnableDefault, &qr);
    fn = (EncodeFn)p;
    cudaGetSymbolAddress(&po, g_O); cudaGetSymbolAddress(&pkv, g_kv); cudaGetSymbolAddress(&pcnt, g_cnt);
    cudaFuncSetAttribute(fused_kernel, cudaFuncAttributeMaxDynamicSharedMemorySize, SMEM_BYTES);
  }
  const CUtensorMapL2promotion P128 = CU_TENSOR_MAP_L2_PROMOTION_L2_128B, P0 = CU_TENSOR_MAP_L2_PROMOTION_NONE;
  CUtensorMap mX, mW, mWq, mWo, mK, mV, mH, mQ, mOut, mOutA, mWp;
  { cuuint64_t d[2] = {1024, 2048}, s[1] = {2048}; cuuint32_t bx[2] = {64, 128}, bq[2] = {16, 128};
    encode(fn, &mX, d_in[6], 2, d, s, bx, CU_TENSOR_MAP_SWIZZLE_128B, P128);
    encode(fn, &mQ, d_in[0], 2, d, s, bq, CU_TENSOR_MAP_SWIZZLE_NONE, P128); }
  { cuuint64_t d[3] = {1024, 1024, 3}, s[2] = {6144, 2048}; cuuint32_t bx[3] = {64, 32, 2};
    encode(fn, &mW, d_in[7], 3, d, s, bx, CU_TENSOR_MAP_SWIZZLE_128B, P128); }
  { cuuint64_t d[2] = {1024, 1024}, s[1] = {6144}, so[1] = {2048}; cuuint32_t bx[2] = {64, 64};
    encode(fn, &mWq, d_in[7], 2, d, s, bx, CU_TENSOR_MAP_SWIZZLE_128B, P128);
    encode(fn, &mWo, d_in[8], 2, d, so, bx, CU_TENSOR_MAP_SWIZZLE_128B, P128); }
  { cuuint64_t d[5] = {1024, 2, 4, 4, 32}, s[4] = {2048, 16384, 4096, 65536}; cuuint32_t bx[5] = {64, 2, 4, 4, 4};
    encode(fn, &mWp, d_in[8], 5, d, s, bx, CU_TENSOR_MAP_SWIZZLE_128B, P128); }
  { cuuint64_t d[3] = {1024, 128, 16}, s[2] = {32768, 2048}; cuuint32_t bk[3] = {16, 17, 8}, bv[3] = {16, 16, 8};
    encode(fn, &mK, d_in[1], 3, d, s, bk, CU_TENSOR_MAP_SWIZZLE_32B, P128);
    encode(fn, &mV, d_in[2], 3, d, s, bv, CU_TENSOR_MAP_SWIZZLE_32B, P128); }
  { cuuint64_t d[2] = {16, 131072}, s[1] = {32}; cuuint32_t bx[2] = {16, 128};
    encode(fn, &mH, d_in[4], 2, d, s, bx, CU_TENSOR_MAP_SWIZZLE_32B, CU_TENSOR_MAP_L2_PROMOTION_L2_256B); }
  { cuuint64_t d[2] = {2048, 2048}, s[1] = {4096}; cuuint32_t bx[2] = {64, 16}, ba[2] = {16, 32};
    encode(fn, &mOut, d_out, 2, d, s, bx, CU_TENSOR_MAP_SWIZZLE_128B, P0);
    encode(fn, &mOutA, d_out, 2, d, s, ba, CU_TENSOR_MAP_SWIZZLE_NONE, P0); }
  Params P;
  P.shift = (const __nv_bfloat16*)d_in[3]; P.ssmD = (const __nv_bfloat16*)d_in[5];
  P.x = (const __nv_bfloat16*)d_in[6]; P.w = (const __nv_bfloat16*)d_in[7]; P.out = (__nv_bfloat16*)d_out; P.one = 1;
  P.o = (uint4*)po; P.kv = (float*)pkv; P.cnt = (unsigned*)pcnt;
  P.k = (const char*)d_in[1]; P.v = (const char*)d_in[2];
  P.pt[0] = {(const char*)d_in[6], 16 * 32768, 64 * 32768, 65536, 32768, 256, 4096, 2048};
  P.pt[1] = {(const char*)d_in[7] + 2048, 256, 1024, 16 * 6144, 8 * 6144, 128 * 6144, 6144, 2048};
  P.pt[2] = {(const char*)d_in[7], 512, 128 * 6144, 16 * 6144, 8 * 6144, 256 * 6144, 6144, 256};
  P.pt[3] = {(const char*)d_in[8], 512, 128 * 2048, 16 * 2048, 8 * 2048, 256 * 2048, 2048, 256};
  P.pt[4] = {(const char*)d_in[0], 256, 1024, 32768, 2097152, 262144, 4096, 2048};
  P.pt[5] = {(const char*)d_in[4], 16 * 32768, 64 * 32768, 65536, 32768, 4096, 512, 256};
  const uint8_t pf[32] = {PF_LIST};
  for (int i = 0; i < 32; i++) P.pf[i] = pf[i];
  const uint64_t cd[18] = {CONV_DESC};
  for (int i = 0; i < 18; i++) P.cd[i] = cd[i];
  fused_kernel<<<NCTA, NTHREADS, SMEM_BYTES, cudaStreamPerThread>>>(P, mX, mW, mWq, mWo, mK, mV, mH, mQ, mOut, mOutA, mWp);
}
```

```cpp
#include <cuda_runtime.h>
#include <cuda_bf16.h>
#include <cuda.h>
#include <stdint.h>

#define PARAM(name, value) constexpr int name = value
#define TUNE
namespace dflt {
PARAM(SK1, 2); PARAM(SK2, 3); PARAM(SK3, 2);
PARAM(MID, 3);
PARAM(STG_T0, 1300); PARAM(STG_DT, 540);
PARAM(RS_T0, 12000); PARAM(RS_DT, 600);
PARAM(FAR_DT, 500);
PARAM(OA_END, 7400); PARAM(OA_MIN, 200); PARAM(OA_MAX, 450);
PARAM(PF_DT0, 200); PARAM(PF_DT1, 1060); PARAM(PF_DT2, 512); PARAM(PF_N1, 9);
PARAM(TEST, 0);
PARAM(EHI, 0); PARAM(FG, 2); PARAM(CI, 1); PARAM(CW, 2);
}
#define PF_LIST 0x01, 0x11, 0x02, 0x12, 0x03, 0x13, 0x04, 0x14, 0x05, 0x15, 0x51, 0x06, 0x16, 0x20, 0x07, 0x17, 0x21, 0x22, 0x23, \
                0x40, 0x41, 0x42, 0x43, 0x44, 0x45, 0x46, 0x47, 0x30, 0x31, 0x32, 0x33
#define PF_N 31
#define WAIT_BOUND 262144

namespace {
using namespace dflt;
TUNE

constexpr int S_LEN = 2048;
constexpr int DM    = 1024;
constexpr int NCTA  = 128;
constexpr int NTHREADS = 512;
constexpr int SLOT  = 32768;
constexpr int W_OFF = 3 * SLOT;
constexpr int M_OFF = 4 * SLOT;
constexpr int VT    = 16 * 1152;
constexpr int T_OFF = M_OFF + 43008;
constexpr int XS    = 4096 + 16;
constexpr int YX    = 2048 + 16;
constexpr int X_OFF = T_OFF + 8192 + 2176;
constexpr int H_OFF = X_OFF + 8 * XS;
constexpr int A_OFF = H_OFF + 4096;
constexpr int F_OFF = A_OFF + 8192;
constexpr int BAR_OFF = F_OFF + 2048;
constexpr int D_OFF = BAR_OFF + 384;
constexpr int SMEM_BYTES = D_OFF + 64 + 256;
constexpr int KB = 8704;
constexpr int KVB_OFF = M_OFF + 32768;
static_assert(H_OFF % 256 == 0 && X_OFF % 128 == 0 && SMEM_BYTES <= 232448, "layout");
constexpr int B_XF = 0, B_F0 = 3, B_FULL = 4, B_FA = 4, B_FULL2 = 25, B_KVL = 24, B_STG = 8, B_X = 12, B_Z = 13, B_H = 14, B_Q = 15, B_YR = 16,
              B_SK = 29, B_GO = 30, B_QE = 31,
              B_EMPTY = 32, B_KVB = 36, B_EMPTY2 = 37, B_SFREE = 41, B_CD = 43, B_MF = 44, B_OD = 45, B_EX = 46;
constexpr int KV_PER_HP = 2 * 1056;

__device__ __align__(1024) uint4 g_O[S_LEN * DM / 8];
__device__ __align__(128) float g_kv[16 * KV_PER_HP];
__device__ __align__(128) unsigned g_cnt[81 * 32];

#define OSTAMP(i) do {} while (0)
#define TSTAMP(k, i) do {} while (0)

__device__ __forceinline__ uint32_t wanted_job() {
  uint32_t t;
  asm volatile("mov.u32 %0, %%smid;" : "=r"(t));
  if (TEST & 1) t = t * 3 % 100;
  t >>= 1;
  const uint32_t q = ((t - 32) * 37) >> 8;
  uint32_t r;
  asm("{\n.reg .pred p, q;\nsetp.lt.u32 p, %3, 32;\nsetp.lt.u32 q, %3, 62;\nselp.u32 %0, %1, %2, q;\nselp.u32 %0, %3, %0, p;\n}" : "=&r"(r) : "r"(t + 1 + q), "r"((t - 58) * 8), "r"(t));
  return (r & 7) | ((((r & 7 ? 0x76154032 : 0x76543012) >> ((r >> 1) & 28)) & 7) << 3);
}

#define ELECT "{\n.reg .pred e;\nelect.sync _|e, 0xffffffff;\n@e "
__device__ __forceinline__ uint32_t uni(uint32_t v) { return __shfl_sync(0xffffffffu, v, 0); }
__device__ __forceinline__ uint32_t fresh(uint32_t v) { asm volatile("" : "+r"(v)); return v; }
__device__ __forceinline__ uint32_t smem_u32(const void* p) { return (uint32_t)__cvta_generic_to_shared(p); }
__device__ __forceinline__ void mbar_init(uint32_t b, uint32_t c) { asm volatile(ELECT "mbarrier.init.shared::cta.b64 [%0], %1;\n}" :: "r"(b), "r"(c) : "memory"); }
__device__ __forceinline__ void mbar_expect_tx(uint32_t b, uint32_t bytes) { asm volatile(ELECT "mbarrier.arrive.expect_tx.shared::cta.b64 _, [%0], %1;\n}" :: "r"(b), "r"(bytes) : "memory"); }
__device__ __forceinline__ void mbar_arrive(uint32_t b) { asm volatile(ELECT "mbarrier.arrive.shared::cluster.b64 _, [%0];\n}" :: "r"(b) : "memory"); }
__device__ __forceinline__ void mbar_wait(uint32_t b, uint32_t ph) {
  asm volatile("{\n.reg .pred p;\nWAIT_LOOP:\nmbarrier.try_wait.parity.shared::cta.b64 p, [%0], %1;\n@!p bra.uni WAIT_LOOP;\n}" :: "r"(b), "r"(ph) : "memory");
}
__device__ __forceinline__ void tma2d(uint32_t dst, const CUtensorMap* m, int c0, int c1, uint32_t bar) {
  asm volatile(ELECT "cp.async.bulk.tensor.2d.shared::cluster.global.mbarrier::complete_tx::bytes [%0], [%1, {%3, %4}], [%2];\n}"
    :: "r"(dst), "l"(m), "r"(bar), "r"(c0), "r"(c1) : "memory"); }
__device__ __forceinline__ void tma2d_mc(uint32_t dst, const CUtensorMap* m, int c0, int c1, uint32_t bar) {
  asm volatile(ELECT "cp.async.bulk.tensor.2d.shared::cluster.global.mbarrier::complete_tx::bytes.multicast::cluster [%0], [%1, {%3, %4}], [%2], %5;\n}"
    :: "r"(dst), "l"(m), "r"(bar), "r"(c0), "r"(c1), "h"((uint16_t)3) : "memory"); }
__device__ __forceinline__ void tma3d(uint32_t dst, const CUtensorMap* m, int c0, int c1, int c2, uint32_t bar) {
  asm volatile(ELECT "cp.async.bulk.tensor.3d.shared::cluster.global.mbarrier::complete_tx::bytes [%0], [%1, {%3, %4, %5}], [%2];\n}"
    :: "r"(dst), "l"(m), "r"(bar), "r"(c0), "r"(c1), "r"(c2) : "memory"); }
__device__ __forceinline__ void tma2d_store(const CUtensorMap* m, int c0, int c1, uint32_t src) {
  asm volatile(ELECT "cp.async.bulk.tensor.2d.global.shared::cta.bulk_group [%0, {%2, %3}], [%1];\n}"
    :: "l"(m), "r"(src), "r"(c0), "r"(c1) : "memory"); }
__device__ __forceinline__ void bulk_load(uint32_t dst, const void* src, uint32_t bytes, uint32_t bar) {
  asm volatile(ELECT "cp.async.bulk.shared::cluster.global.mbarrier::complete_tx::bytes [%0], [%1], %2, [%3];\n}"
    :: "r"(dst), "l"(src), "r"(bytes), "r"(bar) : "memory"); }
__device__ __forceinline__ void bulk_commit() { asm volatile("cp.async.bulk.commit_group;" ::: "memory"); }
__device__ __forceinline__ void bulk_wait_read() { asm volatile("cp.async.bulk.wait_group.read 0;" ::: "memory"); }
__device__ __forceinline__ void fence_async_smem() { asm volatile("fence.proxy.async.shared::cta;" ::: "memory"); }
__device__ __forceinline__ void bar_sync(int id, int n) { asm volatile("bar.sync %0, %1;" :: "r"(id), "r"(n) : "memory"); }
__device__ __forceinline__ void bar_arrive(int id, int n) { asm volatile("bar.arrive %0, %1;" :: "r"(id), "r"(n) : "memory"); }
__device__ __forceinline__ void wg_fence() { asm volatile("wgmma.fence.sync.aligned;" ::: "memory"); }
__device__ __forceinline__ void wg_commit() { asm volatile("wgmma.commit_group.sync.aligned;" ::: "memory"); }
template <int N> __device__ __forceinline__ void wg_wait() { asm volatile("wgmma.wait_group.sync.aligned %0;" :: "n"(N) : "memory"); }
constexpr uint32_t SB0 = 1024;
__host__ __device__ constexpr uint64_t cdesc(uint32_t off, uint32_t lbo, uint32_t sbo, uint32_t swz) {
  return (uint64_t)((SB0 + off) >> 4) | ((uint64_t)(lbo >> 4) << 16) | ((uint64_t)(sbo >> 4) << 32) | ((uint64_t)swz << 62); }
__device__ __forceinline__ uint64_t dofs(uint64_t d, uint32_t bytes) { return (d & 0xffffffff00000000ull) | (uint32_t)((uint32_t)d + (bytes >> 4)); }
__device__ __forceinline__ uint32_t mbar_try(uint32_t b, uint32_t ph) {
  uint32_t ok;
  asm volatile("{\n.reg .pred p;\nmbarrier.test_wait.parity.shared::cta.b64 p, [%1], %2;\nselp.u32 %0, 1, 0, p;\n}" : "=r"(ok) : "r"(b), "r"(ph) : "memory");
  return ok; }
__device__ __forceinline__ void arrive_at(uint32_t a, uint32_t on) {
  asm volatile("{\n.reg .pred p;\nsetp.ne.b32 p, %1, 0;\n@p mbarrier.arrive.shared::cluster.b64 _, [%0];\n}" :: "r"(a), "r"(on) : "memory"); }
__device__ __forceinline__ void ldsm4(uint32_t* r, uint32_t a) {
  asm volatile("ldmatrix.sync.aligned.m8n8.x4.shared.b16 {%0,%1,%2,%3}, [%4];" : "=r"(r[0]), "=r"(r[1]), "=r"(r[2]), "=r"(r[3]) : "r"(a) : "memory"); }
__device__ __forceinline__ void ldsm4t(uint32_t* r, uint32_t a) {
  asm volatile("ldmatrix.sync.aligned.m8n8.x4.trans.shared.b16 {%0,%1,%2,%3}, [%4];" : "=r"(r[0]), "=r"(r[1]), "=r"(r[2]), "=r"(r[3]) : "r"(a) : "memory"); }
__device__ __forceinline__ void stsm4(uint32_t a, uint32_t r0, uint32_t r1, uint32_t r2, uint32_t r3) {
  asm volatile("stmatrix.sync.aligned.m8n8.x4.shared.b16 [%0], {%1,%2,%3,%4};" :: "r"(a), "r"(r0), "r"(r1), "r"(r2), "r"(r3) : "memory"); }
__device__ __forceinline__ void stsm4t(uint32_t a, uint32_t r0, uint32_t r1, uint32_t r2, uint32_t r3) {
  asm volatile("stmatrix.sync.aligned.m8n8.x4.trans.shared.b16 [%0], {%1,%2,%3,%4};" :: "r"(a), "r"(r0), "r"(r1), "r"(r2), "r"(r3) : "memory"); }
__device__ __forceinline__ uint32_t lds32(uint32_t a) { uint32_t v; asm volatile("ld.shared.b32 %0, [%1];" : "=r"(v) : "r"(a) : "memory"); return v; }
__device__ __forceinline__ void lds128(uint32_t* v, uint32_t a) { asm volatile("ld.shared.v4.b32 {%0,%1,%2,%3}, [%4];" : "=r"(v[0]), "=r"(v[1]), "=r"(v[2]), "=r"(v[3]) : "r"(a) : "memory"); }
__device__ __forceinline__ void sts32(uint32_t a, uint32_t v) { asm volatile("st.shared.b32 [%0], %1;" :: "r"(a), "r"(v) : "memory"); }
__device__ __forceinline__ void sts128(uint32_t a, uint32_t v0, uint32_t v1, uint32_t v2, uint32_t v3) {
  asm volatile("st.shared.v4.b32 [%0], {%1,%2,%3,%4};" :: "r"(a), "r"(v0), "r"(v1), "r"(v2), "r"(v3) : "memory"); }
__device__ __forceinline__ uint32_t pack_bf16(float lo, float hi) { uint32_t r; asm("cvt.rn.bf16x2.f32 %0, %1, %2;" : "=r"(r) : "f"(hi), "f"(lo)); return r; }
template <int ID = 0> __device__ __forceinline__ void sched_fence(uint32_t key) {
  asm volatile("{\n.reg .pred p;\nsetp.eq.u32 p, %0, %1;\nSF_LOOP:\n@p pmevent 1;\n@p bra.uni SF_LOOP;\n}" :: "r"(key), "n"(ID) : "memory");
}
template <int N> __device__ __forceinline__ void pinv(float* v) {
  #pragma unroll
  for (int i = 0; i < N; i++) asm volatile("" : "+f"(v[i]) :: "memory"); }
__device__ __forceinline__ uint32_t bmul2(uint32_t a, uint32_t b) { uint32_t r; asm("mul.rn.bf16x2 %0, %1, %2;" : "=r"(r) : "r"(a), "r"(b)); return r; }
__device__ __forceinline__ uint32_t badd2(uint32_t a, uint32_t b) { uint32_t r; asm("add.rn.bf16x2 %0, %1, %2;" : "=r"(r) : "r"(a), "r"(b)); return r; }
__device__ __forceinline__ void spin_until(const unsigned* p, unsigned target) {
  int n = 0;
  unsigned v;
  do { asm volatile("ld.relaxed.gpu.global.u32 %0, [%1];" : "=r"(v) : "l"(p) : "memory"); } while ((int)(v - target) < 0 && ++n < WAIT_BOUND);
  asm volatile("fence.acquire.gpu;" ::: "memory");
}
__device__ __forceinline__ void cluster_wait() { asm volatile("barrier.cluster.wait.aligned;" ::: "memory"); }
__device__ __forceinline__ void fence_gpu() { asm volatile("fence.release.gpu;" ::: "memory"); }
__device__ __forceinline__ void fence_async_global() { asm volatile("fence.proxy.async.global;" ::: "memory"); }
__device__ __forceinline__ void red_add(unsigned* p) { asm volatile(ELECT "red.relaxed.gpu.global.add.u32 [%0], 1;\n}" :: "l"(p) : "memory"); }
__device__ __forceinline__ float rcp_fast(float x) { float r; asm("rcp.approx.ftz.f32 %0, %1;" : "=f"(r) : "f"(x)); return r; }
__device__ __forceinline__ uint32_t mapa(uint32_t a, uint32_t rank) { uint32_t r; asm("mapa.shared::cluster.u32 %0, %1, %2;" : "=r"(r) : "r"(a), "r"(rank)); return r; }
__device__ __forceinline__ void st_async128(uint32_t a, uint32_t bar, uint32_t v0, uint32_t v1, uint32_t v2, uint32_t v3) {
  asm volatile("st.async.weak.shared::cluster.mbarrier::complete_tx::bytes.v4.b32 [%0], {%2,%3,%4,%5}, [%1];"
    :: "r"(a), "r"(bar), "r"(v0), "r"(v1), "r"(v2), "r"(v3) : "memory"); }
__device__ __forceinline__ int fresh_tid() { int t; asm volatile("mov.u32 %0, %%tid.x;" : "=r"(t)); return t; }
__device__ __forceinline__ void pace(uint32_t& t, uint32_t dt) {
  uint32_t c;
  while ((int)((c = uni((uint32_t)clock())) - t) < 0) __nanosleep(40);
  t = ((int)(c - t) > (int)dt ? c : t) + dt;
}
template <int LOG> __device__ __forceinline__ void unit_root(int a, float& c, float& s) {
  const float x = (float)((a << (32 - LOG)) >> (32 - LOG)) * (6.283185307179586f / (1 << LOG));
  c = __cosf(x); s = __sinf(x); }

struct D2 { uint64_t a, b; };
template <int TA, int TB> __device__ __forceinline__ void ss128p(float* d, uint64_t da, uint64_t db, int sd) {
  asm volatile("{\n.reg .pred p;\nsetp.ne.b32 p, %68, 0;\n"
    "wgmma.mma_async.sync.aligned.m64n128k16.f32.bf16.bf16 "
    "{%0, %1, %2, %3, %4, %5, %6, %7, %8, %9, %10, %11, %12, %13, %14, %15, "
    "%16, %17, %18, %19, %20, %21, %22, %23, %24, %25, %26, %27, %28, %29, %30, %31, "
    "%32, %33, %34, %35, %36, %37, %38, %39, %40, %41, %42, %43, %44, %45, %46, %47, "
    "%48, %49, %50, %51, %52, %53, %54, %55, %56, %57, %58, %59, %60, %61, %62, %63}, %64, %65, p, 1, 1, %66, %67;\n}\n"
    : "+f"(d[0]), "+f"(d[1]), "+f"(d[2]), "+f"(d[3]), "+f"(d[4]), "+f"(d[5]), "+f"(d[6]), "+f"(d[7]),
      "+f"(d[8]), "+f"(d[9]), "+f"(d[10]), "+f"(d[11]), "+f"(d[12]), "+f"(d[13]), "+f"(d[14]), "+f"(d[15]),
      "+f"(d[16]), "+f"(d[17]), "+f"(d[18]), "+f"(d[19]), "+f"(d[20]), "+f"(d[21]), "+f"(d[22]), "+f"(d[23]),
      "+f"(d[24]), "+f"(d[25]), "+f"(d[26]), "+f"(d[27]), "+f"(d[28]), "+f"(d[29]), "+f"(d[30]), "+f"(d[31]),
      "+f"(d[32]), "+f"(d[33]), "+f"(d[34]), "+f"(d[35]), "+f"(d[36]), "+f"(d[37]), "+f"(d[38]), "+f"(d[39]),
      "+f"(d[40]), "+f"(d[41]), "+f"(d[42]), "+f"(d[43]), "+f"(d[44]), "+f"(d[45]), "+f"(d[46]), "+f"(d[47]),
      "+f"(d[48]), "+f"(d[49]), "+f"(d[50]), "+f"(d[51]), "+f"(d[52]), "+f"(d[53]), "+f"(d[54]), "+f"(d[55]),
      "+f"(d[56]), "+f"(d[57]), "+f"(d[58]), "+f"(d[59]), "+f"(d[60]), "+f"(d[61]), "+f"(d[62]), "+f"(d[63])
    : "l"(da), "l"(db), "n"(TA), "n"(TB), "r"(sd));
}
template <int TA, int TB> __device__ __forceinline__ void ss128a(float* d, uint64_t da, uint64_t db) {
  asm volatile("{\n.reg .pred p;\nsetp.eq.b32 p, 0, 0;\n"
    "wgmma.mma_async.sync.aligned.m64n128k16.f32.bf16.bf16 "
    "{%0, %1, %2, %3, %4, %5, %6, %7, %8, %9, %10, %11, %12, %13, %14, %15, "
    "%16, %17, %18, %19, %20, %21, %22, %23, %24, %25, %26, %27, %28, %29, %30, %31, "
    "%32, %33, %34, %35, %36, %37, %38, %39, %40, %41, %42, %43, %44, %45, %46, %47, "
    "%48, %49, %50, %51, %52, %53, %54, %55, %56, %57, %58, %59, %60, %61, %62, %63}, %64, %65, p, 1, 1, %66, %67;\n}\n"
    : "+f"(d[0]), "+f"(d[1]), "+f"(d[2]), "+f"(d[3]), "+f"(d[4]), "+f"(d[5]), "+f"(d[6]), "+f"(d[7]),
      "+f"(d[8]), "+f"(d[9]), "+f"(d[10]), "+f"(d[11]), "+f"(d[12]), "+f"(d[13]), "+f"(d[14]), "+f"(d[15]),
      "+f"(d[16]), "+f"(d[17]), "+f"(d[18]), "+f"(d[19]), "+f"(d[20]), "+f"(d[21]), "+f"(d[22]), "+f"(d[23]),
      "+f"(d[24]), "+f"(d[25]), "+f"(d[26]), "+f"(d[27]), "+f"(d[28]), "+f"(d[29]), "+f"(d[30]), "+f"(d[31]),
      "+f"(d[32]), "+f"(d[33]), "+f"(d[34]), "+f"(d[35]), "+f"(d[36]), "+f"(d[37]), "+f"(d[38]), "+f"(d[39]),
      "+f"(d[40]), "+f"(d[41]), "+f"(d[42]), "+f"(d[43]), "+f"(d[44]), "+f"(d[45]), "+f"(d[46]), "+f"(d[47]),
      "+f"(d[48]), "+f"(d[49]), "+f"(d[50]), "+f"(d[51]), "+f"(d[52]), "+f"(d[53]), "+f"(d[54]), "+f"(d[55]),
      "+f"(d[56]), "+f"(d[57]), "+f"(d[58]), "+f"(d[59]), "+f"(d[60]), "+f"(d[61]), "+f"(d[62]), "+f"(d[63])
    : "l"(da), "l"(db), "n"(TA), "n"(TB));
}
template <int TA, int TB> __device__ __forceinline__ void ss128z(float* d, uint64_t da, uint64_t db) {
  asm volatile("{\n.reg .pred p;\nsetp.ne.b32 p, 0, 0;\n"
    "wgmma.mma_async.sync.aligned.m64n128k16.f32.bf16.bf16 "
    "{%0, %1, %2, %3, %4, %5, %6, %7, %8, %9, %10, %11, %12, %13, %14, %15, "
    "%16, %17, %18, %19, %20, %21, %22, %23, %24, %25, %26, %27, %28, %29, %30, %31, "
    "%32, %33, %34, %35, %36, %37, %38, %39, %40, %41, %42, %43, %44, %45, %46, %47, "
    "%48, %49, %50, %51, %52, %53, %54, %55, %56, %57, %58, %59, %60, %61, %62, %63}, %64, %65, p, 1, 1, %66, %67;\n}\n"
    : "=f"(d[0]), "=f"(d[1]), "=f"(d[2]), "=f"(d[3]), "=f"(d[4]), "=f"(d[5]), "=f"(d[6]), "=f"(d[7]),
      "=f"(d[8]), "=f"(d[9]), "=f"(d[10]), "=f"(d[11]), "=f"(d[12]), "=f"(d[13]), "=f"(d[14]), "=f"(d[15]),
      "=f"(d[16]), "=f"(d[17]), "=f"(d[18]), "=f"(d[19]), "=f"(d[20]), "=f"(d[21]), "=f"(d[22]), "=f"(d[23]),
      "=f"(d[24]), "=f"(d[25]), "=f"(d[26]), "=f"(d[27]), "=f"(d[28]), "=f"(d[29]), "=f"(d[30]), "=f"(d[31]),
      "=f"(d[32]), "=f"(d[33]), "=f"(d[34]), "=f"(d[35]), "=f"(d[36]), "=f"(d[37]), "=f"(d[38]), "=f"(d[39]),
      "=f"(d[40]), "=f"(d[41]), "=f"(d[42]), "=f"(d[43]), "=f"(d[44]), "=f"(d[45]), "=f"(d[46]), "=f"(d[47]),
      "=f"(d[48]), "=f"(d[49]), "=f"(d[50]), "=f"(d[51]), "=f"(d[52]), "=f"(d[53]), "=f"(d[54]), "=f"(d[55]),
      "=f"(d[56]), "=f"(d[57]), "=f"(d[58]), "=f"(d[59]), "=f"(d[60]), "=f"(d[61]), "=f"(d[62]), "=f"(d[63])
    : "l"(da), "l"(db), "n"(TA), "n"(TB));
}
template <int TA, int TB> __device__ __forceinline__ void ss64a(float* d, uint64_t da, uint64_t db) {
  asm volatile("{\n.reg .pred p;\nsetp.eq.b32 p, 0, 0;\n"
    "wgmma.mma_async.sync.aligned.m64n64k16.f32.bf16.bf16 "
    "{%0, %1, %2, %3, %4, %5, %6, %7, %8, %9, %10, %11, %12, %13, %14, %15, "
    "%16, %17, %18, %19, %20, %21, %22, %23, %24, %25, %26, %27, %28, %29, %30, %31}, %32, %33, p, 1, 1, %34, %35;\n}\n"
    : "+f"(d[0]), "+f"(d[1]), "+f"(d[2]), "+f"(d[3]), "+f"(d[4]), "+f"(d[5]), "+f"(d[6]), "+f"(d[7]),
      "+f"(d[8]), "+f"(d[9]), "+f"(d[10]), "+f"(d[11]), "+f"(d[12]), "+f"(d[13]), "+f"(d[14]), "+f"(d[15]),
      "+f"(d[16]), "+f"(d[17]), "+f"(d[18]), "+f"(d[19]), "+f"(d[20]), "+f"(d[21]), "+f"(d[22]), "+f"(d[23]),
      "+f"(d[24]), "+f"(d[25]), "+f"(d[26]), "+f"(d[27]), "+f"(d[28]), "+f"(d[29]), "+f"(d[30]), "+f"(d[31])
    : "l"(da), "l"(db), "n"(TA), "n"(TB));
}
template <int TA, int TB> __device__ __forceinline__ void ss64z(float* d, uint64_t da, uint64_t db) {
  asm volatile("{\n.reg .pred p;\nsetp.ne.b32 p, 0, 0;\n"
    "wgmma.mma_async.sync.aligned.m64n64k16.f32.bf16.bf16 "
    "{%0, %1, %2, %3, %4, %5, %6, %7, %8, %9, %10, %11, %12, %13, %14, %15, "
    "%16, %17, %18, %19, %20, %21, %22, %23, %24, %25, %26, %27, %28, %29, %30, %31}, %32, %33, p, 1, 1, %34, %35;\n}\n"
    : "=f"(d[0]), "=f"(d[1]), "=f"(d[2]), "=f"(d[3]), "=f"(d[4]), "=f"(d[5]), "=f"(d[6]), "=f"(d[7]),
      "=f"(d[8]), "=f"(d[9]), "=f"(d[10]), "=f"(d[11]), "=f"(d[12]), "=f"(d[13]), "=f"(d[14]), "=f"(d[15]),
      "=f"(d[16]), "=f"(d[17]), "=f"(d[18]), "=f"(d[19]), "=f"(d[20]), "=f"(d[21]), "=f"(d[22]), "=f"(d[23]),
      "=f"(d[24]), "=f"(d[25]), "=f"(d[26]), "=f"(d[27]), "=f"(d[28]), "=f"(d[29]), "=f"(d[30]), "=f"(d[31])
    : "l"(da), "l"(db), "n"(TA), "n"(TB));
}
__device__ __forceinline__ void ss64x4(float* d, const D2* c, int on) {
  asm volatile("{\n.reg .pred p, z, c;\nsetp.eq.b32 p, 0, 0;\nsetp.ne.b32 z, 0, 0;\nsetp.eq.b32 c, %40, 0;\n"
    "wgmma.mma_async.sync.aligned.m64n64k16.f32.bf16.bf16 "
    "{%0, %1, %2, %3, %4, %5, %6, %7, %8, %9, %10, %11, %12, %13, %14, %15, "
    "%16, %17, %18, %19, %20, %21, %22, %23, %24, %25, %26, %27, %28, %29, %30, %31}, %32, %33, z, 1, 1, 0, 1;\n"
    "wgmma.commit_group.sync.aligned;\n@c bra.uni X4_DONE;\n"
    "wgmma.mma_async.sync.aligned.m64n64k16.f32.bf16.bf16 "
    "{%0, %1, %2, %3, %4, %5, %6, %7, %8, %9, %10, %11, %12, %13, %14, %15, "
    "%16, %17, %18, %19, %20, %21, %22, %23, %24, %25, %26, %27, %28, %29, %30, %31}, %34, %35, p, 1, 1, 0, 1;\n"
    "wgmma.mma_async.sync.aligned.m64n64k16.f32.bf16.bf16 "
    "{%0, %1, %2, %3, %4, %5, %6, %7, %8, %9, %10, %11, %12, %13, %14, %15, "
    "%16, %17, %18, %19, %20, %21, %22, %23, %24, %25, %26, %27, %28, %29, %30, %31}, %36, %37, p, 1, 1, 0, 1;\n"
    "wgmma.mma_async.sync.aligned.m64n64k16.f32.bf16.bf16 "
    "{%0, %1, %2, %3, %4, %5, %6, %7, %8, %9, %10, %11, %12, %13, %14, %15, "
    "%16, %17, %18, %19, %20, %21, %22, %23, %24, %25, %26, %27, %28, %29, %30, %31}, %38, %39, p, 1, 1, 0, 1;\n"
    "wgmma.commit_group.sync.aligned;\nX4_DONE:\n}\n"
    : "=f"(d[0]), "=f"(d[1]), "=f"(d[2]), "=f"(d[3]), "=f"(d[4]), "=f"(d[5]), "=f"(d[6]), "=f"(d[7]),
      "=f"(d[8]), "=f"(d[9]), "=f"(d[10]), "=f"(d[11]), "=f"(d[12]), "=f"(d[13]), "=f"(d[14]), "=f"(d[15]),
      "=f"(d[16]), "=f"(d[17]), "=f"(d[18]), "=f"(d[19]), "=f"(d[20]), "=f"(d[21]), "=f"(d[22]), "=f"(d[23]),
      "=f"(d[24]), "=f"(d[25]), "=f"(d[26]), "=f"(d[27]), "=f"(d[28]), "=f"(d[29]), "=f"(d[30]), "=f"(d[31])
    : "l"(c[0].a), "l"(c[0].b), "l"(c[1].a), "l"(c[1].b), "l"(c[2].a), "l"(c[2].b), "l"(c[3].a), "l"(c[3].b), "r"(on));
}
template <int TB> __device__ __forceinline__ void rs32a(float* d, const uint32_t* a, uint64_t db) {
  asm volatile("{\n.reg .pred p;\nsetp.eq.b32 p, 0, 0;\n"
    "wgmma.mma_async.sync.aligned.m64n32k16.f32.bf16.bf16 "
    "{%0, %1, %2, %3, %4, %5, %6, %7, %8, %9, %10, %11, %12, %13, %14, %15}, {%16, %17, %18, %19}, %20, p, 1, 1, %21;\n}\n"
    : "+f"(d[0]), "+f"(d[1]), "+f"(d[2]), "+f"(d[3]), "+f"(d[4]), "+f"(d[5]), "+f"(d[6]), "+f"(d[7]),
      "+f"(d[8]), "+f"(d[9]), "+f"(d[10]), "+f"(d[11]), "+f"(d[12]), "+f"(d[13]), "+f"(d[14]), "+f"(d[15])
    : "r"(a[0]), "r"(a[1]), "r"(a[2]), "r"(a[3]), "l"(db), "n"(TB));
}
template <int TB> __device__ __forceinline__ void rs32z(float* d, const uint32_t* a, uint64_t db) {
  asm volatile("{\n.reg .pred p;\nsetp.ne.b32 p, 0, 0;\n"
    "wgmma.mma_async.sync.aligned.m64n32k16.f32.bf16.bf16 "
    "{%0, %1, %2, %3, %4, %5, %6, %7, %8, %9, %10, %11, %12, %13, %14, %15}, {%16, %17, %18, %19}, %20, p, 1, 1, %21;\n}\n"
    : "=&f"(d[0]), "=&f"(d[1]), "=&f"(d[2]), "=&f"(d[3]), "=&f"(d[4]), "=&f"(d[5]), "=&f"(d[6]), "=&f"(d[7]),
      "=&f"(d[8]), "=&f"(d[9]), "=&f"(d[10]), "=&f"(d[11]), "=&f"(d[12]), "=&f"(d[13]), "=&f"(d[14]), "=&f"(d[15])
    : "r"(a[0]), "r"(a[1]), "r"(a[2]), "r"(a[3]), "l"(db), "n"(TB));
}
template <int TB> __device__ __forceinline__ void rs40a(float* d, const uint32_t* a, uint64_t db) {
  asm volatile("{\n.reg .pred p;\nsetp.eq.b32 p, 0, 0;\n"
    "wgmma.mma_async.sync.aligned.m64n40k16.f32.bf16.bf16 "
    "{%0, %1, %2, %3, %4, %5, %6, %7, %8, %9, %10, %11, %12, %13, %14, %15, "
    "%16, %17, %18, %19}, {%20, %21, %22, %23}, %24, p, 1, 1, %25;\n}\n"
    : "+f"(d[0]), "+f"(d[1]), "+f"(d[2]), "+f"(d[3]), "+f"(d[4]), "+f"(d[5]), "+f"(d[6]), "+f"(d[7]),
      "+f"(d[8]), "+f"(d[9]), "+f"(d[10]), "+f"(d[11]), "+f"(d[12]), "+f"(d[13]), "+f"(d[14]), "+f"(d[15]),
      "+f"(d[16]), "+f"(d[17]), "+f"(d[18]), "+f"(d[19])
    : "r"(a[0]), "r"(a[1]), "r"(a[2]), "r"(a[3]), "l"(db), "n"(TB));
}
template <int TB> __device__ __forceinline__ void rs40z(float* d, const uint32_t* a, uint64_t db) {
  asm volatile("{\n.reg .pred p;\nsetp.ne.b32 p, 0, 0;\n"
    "wgmma.mma_async.sync.aligned.m64n40k16.f32.bf16.bf16 "
    "{%0, %1, %2, %3, %4, %5, %6, %7, %8, %9, %10, %11, %12, %13, %14, %15, "
    "%16, %17, %18, %19}, {%20, %21, %22, %23}, %24, p, 1, 1, %25;\n}\n"
    : "=&f"(d[0]), "=&f"(d[1]), "=&f"(d[2]), "=&f"(d[3]), "=&f"(d[4]), "=&f"(d[5]), "=&f"(d[6]), "=&f"(d[7]),
      "=&f"(d[8]), "=&f"(d[9]), "=&f"(d[10]), "=&f"(d[11]), "=&f"(d[12]), "=&f"(d[13]), "=&f"(d[14]), "=&f"(d[15]),
      "=&f"(d[16]), "=&f"(d[17]), "=&f"(d[18]), "=&f"(d[19])
    : "r"(a[0]), "r"(a[1]), "r"(a[2]), "r"(a[3]), "l"(db), "n"(TB));
}
template <int TB> __device__ __forceinline__ void rs72a(float* d, const uint32_t* a, uint64_t db) {
  asm volatile("{\n.reg .pred p;\nsetp.eq.b32 p, 0, 0;\n"
    "wgmma.mma_async.sync.aligned.m64n72k16.f32.bf16.bf16 "
    "{%0, %1, %2, %3, %4, %5, %6, %7, %8, %9, %10, %11, %12, %13, %14, %15, "
    "%16, %17, %18, %19, %20, %21, %22, %23, %24, %25, %26, %27, %28, %29, %30, %31, "
    "%32, %33, %34, %35}, {%36, %37, %38, %39}, %40, p, 1, 1, %41;\n}\n"
    : "+f"(d[0]), "+f"(d[1]), "+f"(d[2]), "+f"(d[3]), "+f"(d[4]), "+f"(d[5]), "+f"(d[6]), "+f"(d[7]),
      "+f"(d[8]), "+f"(d[9]), "+f"(d[10]), "+f"(d[11]), "+f"(d[12]), "+f"(d[13]), "+f"(d[14]), "+f"(d[15]),
      "+f"(d[16]), "+f"(d[17]), "+f"(d[18]), "+f"(d[19]), "+f"(d[20]), "+f"(d[21]), "+f"(d[22]), "+f"(d[23]),
      "+f"(d[24]), "+f"(d[25]), "+f"(d[26]), "+f"(d[27]), "+f"(d[28]), "+f"(d[29]), "+f"(d[30]), "+f"(d[31]),
      "+f"(d[32]), "+f"(d[33]), "+f"(d[34]), "+f"(d[35])
    : "r"(a[0]), "r"(a[1]), "r"(a[2]), "r"(a[3]), "l"(db), "n"(TB));
}
template <int TB> __device__ __forceinline__ void rs72z(float* d, const uint32_t* a, uint64_t db) {
  asm volatile("{\n.reg .pred p;\nsetp.ne.b32 p, 0, 0;\n"
    "wgmma.mma_async.sync.aligned.m64n72k16.f32.bf16.bf16 "
    "{%0, %1, %2, %3, %4, %5, %6, %7, %8, %9, %10, %11, %12, %13, %14, %15, "
    "%16, %17, %18, %19, %20, %21, %22, %23, %24, %25, %26, %27, %28, %29, %30, %31, "
    "%32, %33, %34, %35}, {%36, %37, %38, %39}, %40, p, 1, 1, %41;\n}\n"
    : "=&f"(d[0]), "=&f"(d[1]), "=&f"(d[2]), "=&f"(d[3]), "=&f"(d[4]), "=&f"(d[5]), "=&f"(d[6]), "=&f"(d[7]),
      "=&f"(d[8]), "=&f"(d[9]), "=&f"(d[10]), "=&f"(d[11]), "=&f"(d[12]), "=&f"(d[13]), "=&f"(d[14]), "=&f"(d[15]),
      "=&f"(d[16]), "=&f"(d[17]), "=&f"(d[18]), "=&f"(d[19]), "=&f"(d[20]), "=&f"(d[21]), "=&f"(d[22]), "=&f"(d[23]),
      "=&f"(d[24]), "=&f"(d[25]), "=&f"(d[26]), "=&f"(d[27]), "=&f"(d[28]), "=&f"(d[29]), "=&f"(d[30]), "=&f"(d[31]),
      "=&f"(d[32]), "=&f"(d[33]), "=&f"(d[34]), "=&f"(d[35])
    : "r"(a[0]), "r"(a[1]), "r"(a[2]), "r"(a[3]), "l"(db), "n"(TB));
}
template <int TB> __device__ __forceinline__ void rs128a(float* d, const uint32_t* a, uint64_t db) {
  asm volatile("{\n.reg .pred p;\nsetp.eq.b32 p, 0, 0;\n"
    "wgmma.mma_async.sync.aligned.m64n128k16.f32.bf16.bf16 "
    "{%0, %1, %2, %3, %4, %5, %6, %7, %8, %9, %10, %11, %12, %13, %14, %15, "
    "%16, %17, %18, %19, %20, %21, %22, %23, %24, %25, %26, %27, %28, %29, %30, %31, "
    "%32, %33, %34, %35, %36, %37, %38, %39, %40, %41, %42, %43, %44, %45, %46, %47, "
    "%48, %49, %50, %51, %52, %53, %54, %55, %56, %57, %58, %59, %60, %61, %62, %63}, {%64, %65, %66, %67}, %68, p, 1, 1, %69;\n}\n"
    : "+f"(d[0]), "+f"(d[1]), "+f"(d[2]), "+f"(d[3]), "+f"(d[4]), "+f"(d[5]), "+f"(d[6]), "+f"(d[7]),
      "+f"(d[8]), "+f"(d[9]), "+f"(d[10]), "+f"(d[11]), "+f"(d[12]), "+f"(d[13]), "+f"(d[14]), "+f"(d[15]),
      "+f"(d[16]), "+f"(d[17]), "+f"(d[18]), "+f"(d[19]), "+f"(d[20]), "+f"(d[21]), "+f"(d[22]), "+f"(d[23]),
      "+f"(d[24]), "+f"(d[25]), "+f"(d[26]), "+f"(d[27]), "+f"(d[28]), "+f"(d[29]), "+f"(d[30]), "+f"(d[31]),
      "+f"(d[32]), "+f"(d[33]), "+f"(d[34]), "+f"(d[35]), "+f"(d[36]), "+f"(d[37]), "+f"(d[38]), "+f"(d[39]),
      "+f"(d[40]), "+f"(d[41]), "+f"(d[42]), "+f"(d[43]), "+f"(d[44]), "+f"(d[45]), "+f"(d[46]), "+f"(d[47]),
      "+f"(d[48]), "+f"(d[49]), "+f"(d[50]), "+f"(d[51]), "+f"(d[52]), "+f"(d[53]), "+f"(d[54]), "+f"(d[55]),
      "+f"(d[56]), "+f"(d[57]), "+f"(d[58]), "+f"(d[59]), "+f"(d[60]), "+f"(d[61]), "+f"(d[62]), "+f"(d[63])
    : "r"(a[0]), "r"(a[1]), "r"(a[2]), "r"(a[3]), "l"(db), "n"(TB));
}
template <int TB> __device__ __forceinline__ void rs128z(float* d, const uint32_t* a, uint64_t db) {
  asm volatile("{\n.reg .pred p;\nsetp.ne.b32 p, 0, 0;\n"
    "wgmma.mma_async.sync.aligned.m64n128k16.f32.bf16.bf16 "
    "{%0, %1, %2, %3, %4, %5, %6, %7, %8, %9, %10, %11, %12, %13, %14, %15, "
    "%16, %17, %18, %19, %20, %21, %22, %23, %24, %25, %26, %27, %28, %29, %30, %31, "
    "%32, %33, %34, %35, %36, %37, %38, %39, %40, %41, %42, %43, %44, %45, %46, %47, "
    "%48, %49, %50, %51, %52, %53, %54, %55, %56, %57, %58, %59, %60, %61, %62, %63}, {%64, %65, %66, %67}, %68, p, 1, 1, %69;\n}\n"
    : "=&f"(d[0]), "=&f"(d[1]), "=&f"(d[2]), "=&f"(d[3]), "=&f"(d[4]), "=&f"(d[5]), "=&f"(d[6]), "=&f"(d[7]),
      "=&f"(d[8]), "=&f"(d[9]), "=&f"(d[10]), "=&f"(d[11]), "=&f"(d[12]), "=&f"(d[13]), "=&f"(d[14]), "=&f"(d[15]),
      "=&f"(d[16]), "=&f"(d[17]), "=&f"(d[18]), "=&f"(d[19]), "=&f"(d[20]), "=&f"(d[21]), "=&f"(d[22]), "=&f"(d[23]),
      "=&f"(d[24]), "=&f"(d[25]), "=&f"(d[26]), "=&f"(d[27]), "=&f"(d[28]), "=&f"(d[29]), "=&f"(d[30]), "=&f"(d[31]),
      "=&f"(d[32]), "=&f"(d[33]), "=&f"(d[34]), "=&f"(d[35]), "=&f"(d[36]), "=&f"(d[37]), "=&f"(d[38]), "=&f"(d[39]),
      "=&f"(d[40]), "=&f"(d[41]), "=&f"(d[42]), "=&f"(d[43]), "=&f"(d[44]), "=&f"(d[45]), "=&f"(d[46]), "=&f"(d[47]),
      "=&f"(d[48]), "=&f"(d[49]), "=&f"(d[50]), "=&f"(d[51]), "=&f"(d[52]), "=&f"(d[53]), "=&f"(d[54]), "=&f"(d[55]),
      "=&f"(d[56]), "=&f"(d[57]), "=&f"(d[58]), "=&f"(d[59]), "=&f"(d[60]), "=&f"(d[61]), "=&f"(d[62]), "=&f"(d[63])
    : "r"(a[0]), "r"(a[1]), "r"(a[2]), "r"(a[3]), "l"(db), "n"(TB));
}

template <int V> struct IC { static constexpr int value = V; };
struct PfType { const char* base; uint32_t gl, gh, sp, sr, su, l4, l2; };
struct Params {
  const __nv_bfloat16 *x, *w;
  unsigned* cnt;
  uint32_t one;
  const __nv_bfloat16 *shift, *ssmD;
  __nv_bfloat16* out;
  uint4* o; float* kv;
  const char *k, *v;
  PfType pt[6];
  uint8_t pf[32];
  uint64_t cd[18];
};

struct Tmp { float t0, t1; };
__device__ __forceinline__ void mul2(Tmp& t, float a0, float b0, float a1, float b1) {
  asm volatile("@p_one mul.rn.f32 %0, %2, %3;\n@p_one mul.rn.f32 %1, %4, %5;" : "+f"(t.t0), "+f"(t.t1) : "f"(a0), "f"(b0), "f"(a1), "f"(b1)); }
__device__ __forceinline__ void add2(Tmp& t, float a0, float b0, float a1, float b1) {
  asm volatile("@p_one add.rn.f32 %0, %2, %3;\n@p_one add.rn.f32 %1, %4, %5;" : "+f"(t.t0), "+f"(t.t1) : "f"(a0), "f"(b0), "f"(a1), "f"(b1)); }
__device__ __forceinline__ void fma2(Tmp& t, float a0, float b0, float a1, float b1) { t.t0 = fmaf(a0, b0, t.t0); t.t1 = fmaf(a1, b1, t.t1); }
struct Tw { uint32_t c[2], s[2], ns[2]; };
__device__ __forceinline__ void rot(uint32_t& u, uint32_t& v, const Tw& w, int k) {
  asm("{\n.reg .b32 a, b;\nmul.rn.bf16x2 a, %0, %2;\nmul.rn.bf16x2 b, %0, %3;\nfma.rn.bf16x2 %0, %1, %4, a;\nfma.rn.bf16x2 %1, %1, %2, b;\n}"
    : "+r"(u), "+r"(v) : "r"(w.c[k]), "r"(w.s[k]), "r"(w.ns[k]));
}
__device__ __forceinline__ void pack_fwd(uint32_t (&f)[2][2][4], const float* a) {
  #pragma unroll
  for (int j = 0; j < 16; j++) f[j >> 3][(j >> 1) & 1][2 * (j & 1) + ((j >> 2) & 1)] = fresh(pack_bf16(a[2 * j], a[2 * j + 1]));
}
__device__ __forceinline__ void rot_fwd(uint32_t (&f)[2][2][4], const Tw& w) {
  #pragma unroll
  for (int j = 0; j < 8; j++) rot(f[j >> 2][j & 1][(j >> 1) & 1], f[j >> 2][j & 1][2 + ((j >> 1) & 1)], w, j & 1);
}
__device__ __forceinline__ void add_skip(float* h, float d) {
  asm volatile("add.rn.f32 %0, %0, %4;\nadd.rn.f32 %1, %1, %4;\nadd.rn.f32 %2, %2, %4;\nadd.rn.f32 %3, %3, %4;" : "+f"(h[0]), "+f"(h[1]), "+f"(h[4]), "+f"(h[5]) : "f"(d)); }
__device__ __forceinline__ void dft16h(float* d, const uint32_t (&f)[2][4], const D2& dF) { rs32z<0>(d, f[0], dF.a); rs32a<0>(d, f[1], dF.b); }
#define SP(h, p, im, k) (((p) >> 1 ? hi : lo) + 16 * (h) + 8 * (im) + 4 * (k) + 2 * ((p) & 1))
template <int PH, int G0 = 0, int G1 = 8> __device__ __forceinline__ void prod(Tmp& t, uint32_t (&f)[2][4], const float* lo, const float* hi) {
  #pragma unroll
  for (int g = G0; g < G1; g++) {
    const int p = 2 * PH + 1 - (g >> 2), k = (g >> 1) & 1, im = g & 1;
    #pragma unroll
    for (int q = 0; q <= p; q++) {
      const float *hr = SP(1, q, 0, k), *hi_ = SP(1, q, 1, k), *xa = SP(0, p - q, im, k), *xb = SP(0, p - q, 1 - im, k);
      if (q == 0) mul2(t, hr[0], xa[0], hr[1], xa[1]); else fma2(t, hr[0], xa[0], hr[1], xa[1]);
      if (im) fma2(t, hi_[0], xb[0], hi_[1], xb[1]); else fma2(t, -hi_[0], xb[0], -hi_[1], xb[1]);
    }
    f[k][2 * (1 - im) + (p & 1)] = pack_bf16(t.t0, t.t1);
  }
}

constexpr uint64_t dA = cdesc(A_OFF, 2048, 128, 0), dAi = cdesc(A_OFF, 128, 1024, 0), dF0 = cdesc(F_OFF, 128, 512, 0),
                   dT0 = cdesc(T_OFF, 1024, 128, 0), dH0 = cdesc(H_OFF, 1024, 256, 3), dX0 = cdesc(X_OFF, 1024, 128, 0);
#define CONV_DESC dF0, dF0 + 16, dAi, dT0, dAi + 16, dT0 + 128, dAi + 32, dT0 + 256, dAi + 48, dT0 + 384, dA, dH0, dA + 256, dH0 + 32, dA, dX0, dA + 256, dX0 + 128
__device__ __forceinline__ void make_tw(Tw& tw, int ht) {
  #pragma unroll
  for (int i = 0; i < 2; i++) {
    float c0, s0, c1, s1;
    unit_root<11>((4 * (ht >> 2) + 1) * (i * 8 + 2 * (ht & 3)), c0, s0);
    unit_root<11>((4 * (ht >> 2) + 1) * (i * 8 + 2 * (ht & 3) + 1), c1, s1);
    tw.c[i] = pack_bf16(c0, c1); tw.s[i] = pack_bf16(s0, s1); tw.ns[i] = fresh(tw.s[i] ^ 0x80008000u);
  }
}
template <bool COMMIT = true> __device__ __forceinline__ void dft32_h(float* r, const D2* d) {
  ss64z<1, 1>(r, d[0].a, d[0].b); ss64a<1, 1>(r, d[1].a, d[1].b);
  if (COMMIT) wg_commit();
}
template <bool COMMIT = true> __device__ __forceinline__ void dft32_x(float* r, D2* d) {
  ss64z<1, 0>(r, d[0].a, d[0].b); ss64a<1, 0>(r, d[1].a, d[1].b);
  if (COMMIT) wg_commit();
  d[0].b = dofs(d[0].b, XS); d[1].b = dofs(d[1].b, XS);
}
__device__ __forceinline__ void pack_inv(uint32_t (&u)[2][2][4], const float* r) {
  #pragma unroll
  for (int j = 0; j < 16; j++) u[j >> 3][(j >> 2) & 1][2 * (j & 1) + ((j >> 1) & 1)] = fresh(pack_bf16(r[2 * j], r[2 * j + 1]));
}
__device__ __forceinline__ void rot_inv(uint32_t (&u)[2][2][4], const Tw& tw, uint32_t ta) {
  #pragma unroll
  for (int m = 0; m < 2; m++) {
    #pragma unroll
    for (int j = 0; j < 4; j++) rot(u[m][0][j], u[m][1][j], tw, j & 1);
    stsm4(ta + m * 512, u[m][1][0], u[m][1][1], u[m][1][2], u[m][1][3]);
    stsm4(ta + 1024 + m * 512, u[m][0][0], u[m][0][1], u[m][0][2], u[m][0][3]);
  }
}
__device__ __forceinline__ void idft32(float* r, const D2* d) {
  wg_fence();
  ss64z<0, 1>(r, d[0].a, d[0].b);
  #pragma unroll
  for (int j = 1; j < 4; j++) ss64a<0, 1>(r, d[j].a, d[j].b);
  wg_commit();
}
__device__ __forceinline__ void finish(Tmp& t, const float* r, int ch, int ht, int rank, uint32_t y0, uint32_t y1) {
  const uint32_t ya = X_OFF + ch * XS + (ch & 1) * 16, yb = BAR_OFF + (B_YR + ch) * 8;
  uint32_t y[8];
  #pragma unroll
  for (int j = 0; j < 8; j++) {
    if (j >= 2) add2(t, r[4 * j], r[4 * j - 6], r[4 * j + 1], r[4 * j - 5]);
    y[j] = j < 2 ? pack_bf16(r[4 * j], r[4 * j + 1]) : pack_bf16(t.t0, t.t1);
  }
  st_async128(y0 + ya + (ht ^ (rank * 4)) * 16 + rank * (YX - XS), y0 + yb, y[0], y[1], y[2], y[3]);
  st_async128(y1 + ya + (ht ^ (rank * 4) ^ 4) * 16 + (rank ^ 1) * (YX - XS), y1 + yb, y[4], y[5], y[6], y[7]);
}

struct Team { uint32_t bars, rel, wofs, lead; };
struct Nop { __device__ __forceinline__ void operator()() const {} };
template <bool M, class F> __device__ __forceinline__ void mid_wait(F f) { if (M) wg_commit(); f(); if (M) { wg_wait<0>(); wg_fence(); } }
template <int J, bool M = false, class F = Nop> __device__ __forceinline__ void kv_issue(float* aK, float* aV, uint32_t xo, int sd, F f = F()) {
  constexpr uint64_t dw = cdesc(W_OFF + J * 8192, 8192, 1024, 1);
  const uint64_t dx = dofs(cdesc((J & 1) * 64, 16, 1024, 1), xo);
  wg_fence();
  ss128p<1, 0>(aV, dw + (4096 >> 4), dx, sd);
  ss128p<1, 0>(aK, dw, dx, sd);
  mid_wait<M>(f);
  ss128a<1, 0>(aV, dw + (6144 >> 4), dofs(dx, 32));
  ss128a<1, 0>(aK, dw + (2048 >> 4), dofs(dx, 32));
  wg_commit();
}
template <int O, int J, int H> __device__ __forceinline__ void g2_half(float* acc, const Team& c) {
  constexpr uint64_t db = cdesc(J * SLOT + 16384 + H * 4096, 8192, 1024, 1);
  const uint64_t da = dofs(O ? cdesc(J * SLOT + H * 4096, 16, 512, 2) : cdesc(J * SLOT + H * 64, 16, 1024, 1), c.wofs);
  wg_fence();
  ss128a<0, 1>(acc, da, db);
  ss128a<0, 1>(acc, dofs(da, 32), db + (2048 >> 4));
  wg_commit();
}
template <int O, int J, bool M = false, bool FIRST = false, class F = Nop> __device__ __forceinline__ void g2_issue(float* acc, const Team& c, F f = F()) {
  constexpr uint64_t db = cdesc(J * SLOT + 16384, 8192, 1024, 1);
  const uint64_t da = dofs(O ? cdesc(J * SLOT, 16, 512, 2) : cdesc(J * SLOT, 16, 1024, 1), c.wofs);
  wg_fence();
  if (FIRST) ss128z<0, 1>(acc, da, db); else ss128a<0, 1>(acc, da, db);
  ss128a<0, 1>(acc, dofs(da, 32), db + (2048 >> 4));
  mid_wait<M>(f);
  ss128a<0, 1>(acc, dofs(da, O ? 4096 : 64), db + (4096 >> 4));
  ss128a<0, 1>(acc, dofs(da, O ? 4128 : 96), db + (6144 >> 4));
  wg_commit();
}
template <bool DEEP, bool AB = false, class F>
__device__ __forceinline__ void ring_step(const Team& c, int fb, uint32_t ph, int eb, uint32_t rel, F issue, uint32_t ab = 0, uint32_t aph = 0) {
  uint32_t ok = mbar_try(c.bars + fb * 8, ph);
  if (AB) ok &= mbar_try(ab, aph);
  if (!ok) {
    wg_wait<0>();
    arrive_at(c.rel + eb * 8, rel);
    rel = 0;
    mbar_wait(c.bars + fb * 8, ph);
    if (AB) mbar_wait(ab, aph);
  }
  if constexpr (!DEEP) {
    wg_wait<0>();
    issue([&]() { arrive_at(c.rel + eb * 8, rel); });
  } else {
    issue();
    wg_wait<1>(); arrive_at(c.rel + eb * 8, rel);
  }
}
template <int N, int I = 0, class R> __device__ __forceinline__ void tail_release(R rel) {
  if constexpr (I <= N) { wg_wait<N - I>(); rel(I - 1); tail_release<N, I + 1>(rel); }
}
template <int N, class F, class R> __device__ __forceinline__ void skew_tail(const Team& c, int ph, F issue, R rel) {
  if (c.wofs) { wg_wait<0>(); rel(-1); mbar_wait(c.bars + B_SK * 8, ph); }
  issue();
  arrive_at(c.bars + B_SK * 8, fresh_tid() == 0);
  tail_release<N>([&](int i) { if (i >= 0 || !c.wofs) rel(i); });
}
__device__ __forceinline__ void phi_a(float* a, uint32_t* f) {
  #pragma unroll
  for (int i = 0; i < 8; i++) {
    asm("cvt.rn.relu.bf16x2.f32 %0, %1, %2;" : "=r"(f[i]) : "f"(a[2 * i + 1]), "f"(a[2 * i]));
    asm("ex2.approx.ftz.f32 %0, %1;" : "=f"(a[2 * i]) : "f"(a[2 * i] * 1.4426950408889634f));
    asm("ex2.approx.ftz.f32 %0, %1;" : "=f"(a[2 * i + 1]) : "f"(a[2 * i + 1] * 1.4426950408889634f));
  }
  pinv<16>(a);
}
__device__ __forceinline__ void phi_s(float* a, uint32_t* f) {
  #pragma unroll
  for (int i = 0; i < 8; i++) {
    asm("cvt.rn.relu.bf16x2.f32 %0, %1, %2;" : "=r"(f[i]) : "f"(a[2 * i + 1]), "f"(a[2 * i]));
    a[2 * i] *= 1.4426950408889634f; a[2 * i + 1] *= 1.4426950408889634f;
  }
  pinv<16>(a);
}
__device__ __forceinline__ void phi_e(float* a) {
  #pragma unroll
  for (int i = 0; i < 16; i++) asm("ex2.approx.ftz.f32 %0, %0;" : "+f"(a[i]));
  pinv<16>(a);
}
__device__ __forceinline__ void phi_b(const float* e, uint32_t* f) {
  #pragma unroll
  for (int i = 0; i < 8; i++) f[i] = badd2(f[i], pack_bf16(__saturatef(e[2 * i] + 1e-6f), __saturatef(e[2 * i + 1] + 1e-6f)));
}
__device__ __forceinline__ int g2_k(int st, int n2) {
  const int j = (st >> 1) - 1;
  return 2 * (j == 0 ? n2 == 0 : (j == max(n2, 1) ? 7 : j)) + (st & 1);
}

__global__ void __cluster_dims__(2, 1, 1) __launch_bounds__(NTHREADS, 1)
fused_kernel(const __grid_constant__ Params P, const __grid_constant__ CUtensorMap mX, const __grid_constant__ CUtensorMap mW,
             const __grid_constant__ CUtensorMap mWq, const __grid_constant__ CUtensorMap mWo,
             const __grid_constant__ CUtensorMap mK, const __grid_constant__ CUtensorMap mV, const __grid_constant__ CUtensorMap mH,
             const __grid_constant__ CUtensorMap mQ, const __grid_constant__ CUtensorMap mOut, const __grid_constant__ CUtensorMap mOutA,
             const __grid_constant__ CUtensorMap mWp) {
  extern __shared__ __align__(1024) uint8_t smem[];
  asm volatile(".reg .pred p_one;");
  const int tid = threadIdx.x, lane = tid & 31;
  const int warp = __shfl_sync(0xffffffffu, tid >> 5, 0);
  if (warp == 0) {
    asm volatile(ELECT "prefetch.tensormap [%0];\n}" :: "l"(&mW) : "memory");
    asm volatile(ELECT "prefetch.tensormap [%0];\n}" :: "l"(&mX) : "memory");
  }
  {
    const uint32_t t = threadIdx.x, bb = blockIdx.x;
    asm volatile("{\n.reg .pred p, q;\nsetp.eq.u32 p, %2, 2;\nsetp.eq.u32 q, %3, 8;\n@p prefetch.global.L2 [%0];\n@q prefetch.global.L2 [%1];\n}"
      :: "l"(reinterpret_cast<const char*>(P.x) + ((bb * 16 + t - 32) * 2048)),
         "l"(reinterpret_cast<const char*>(P.w) + ((bb >> 2) * 2048 + bb * 1024 + t * 128 - 6144)), "r"(t >> 4), "r"(t >> 3));
  }
  const uint32_t sb = uni(smem_u32(smem));
  const uint32_t bars = sb + BAR_OFF;
  const uint32_t ids = uni(wanted_job() * 2 + (blockIdx.x & 1));
#define IDS(w) const int rank = (w) & 1, hp = (w) & 15, g = hp >> 1, mb = (w) >> 4, m2 = hp, n2 = mb, cp = g * 8 + mb; \
               (void)rank; (void)m2; (void)n2; (void)cp
  auto job = [&]() { return (uni(lds32(sb + D_OFF + 52)) & 126) | (ids & 1); };
  auto wrong_job = [&]() {
    mbar_wait(bars + B_EX * 8, 0);
    return uni(lds32(sb + D_OFF + 52) ^ lds32(sb + D_OFF + 56)) != 1;
  };

  if (warp == 0) {
    IDS(ids);
    mbar_init(bars + (B_XF + 2) * 8, 1); mbar_init(bars + B_F0 * 8, 1); mbar_init(bars + B_FULL * 8, 1);
    mbar_expect_tx(bars + B_FULL * 8, 8192);
    tma3d(sb + W_OFF, &mW, hp * 64, 0, 1, bars + B_FULL * 8);
    mbar_expect_tx(bars + (B_XF + 2) * 8, 16384);
    tma2d(sb + 2 * SLOT, &mX, 0, mb * 256, bars + (B_XF + 2) * 8);
    mbar_expect_tx(bars + B_F0 * 8, 16384);
    tma2d(sb + 2 * SLOT + 16384, &mX, 0, mb * 256 + 128, bars + B_F0 * 8);
    #pragma unroll
    for (int i = 1; i < 4; i++) mbar_init(bars + (B_FULL + i) * 8, 1);
    #pragma unroll
    for (int i = 1; i < 4; i++) {
      mbar_expect_tx(bars + (B_FULL + i) * 8, 8192);
      tma3d(sb + W_OFF + i * 8192, &mW, hp * 64, i * 32, 1, bars + (B_FULL + i) * 8);
    }
    mbar_init(bars + B_XF * 8, 1); mbar_init(bars + (B_XF + 1) * 8, 1);
  } else if (warp >= 6) {
    const uint32_t cnt = warp < 12 || warp == 15 ? 1 : 4, b0 = bars + (warp - 4) * 32;
    #pragma unroll
    for (int i = 0; i < 4; i++) mbar_init(b0 + i * 8, i == 3 && warp == 15 ? 4 : cnt);
    if (warp == 8 || warp == 9) {
      #pragma unroll
      for (int i = 0; i < 4; i++) mbar_expect_tx(b0 + i * 8, 4096);
    } else if ((warp & 13) == 13) {
      mbar_expect_tx(bars + (warp == 13 ? B_KVB : B_EX) * 8, warp == 13 ? 5120 : 8);
    }
  }
  asm volatile("fence.mbarrier_init.release.cluster;" ::: "memory");
  __syncwarp();
  asm volatile("barrier.cluster.arrive.relaxed.aligned;" ::: "memory");

  if ((warp >> 2) == 2) {
    asm volatile("setmaxnreg.inc.sync.aligned.u32 %0;" :: "n"(160));
    const int ht = tid - 256, w = warp - 8;
    const int kap = w & 1;
    {
      uint32_t c4[4], s4[4];
      #pragma unroll
      for (int i = 0; i < 4; i++) {
        float c0, s0, c1, s1;
        unit_root<7>((32 * (ht & 3) + 8 * i + 1) * (ht >> 2), c0, s0);
        unit_root<7>((32 * (ht & 3) + 8 * i + 5) * (ht >> 2), c1, s1);
        c4[i] = pack_bf16(c0 * 0.125f, c1 * 0.125f); s4[i] = pack_bf16(s0 * 0.125f, s1 * 0.125f);
      }
      const uint32_t aa = sb + A_OFF + w * 2048 + (ht & 3) * 256 + ((ht >> 2) & 7) * 16;
      sts128(aa, c4[0], c4[1], c4[2], c4[3]);
      sts128(aa + 128, s4[0], s4[1], s4[2], s4[3]);
      sts128(aa + 1024, s4[0] ^ 0x80008000u, s4[1] ^ 0x80008000u, s4[2] ^ 0x80008000u, s4[3] ^ 0x80008000u);
      sts128(aa + 1024 + 128, c4[0], c4[1], c4[2], c4[3]);
      float c0, s0, c1, s1;
      unit_root<4>((ht >> 3) * (2 * (ht & 7)), c0, s0);
      unit_root<4>((ht >> 3) * (2 * (ht & 7) + 1), c1, s1);
      const uint32_t fa = sb + F_OFF + (ht >> 6) * 512 + ((ht >> 2) & 1) * 256 + ((ht >> 3) & 7) * 16 + (ht & 3) * 4;
      const uint32_t cc = pack_bf16(c0, c1), ss = pack_bf16(s0, s1);
      sts32(fa, cc); sts32(fa + 128, ss ^ 0x80008000u); sts32(fa + 1024, ss); sts32(fa + 1024 + 128, cc);
    }
    cluster_wait();
    mbar_wait(bars + B_EX * 8, 0);
    const uint32_t id2 = job(); IDS(id2);
    if (id2 != ids) bar_sync(8, 160);
    const uint4 sw = *reinterpret_cast<const uint4*>(P.shift + (cp * 16 + kap * 8 + 2 * (lane & 3)) * 4);
    const float dv = __bfloat162float(P.ssmD[cp * 16 + rank * 8 + (ht & 7)]) * 0.125f;
    Tw tw;
    make_tw(tw, ht);
    D2 cd[9];
    {
      const uint64_t v = P.cd[min(lane, 17)];
      #pragma unroll
      for (int i = 0; i < 9; i++) { cd[i].a = __shfl_sync(0xffffffffu, v, 2 * i); cd[i].b = __shfl_sync(0xffffffffu, v, 2 * i + 1); }
    }
    const D2 &dF = cd[0], *dT = cd + 1, *dH = cd + 5;
    D2* dX = cd + 7;
#define CFENCE(n) sched_fence<n>((uint32_t)dF.a)
    if (ht < 8) sts32(sb + D_OFF + ht * 4, __float_as_uint(dv));
    const uint32_t w0 = __byte_perm(sw.x, sw.z, 0x5410), w1 = __byte_perm(sw.x, sw.z, 0x7632);
    const uint32_t w2 = __byte_perm(sw.y, sw.w, 0x5410), w3 = __byte_perm(sw.y, sw.w, 0x7632);
    const uint32_t psb = uni(mapa(sb, rank ^ 1));
    if (ht == 0) OSTAMP(20);
    {
      const int m = lane >> 3, n1 = (w >> 1) * 8 + (lane & 7);
      const int rk = 17 * m + n1 + 1, rh = 17 * (12 + m) + n1, rv = 16 * m + n1;
      const uint32_t ka = rk * 32 + ((kap ^ (rk >> 2)) & 1) * 16, ha = rh * 32 + ((kap ^ (rh >> 2)) & 1) * 16;
      const uint32_t va = rv * 32 + ((kap ^ (rv >> 2)) & 1) * 16;
      const uint32_t po = sb + T_OFF + (w >> 1) * 2176;
      #pragma unroll 1
      for (int rd = 0; rd < 4; rd++) {
        const uint32_t kb = sb + M_OFF + (rd & 1) * KB, vb = sb + M_OFF + 2 * KB + (rd & 1) * 8192;
        const uint32_t xo = X_OFF + ((rd & 1) * 2 + (w >> 1)) * 1024 + (2 * rank + (rd >> 1)) * 256;
        const uint32_t xa = (kap == rank ? sb + xo + (lane & 7) * XS : po + (lane & 7) * 272) + m * 16;
        mbar_wait(bars + (B_STG + (rd & 1) * 2) * 8, rd >> 1);
        uint32_t kk[20], vv[16];
        const uint32_t zero = P.one - 1;
        ldsm4(kk, kb + ha);
        ldsm4(kk + 4, kb + ka);
        #pragma unroll
        for (int i = 0; i < 16; i++) {
          if ((i & 3) == 0 && i < 12) ldsm4(kk + 8 + i, kb + (ka ^ ((~i & 4) * 4)) + (i + 4) * 544 + (kk[i + 4] & zero));
          uint32_t t = bmul2(kk[i + 1], w3);
          t = badd2(t, bmul2(kk[i + 2], w2));
          t = badd2(t, bmul2(kk[i + 3], w1));
          kk[i] = badd2(t, bmul2(kk[i + 4], w0));
          asm volatile("" : "+r"(kk[i]));
        }
        mbar_wait(bars + (B_STG + (rd & 1) * 2 + 1) * 8, rd >> 1);
        ldsm4(vv, vb + va);
        #pragma unroll
        for (int i = 0; i < 16; i += 4) {
          if (i < 12) ldsm4(vv + 4 + i, vb + va + (i + 4) * 512 + (i == 4 ? vv[0] & zero : 0));
          stsm4t(xa + (i >> 2) * 64, bmul2(kk[i], vv[i]), bmul2(kk[i + 1], vv[i + 1]), bmul2(kk[i + 2], vv[i + 2]), bmul2(kk[i + 3], vv[i + 3]));
        }
        if (rd < 2) {
          fence_async_smem();
          __syncwarp();
          mbar_arrive(bars + (B_SFREE + (rd & 1)) * 8);
        }
        __syncwarp();
        if (kap != rank) {
          #pragma unroll
          for (int i = 0; i < 4; i++) lds128(vv + 4 * i, po + (2 * i + (lane >> 4)) * 272 + (lane & 15) * 16);
          #pragma unroll
          for (int i = 0; i < 4; i++)
            st_async128(psb + xo + (2 * i + (lane >> 4)) * XS + (lane & 15) * 16, psb + BAR_OFF + B_X * 8, vv[4 * i], vv[4 * i + 1], vv[4 * i + 2], vv[4 * i + 3]);
          __syncwarp();
        }
      }
    }
    bar_sync(3, 128);
    if (w == 0) mbar_expect_tx(bars + B_X * 8, 16384);
    {
      constexpr int NC = 8;
      Tmp t; t.t0 = 0.f; t.t1 = 0.f;
      asm volatile("setp.ne.b32 p_one, %0, 0;" :: "r"(lds32(sb + F_OFF)));
      float ra[32], lo[32], hi[32];
      uint32_t fa[2][2][4], fb[2][2][4];
      const uint32_t ta = sb + T_OFF + w * 2048 + lane * 16;
      const uint32_t y0 = rank ? psb : sb, y1 = rank ? sb : psb;
      auto fin = [&](int ch) {
        if (ch > 0) mbar_wait(bars + (B_YR + ch - 1) * 8, 0);
        finish(t, ra, ch, ht, rank, y0, y1);
      };
      auto load_h = [&](int i) {
        mbar_expect_tx(bars + B_H * 8, 4096);
        tma2d(sb + H_OFF, &mH, 0, (cp * 16 + rank * 8 + i) * 128, bars + B_H * 8);
      };
      auto skip = [&](int i) {
        const float dn = __uint_as_float(lds32(sb + D_OFF + i * 4));
        return dn;
      };
      mbar_wait(bars + B_H * 8, 0);
      wg_fence();
      dft32_h(lo, dH);
      mbar_wait(bars + B_X * 8, 0);
      fence_async_smem();
      if (ht == 0) OSTAMP(21);
      wg_fence();
      dft32_x(hi, dX);
      float dn = skip(0);
      wg_wait<1>(); pinv<32>(lo);
      if (w == 0) load_h(1);
      pack_fwd(fa, lo); CFENCE(0); rot_fwd(fa, tw); CFENCE(1);
      wg_wait<0>(); pinv<32>(hi);
      pack_fwd(fb, hi); CFENCE(2); rot_fwd(fb, tw); CFENCE(3);
      wg_fence();
      dft16h(hi, fb[1], dF); dft16h(hi + 16, fa[1], dF); dft16h(lo, fb[0], dF); dft16h(lo + 16, fa[0], dF);
      wg_commit();
      wg_wait<0>(); pinv<32>(lo); pinv<32>(hi);
#define CSTAMP(n) do {} while (0)
      #pragma unroll 1
      for (int i = 0;; i++) {
        CSTAMP(0);
        add_skip(lo + 16, dn);
        prod<1, 0, FG>(t, fa[1], lo, hi);
        CFENCE(4);
        CSTAMP(1);
        fence_async_smem();
        bar_sync(3, 128);
        CSTAMP(2);
        float rg[32];
        wg_fence();
        ss64x4(rg, dT, i);
        CFENCE(5);
        CSTAMP(3);
        const uint32_t yr = bars + (i < 2 ? B_X : B_YR + i - 2) * 8;
        const uint32_t oky = mbar_try(yr, 0);
        dn = skip(i + 1);
        prod<1, FG, 8>(t, fa[1], lo, hi);
        pinv<32>(lo);
        if (!oky) mbar_wait(yr, 0);
        CSTAMP(4);
        wg_wait<0>(); pinv<32>(rg);
        if (i > 0) finish(t, rg, i - 1, ht, rank, y0, y1);
        if (i == NC - 1) break;
        CSTAMP(5);
        wg_fence();
        dft32_x<false>(hi, dX);
        dft16h(ra + 16, fa[1], dF);
        wg_commit();
        CFENCE(7);
        CSTAMP(6);
        const uint32_t okh = mbar_try(bars + B_H * 8, (i + 1) & 1);
        prod<0>(t, fa[0], lo, lo);
        if (!okh) mbar_wait(bars + B_H * 8, (i + 1) & 1);
        CSTAMP(7);
        wg_fence();
        dft32_h<false>(lo, dH);
        dft16h(ra, fa[0], dF);
        wg_commit();
        wg_wait<1>(); pinv<32>(hi);
        if (ht == 64) OSTAMP(22 + i);
        CSTAMP(8);
        pack_fwd(fb, hi); CFENCE(9); rot_fwd(fb, tw); CFENCE(10);
        CSTAMP(9);
        wg_wait<0>(); pinv<32>(lo); pinv<32>(ra);
        CSTAMP(10);
        if (w == 0 && i < NC - 2) load_h(i + 2);
        pack_fwd(fa, lo);
        CFENCE(11);
        wg_fence();
        dft16h(hi, fb[1], dF); dft16h(lo, fb[0], dF);
        wg_commit();
        CFENCE(12);
        rot_fwd(fa, tw);
        uint32_t u[2][2][4];
        CFENCE(13);
        pack_inv(u, ra);
        CFENCE(14);
        CSTAMP(11);
        wg_fence();
        dft16h(hi + 16, fa[1], dF); dft16h(lo + 16, fa[0], dF);
        wg_commit();
        CFENCE(15);
        CSTAMP(12);
        rot_inv(u, tw, ta);
        CSTAMP(13);
        CFENCE(16);
        wg_wait<0>(); pinv<32>(lo); pinv<32>(hi);
        CSTAMP(14);
      }
      wg_fence();
      dft16h(hi + 16, fa[1], dF);
      wg_commit();
      CFENCE(17);
      prod<0>(t, fa[0], lo, lo);
      CFENCE(18);
      wg_fence();
      dft16h(hi, fa[0], dF);
      wg_commit();
      if (ht == 64) OSTAMP(29);
      wg_wait<0>(); pinv<32>(hi);
      pack_inv(fb, hi); CFENCE(19); rot_inv(fb, tw, ta);
      fence_async_smem();
      bar_sync(3, 128);
      idft32(ra, dT);
      const int l3 = fresh_tid() & 31;
      uint32_t qa = sb + M_OFF + ((l3 >> 4) * 512 + w * 128 + (l3 & 8) + ((l3 >> 2) & 1) + (l3 & 2)) * 32 + (l3 & 1) * 16;
      uint32_t yb = sb + X_OFF + (l3 & 1) * (XS + 16) + w * 512
                    + (((l3 >> 1) & 1) == rank ? (l3 >> 2) * 16 : YX - XS + ((l3 >> 2) ^ 4) * 16);
      mbar_wait(bars + B_Q * 8, 0);
      wg_wait<0>(); pinv<32>(ra);
      fin(NC - 1);
      if (ht == 64) OSTAMP(30);
      uint32_t t0 = 0, dt = 0;
      #pragma unroll 1
      for (int sg = 0; sg < 4; sg++, qa += 1024, yb += 128) {
        uint32_t qv[4][4], yv[4][4];
        #pragma unroll
        for (int i = 0; i < 4; i++) lds128(qv[i], qa + (i >> 1) * 512 + (i & 1) * 128);
        #pragma unroll
        for (int m = 0; m < 4; m++) {
          if (m == 3 && sg == 0) mbar_wait(bars + (B_YR + NC - 1) * 8, 0);
          ldsm4t(yv[m], yb + 2 * m * XS);
        }
        #pragma unroll
        for (int i = 0; i < 4; i++)
          sts128(qa + (i >> 1) * 512 + (i & 1) * 128, bmul2(qv[i][0], yv[0][i]), bmul2(qv[i][1], yv[1][i]), bmul2(qv[i][2], yv[2][i]), bmul2(qv[i][3], yv[3][i]));
        if (sg == 3) mbar_arrive(bars + B_CD * 8);
        fence_async_smem();
        __syncwarp();
        if (sg == 0) {
          mbar_wait(bars + B_GO * 8, 0);
          t0 = uni((uint32_t)clock());
          dt = uni(min(max((int)(lds32(sb + D_OFF + 44) + OA_END - t0) >> 2, 4 * OA_MIN), 4 * OA_MAX));
          t0 += w * (dt >> 2);
        }
        pace(t0, dt);
        #pragma unroll
        for (int hf = 0; hf < 2; hf++) {
          const int r = w * 128 + sg * 32 + hf * 512;
          tma2d_store(&mOutA, cp * 16, rank * 1024 + r, sb + M_OFF + r * 32);
        }
      }
      bulk_commit(); bulk_wait_read();
      if (ht == 0) OSTAMP(31);
    }
  } else if (warp >= 12) {
    asm volatile("setmaxnreg.dec.sync.aligned.u32 %0;" :: "n"(32));
    const uint32_t t_pf = (uint32_t)clock();
    if (warp >= 14) {
      const uint32_t id2 = fresh(ids); IDS(id2);
      if (warp == 14) {
        asm volatile("prefetch.global.L2 [%0];" :: "l"(((lane & 1) ? P.v : P.k) + (rank * 2097152 + cp * 32 + (lane >> 1) * 131072)));
      } else {
        uint32_t t0 = t_pf + id2 * 2;
        #pragma unroll 1
        for (int i = 0; i < PF_N; i++) {
          const int u = P.pf[i];
          const PfType& f = P.pt[u >> 4];
          pace(t0, i == 0 ? PF_DT0 : (i < PF_N1 ? PF_DT1 : PF_DT2));
          asm volatile("prefetch.global.L2 [%0];" :: "l"(f.base + ((g & 3) * f.gl + (g >> 2) * f.gh + mb * f.sp + rank * f.sr + (u & 15) * f.su
                                                                   + (lane >> 2) * f.l4 + ((lane >> 1) & 1) * f.l2 + (lane & 1) * 128)));
        }
      }
    }
    cluster_wait();
    if (warp == 13) {
      unsigned* const asked = P.cnt + 80 * 32;
      uint32_t j = ids, taken = 0;
      if (lane + (ids & 1) == 0) taken = atomicExch(P.cnt + 64 * 32 + ids * 4, 1u);
      if (uni(taken)) {
        fence_gpu();
        unsigned n = 0;
        if (lane == 0) n = atomicAdd(asked, 1u);
        spin_until(asked, (uni(n) | 63) + 1);
        #pragma unroll 1
        for (j = 0; j < 126; j += 2) {
          if (lane == 0) n = atomicExch(P.cnt + 64 * 32 + j * 4, 1u);
          if (!uni(n)) break;
        }
        if (lane == 0) P.cnt[64 * 32 + j * 4] = 1;
        j |= 128;
      }
      asm volatile("{\n.reg .pred p;\nsetp.lt.u32 p, %3, 2;\n@p st.async.weak.shared::cluster.mbarrier::complete_tx::bytes.b32 [%0], %2, [%1];\n}"
        :: "r"(mapa(sb + D_OFF + 52 + (j & 1) * 4, lane & 1)), "r"(mapa(bars + B_EX * 8, lane & 1)), "r"(j), "r"(lane) : "memory");
      if (!(j & 129)) { fence_gpu(); red_add(asked); }
    }
    if (warp == 12) {
      uint32_t xs = 0, idk = fresh(ids);
      auto load_x = [&](int k) {
        IDS(idk);
        tma2d_mc(sb + xs * SLOT + rank * 16384, &mX, k, mb * 256 + rank * 128, bars + (B_XF + xs) * 8);
        mbar_expect_tx(bars + (B_XF + xs) * 8, SLOT);
        xs = xs == 2 ? 0 : xs + 1;
      };
      load_x(64); load_x(128);
      mbar_expect_tx(bars + B_Q * 8, 32768);
      int look = 5;
      #pragma unroll 1
      for (int it = 1; it < 8; it++) {
        #pragma unroll
        for (int j = 0; j < 4; j++) {
          bool again = false;
          if (j == 3 && it == look) again = wrong_job();
          mbar_wait(bars + (B_EMPTY + j) * 8, (it - 1) & 1);
          TSTAMP(1, 4 * it + j);
          tma3d(sb + W_OFF + j * 8192, &mW, (idk & 15) * 64, it * 128 + j * 32, 1, bars + (B_FULL + j) * 8);
          if (again) { it = look = -1; idk = job(); }
          if (j == 1 || (j == 3 && it < 7)) load_x(it * 128 + j * 32 + 32);
          mbar_expect_tx(bars + (B_FULL + j) * 8, 8192);
        }
      }
    }
    if (warp == 14) {
      uint32_t t0 = t_pf + STG_T0, idk = fresh(ids);
      #pragma unroll 1
      for (int pc = 0; pc < 16; pc++) {
        if (pc == 2) {
          mbar_wait(bars + B_EX * 8, 0);
          if (job() != idk) { mbar_wait(bars + B_STG * 8, 0); mbar_arrive(bars + B_STG * 8); bar_sync(8, 160); idk = job(); pc = 0; }
        }
        IDS(idk);
        const int rd = pc >> 2, u = pc & 3;
        const uint32_t gb = bars + (B_STG + (rd & 1) * 2 + (u >> 1)) * 8;
        if (pc == 8 || pc == 12) mbar_wait(bars + (B_SFREE + (rd & 1)) * 8, 0);
        if (!(u & 1)) mbar_expect_tx(gb, u ? 8192 : KB);
        pace(t0, STG_DT);
        TSTAMP(3, 16 + pc);
        tma3d(sb + M_OFF + (u < 2 ? (rd & 1) * KB + u * (KB / 2) : 2 * KB + (rd & 1) * 8192 + (u & 1) * 4096), u < 2 ? &mK : &mV,
              cp * 16, rank * 64 + rd * 16 - (u < 2), (u & 1) * 8, gb);
      }
      IDS(idk);
      mbar_expect_tx(bars + B_H * 8, 4096);
      tma2d(sb + H_OFF, &mH, 0, (cp * 16 + rank * 8) * 128, bars + B_H * 8);
    }
    mbar_wait(bars + B_EX * 8, 0);
    const uint32_t id2 = job(); IDS(id2);
    auto reduce_kv = [&](int i0, int i1) {
      float* kr = P.kv + hp * KV_PER_HP;
      mbar_wait(bars + B_Z * 8, 0);
      bar_sync(4, 352);
      #pragma unroll 1
      for (; i0 < i1; i0 += 2) {
        uint32_t p[2][4], q[2][4];
        const int i = (i0 + 2 * mb) & 15;
        const uint32_t pa = sb + M_OFF + (i & 3) * 2048 + (i >> 2) * 512 + (lane & 7) * 64 + (((lane >> 3) ^ (lane >> 1)) & 3) * 16;
        lds128(p[0], pa); lds128(q[0], pa + VT); lds128(p[1], pa + 2048); lds128(q[1], pa + VT + 2048);
        #pragma unroll
        for (int j = 0; j < 2; j++)
          asm volatile("red.relaxed.gpu.global.add.v4.f32 [%0], {%1,%2,%3,%4};" :: "l"(kr + (i + j) * 128 + lane * 4),
            "f"(__uint_as_float(p[j][0]) + __uint_as_float(q[j][0])), "f"(__uint_as_float(p[j][1]) + __uint_as_float(q[j][1])),
            "f"(__uint_as_float(p[j][2]) + __uint_as_float(q[j][2])), "f"(__uint_as_float(p[j][3]) + __uint_as_float(q[j][3])) : "memory");
      }
      if (i1 == 4) {
        const uint32_t za = sb + M_OFF + 8192 + lane * 4;
        #pragma unroll
        for (int h = 0; h < 2; h++)
          asm volatile("red.relaxed.gpu.global.add.f32 [%0], %1;" :: "l"(kr + 2048 + h * 32 + lane),
            "f"(__uint_as_float(lds32(za + h * 128)) + __uint_as_float(lds32(za + h * 128 + VT))) : "memory");
      }
      bar_sync(5, 96);
    };
    auto convert_kv = [&](int u0, auto N_) {
      constexpr int N = N_.value;
      const float* kg = P.kv + (2 * n2 + rank) * KV_PER_HP;
      const uint32_t psb = uni(mapa(sb, rank ^ 1));
      auto put = [&](uint32_t o, uint32_t v0, uint32_t v1, uint32_t v2, uint32_t v3) {
        st_async128(psb + o, psb + BAR_OFF + B_KVB * 8, v0, v1, v2, v3);
        sts128(sb + o, v0, v1, v2, v3);
      };
      mbar_wait(bars + B_KVL * 8, 0);
      spin_until(&P.cnt[(2 * n2 + rank) * 32 + 1], uni(lds32(sb + D_OFF + 40)) * 8);
      float4 v[N][2];
      float z[2];
      #pragma unroll
      for (int j = 0; j < N; j++) {
        const float4* kr = reinterpret_cast<const float4*>(kg + (u0 + j) * 256) + lane;
        v[j][0] = __ldcg(kr); v[j][1] = __ldcg(kr + 32);
      }
      if (N == 2) { z[0] = __ldcg(kg + 2048 + lane); z[1] = __ldcg(kg + 2080 + lane); }
      #pragma unroll
      for (int j = 0; j < N; j++)
        put(KVB_OFF + (rank * 8 + u0 + j) * 640 + lane * 16,
            pack_bf16(v[j][0].x, v[j][0].y), pack_bf16(v[j][0].z, v[j][0].w), pack_bf16(v[j][1].x, v[j][1].y), pack_bf16(v[j][1].z, v[j][1].w));
      if (N == 2) {
        #pragma unroll
        for (int h = 0; h < 2; h++) {
          const uint32_t zz = pack_bf16(z[h], z[h]);
          put(KVB_OFF + (rank * 8 + h * 4 + (lane >> 3)) * 640 + 512 + (lane & 7) * 16, zz, zz, zz, zz);
        }
      }
      fence_async_smem();
      __syncwarp();
      mbar_arrive(bars + B_KVB * 8);
    };
    if (warp == 12) {
      #pragma unroll 1
      for (int it = 0; it < 4; it++) {
        #pragma unroll
        for (int j = 0; j < 4; j++) {
          const uint32_t fb = bars + (B_FULL2 + j) * 8;
          if (j || it) mbar_wait(bars + (it ? B_EMPTY2 + j : B_EMPTY + (j | 1)) * 8, (it - 1) & 1);
          TSTAMP(5, 4 * it + j);
          tma2d_mc(sb + j * SLOT + 16384 + rank * 8192, &mWq, n2 * 128 + rank * 64, it * 256 + j * 64, fb);
          tma2d(sb + j * SLOT, &mX, it * 256 + j * 64, m2 * 128, fb);
          mbar_expect_tx(fb, SLOT);
        }
      }
      mbar_wait(bars + B_MF * 8, 0);
      #pragma unroll 1
      for (int pc = 0; pc < 8; pc++) tma2d(sb + M_OFF + pc * 4096, &mQ, cp * 16, rank * 1024 + pc * 128, bars + B_Q * 8);
      auto load_wo = [&](int st, uint32_t ph) {
        const uint32_t j = st & 3, fb = bars + (B_FULL2 + j) * 8, k = fresh(g2_k(st, n2) * 64);
        mbar_wait(bars + (B_EMPTY2 + j) * 8, ph);
        TSTAMP(5, 16 + st);
        tma2d_mc(sb + j * SLOT + 16384 + rank * 8192, &mWo, n2 * 128 + rank * 64, k, fb);
        mbar_expect_tx(fb, 16384);
      };
      load_wo(4, 1);
      mbar_wait(bars + (B_EMPTY2 + 1) * 8, 1);
      asm volatile(ELECT "cp.async.bulk.tensor.5d.shared::cluster.global.mbarrier::complete_tx::bytes.multicast::cluster [%0], [%1, {%3, %4, %4, %4, %5}], [%2], %6;\n}"
        :: "r"(sb + SLOT + rank * 16384), "l"(&mWp), "r"(bars + (B_FULL2 + 1) * 8), "r"(n2 * 128 + rank * 64), "r"(0), "r"(n2 * 4), "h"((uint16_t)3) : "memory");
      mbar_expect_tx(bars + (B_FULL2 + 1) * 8, SLOT);
      load_wo(2, 1);
      load_wo(3, 1);
      mbar_arrive(bars + B_QE * 8);
      #pragma unroll 1
      for (int it = 1; it < 4; it++) {
        load_wo(4 * it + 1, (it - 1) & 1); load_wo(4 * it + 2, (it - 1) & 1); load_wo(4 * it + 3, (it - 1) & 1);
        if (it < 3) load_wo(4 * it + 4, (it - 1) & 1);
      }
    } else if (warp == 13) {
      if ((sb & 0xffffff) != SB0) __trap();
      float4* zp = reinterpret_cast<float4*>(P.kv + hp * KV_PER_HP + mb * 264);
      const float4 z4 = make_float4(0.f, 0.f, 0.f, 0.f);
      zp[lane] = z4; zp[lane + 32] = z4;
      if (lane < 2) zp[lane + 64] = z4;
      if (lane == 0) P.cnt[hp * 32 + 8 + mb] = t_pf;
      {
        uint4* op = P.o + (m2 * 8 + n2) * 2048 + lane;
        uint32_t t0 = t_pf + RS_T0 + mb * (RS_DT / 8);
        #pragma unroll 1
        for (int i = 0; i < 8; i++) {
          while ((int)((uint32_t)clock() - t0) < 0) __nanosleep(100);
          t0 += RS_DT;
          #pragma unroll
          for (int j = 0; j < 8; j++) op[(i * 8 + j) * 32] = make_uint4(~0u, ~0u, ~0u, ~0u);
        }
      }
      fence_gpu();
      __syncwarp();
      unsigned gen = 0;
      if (lane == 0) gen = (atomicAdd(&P.cnt[hp * 32], 1u) >> 3) + 1;
      gen = uni(gen);
      sts32(sb + D_OFF + 40, gen);
      spin_until(&P.cnt[hp * 32], gen * 8);
      sts32(sb + D_OFF + 48, __ballot_sync(0xffffffffu, (TEST & 4) || __ldcg(&P.cnt[hp * 32 + 8 + (lane & 7)]) - t_pf + 4096 >= 8192));
      mbar_arrive(bars + B_Z * 8);
      reduce_kv(0, 4);
      mbar_arrive(mapa(bars, rank ^ 1) + B_KVL * 8);
      mbar_arrive(bars + B_MF * 8);
      OSTAMP(17);
      fence_gpu();
      red_add(&P.cnt[hp * 32 + 1]);
      OSTAMP(15);
      convert_kv(0, IC<2>());
      bar_sync(6, 288);
      fence_gpu();
      asm volatile(ELECT "st.relaxed.gpu.global.u32 [%0], %1;\n}" :: "l"(&P.cnt[(16 + m2) * 32 + n2]), "r"(gen) : "memory");
      OSTAMP(32);
    } else {
      reduce_kv(warp * 6 - 80, warp * 6 - 74);
      convert_kv(warp * 3 - 40, IC<3>());
      {
        const int wg = 15 - warp;
        const unsigned gen = uni(lds32(sb + D_OFF + 40));
        const uint32_t ab = bars + B_FA * 8 + wg * 32, far = uni(lds32(sb + D_OFF + 48));
        const unsigned* fp = &P.cnt[(32 + m2 * 2 + wg) * 32 + lane];
        uint32_t miss = ~0u, safe = t_pf;
        auto poll = [&]() {
          unsigned v;
          asm volatile("ld.relaxed.gpu.global.u32 %0, [%1];" : "=r"(v) : "l"(fp) : "memory");
          miss = __ballot_sync(0xffffffffu, v != gen);
        };
        mbar_arrive(ab + 8);
        mbar_wait(bars + B_QE * 8, 0);
        #pragma unroll 1
        for (int st = 2; st < 16; st += 2) {
          const int k = g2_k(st, n2), j = st & 3;
          const uint4* src = P.o + (m2 * 16 + k) * 1024 + wg * 512;
          const uint32_t eb = bars + (B_EMPTY2 + j) * 8, ph = ((st >> 2) - 1) & 1, dst = sb + j * SLOT + wg * 8192;
          if ((!(TEST & 2) || st > 6) && ((miss >> (2 * k)) & 15)) {
            #pragma unroll 1
            for (int n = 0; n < WAIT_BOUND && ((miss >> (2 * k)) & 15); n++) poll();
            fence_async_global();
            safe = (uint32_t)clock() + FAR_DT;
          }
          if (st >= 4) {
            if ((far >> (k >> 1)) & 1) while ((int)(uni((uint32_t)clock()) - safe) < 0) {}
            mbar_wait(eb, j ? ph : ph ^ 1);
          }
          bulk_load(dst, src, 8192, ab + j * 8);
          mbar_expect_tx(ab + j * 8, 8192);
          if (st >= 4) mbar_wait(eb + 8, ph);
          bulk_load(dst + SLOT, src + 1024, 8192, ab + j * 8 + 8);
          mbar_expect_tx(ab + j * 8 + 8, 8192);
          if (st == 2) { OSTAMP(18 + wg * 15); if (wg) { sts32(sb + D_OFF + 44, (uint32_t)clock()); mbar_arrive(bars + B_GO * 8); } }
        }
        if (wg + rank + lane == 0) P.cnt[64 * 32 + id2 * 4] = 0;
      }
    }
  } else {
    asm volatile("setmaxnreg.inc.sync.aligned.u32 %0;" :: "n"(160));
    const int wg = warp >> 2;
    Team c;
    c.bars = bars; c.rel = mapa(bars, tid & 1); c.wofs = wg * 8192; c.lead = fresh((tid & 127) < 2);
    uint32_t key = P.one;
    auto gemm2 = [&](float* a, auto O_, auto SK_, auto last) {
      constexpr int O = O_.value, SK = SK_.value;
      static_assert(SK >= 1 && SK <= 3, "tail");
      uint32_t ph = 1;
      const uint32_t ab = bars + B_FA * 8 + wg * 32;
      #pragma unroll 1
      for (int it = 1; it < 4; it++, ph ^= 1) {
        c.wofs += P.one - 1;
        ring_step<false, O>(c, B_FULL2, ph ^ O, B_EMPTY2 + 3, c.lead, [&](auto f) { g2_issue<O, 0, (MID >> (1 + O)) & 1>(a, c, f); }, ab, ph ^ 1);
        if (!O && (tid & 127) == 0) OSTAMP(55 + wg * 4 + it);
        if (O && (tid & 127) == 0) OSTAMP(40 + wg * 4 + it);
        if (SK == 3 && it == 3) break;
        ring_step<false, O>(c, B_FULL2 + 1, ph, B_EMPTY2, (!O || it < 3 ? c.lead : 0), [&](auto f) { g2_issue<O, 1, (MID >> (1 + O)) & 1>(a, c, f); }, ab + 8, ph);
        if (SK == 2 && it == 3) break;
        ring_step<false, O>(c, B_FULL2 + 2, ph, B_EMPTY2 + 1, (!O || it < 3 ? c.lead : 0), [&](auto f) { g2_issue<O, 2, (MID >> (1 + O)) & 1>(a, c, f); }, ab + 16, ph);
        if (SK == 1 && it == 3) break;
        ring_step<false, O>(c, B_FULL2 + 3, ph, B_EMPTY2 + 2, c.lead, [&](auto f) { g2_issue<O, 3, (MID >> (1 + O)) & 1>(a, c, f); }, ab + 24, ph);
      }
      if (!O) {
        auto rel = [&](int jj, bool on) { arrive_at(c.rel + (B_EMPTY2 + jj) * 8, on ? c.lead : 0); };
        if (wg) { wg_wait<0>(); rel(3 - SK, true); mbar_wait(bars + B_SK * 8, 1); }
        auto st = [&](auto J_) {
          constexpr int J = J_.value;
          mbar_wait(bars + (B_FULL2 + J) * 8, 1);
          g2_half<0, J, 0>(a, c);
          wg_wait<1>(); rel(J - 1, J > 4 - SK || !wg);
          g2_half<0, J, 1>(a, c);
          if (J < 3) wg_wait<1>();
        };
        if (SK >= 3) st(IC<1>());
        if (SK >= 2) st(IC<2>());
        st(IC<3>());
        arrive_at(bars + B_SK * 8, fresh_tid() == 0);
        last();
        wg_wait<0>(); rel(3, true);
      } else
      skew_tail<SK>(c, O ^ 1,
        [&]() {
          auto full = [&](int jj) { mbar_wait(bars + (B_FULL2 + jj) * 8, 1); mbar_wait(ab + jj * 8, 1); };
          if (SK >= 3) { full(1); g2_issue<O, 1>(a, c); }
          if (SK >= 2) { full(2); g2_issue<O, 2>(a, c); }
          full(3); g2_issue<O, 3>(a, c);
        },
        [](int) {});
      pinv<64>(a);
    };
    float aq[64];
    {
      float aK[64], aV[64];
      if (wg == 0) { kv_issue<0>(aK, aV, 0, 0); wg_wait<0>(); }
      cluster_wait();
      if (wg == 1) mbar_wait(bars + B_F0 * 8, 0);
      static_assert(SK1 >= 1 && SK1 <= 3, "tail");
      uint32_t ph = 0, xs = 2, xp = 0;
      auto next_x = [&]() { if (xs == 1) xp ^= 1; xs = xs == 2 ? 0 : xs + 1; };
      uint32_t rel = 0;
      int look = 5;
      uint32_t xo = xs * SLOT + wg * 16384;
      #pragma unroll 1
      for (int it = 0; it < 8; it++, ph ^= 1) {
        ring_step<false, true>(c, B_FULL, ph, B_EMPTY + 3, rel, [&](auto f) { kv_issue<0, MID & 1>(aK, aV, xo, it, f); if (tid == 0 && it == 0) OSTAMP(1); }, bars + (B_XF + xs) * 8, xp);
        if (SK1 == 3 && it == 7) break;
        next_x();
        ring_step<false>(c, B_FULL + 1, ph, B_EMPTY, c.lead, [&](auto f) { kv_issue<1, MID & 1>(aK, aV, xo, 1, f); });
        if (SK1 == 2 && it == 7) break;
        xo = xs * SLOT + wg * 16384;
        ring_step<false, true>(c, B_FULL + 2, ph, B_EMPTY + 1, c.lead, [&](auto f) { kv_issue<2, MID & 1>(aK, aV, xo, 1, f); }, bars + (B_XF + xs) * 8, xp);
        if (SK1 == 1 && it == 7) break;
        next_x();
        ring_step<false>(c, B_FULL + 3, ph, B_EMPTY + 2, c.lead, [&](auto f) { kv_issue<3, MID & 1>(aK, aV, xo, 1, f); });
        rel = c.lead;
        xo = xs * SLOT + wg * 16384;
        if (it == look && wrong_job()) { mbar_wait(bars + B_EX * 8, 0); it = look = -1; }
      }
      skew_tail<SK1>(c, 0,
        [&]() {
          auto wait = [&](uint32_t a) { mbar_wait(a, 1); };
          if (SK1 >= 3) { wait(bars + (B_FULL + 1) * 8); kv_issue<1>(aK, aV, SLOT + wg * 16384, 1); }
          if (SK1 >= 2) { wait(bars + (B_FULL + 2) * 8); wait(bars + (B_XF + 2) * 8); kv_issue<2>(aK, aV, 2 * SLOT + wg * 16384, 1); }
          wait(bars + (B_FULL + 3) * 8); kv_issue<3>(aK, aV, 2 * SLOT + wg * 16384, 1);
        },
        [&](int i) { arrive_at(c.rel + (B_EMPTY + ((32 - SK1 + i) & 3)) * 8, c.lead); });
      pinv<64>(aV); pinv<64>(aK);
      if (tid == 128) OSTAMP(3);
      const uint32_t vb = sb + M_OFF + wg * VT;
      float kv[36];
      uint32_t kf[4][8];
      const uint64_t dv = dofs(cdesc(M_OFF, 1152, 128, 0), wg * VT);
      const int t = fresh_tid();
      const uint32_t va = vb + ((t >> 4) & 1) * 1152 + ((t >> 5) & 3) * 256 + (t & 15) * 16;
      mbar_wait(bars + B_X * 8, 0);
      #pragma unroll
      for (int i = 0; i < 8; i++) {
        const float* a = aV + 8 * i;
        stsm4(va + i * 2304, pack_bf16(a[0], a[1]), pack_bf16(a[2], a[3]), pack_bf16(a[4], a[5]), pack_bf16(a[6], a[7]));
      }
      phi_a(aK + 48, kf[3]);
      mbar_wait(bars + B_FULL2 * 8, 0);
      if ((tid & 127) == 0) OSTAMP(50 + wg);
      g2_issue<0, 0, false, true>(aq, c);
      sched_fence(key++);
      sts128(vb + ((t & 127) >> 3) * 1152 + 1024 + (t & 7) * 16, 0x3f803f80u, 0x3f803f80u, 0x3f803f80u, 0x3f803f80u);
      phi_a(aK + 32, kf[2]); phi_b(aK + 48, kf[3]);
      sched_fence(key++);
      ring_step<true>(c, B_FULL2 + 1, 0, B_EMPTY2, c.lead, [&]() { g2_issue<0, 1>(aq, c); });
      sched_fence(key++);
      phi_a(aK + 16, kf[1]); phi_b(aK + 32, kf[2]);
      sched_fence(key++);
      ring_step<true>(c, B_FULL2 + 2, 0, B_EMPTY2 + 1, c.lead, [&]() { g2_issue<0, 2>(aq, c); });
      sched_fence(key++);
      phi_a(aK, kf[0]); phi_b(aK + 16, kf[1]);
      sched_fence(key++);
      fence_async_smem(); bar_sync(1 + wg, 128);
      phi_b(aK, kf[0]);
      sched_fence(key++);
      wg_fence();
      #pragma unroll
      for (int ks = 0; ks < 8; ks++) {
        if (ks == 0) rs72z<0>(kv, kf[0], dv); else rs72a<0>(kv, kf[ks >> 1] + 4 * (ks & 1), dofs(dv, ks * 2304));
      }
      wg_commit();
      wg_wait<1>();
      arrive_at(c.rel + (B_EMPTY2 + 2) * 8, c.lead);
      mbar_wait(bars + (B_FULL2 + 3) * 8, 0);
      g2_issue<0, 3>(aq, c);
      wg_wait<1>();
      pinv<36>(kv);
      const int a = fresh_tid() & 127;
      const bool hi = a >= 64;
      #pragma unroll
      for (int u = 0; u < 4; u++) {
        const int o = (u & 1) * 8 + (u & 2);
        sts128(vb + (a ^ ((a >> 3) & 3)) * 16 + u * 2048, __float_as_uint(hi ? kv[16 + o] : kv[o]), __float_as_uint(hi ? kv[17 + o] : kv[o + 1]),
               __float_as_uint(hi ? kv[20 + o] : kv[o + 4]), __float_as_uint(hi ? kv[21 + o] : kv[o + 5]));
      }
      if ((a & 3) < 2) sts32(vb + 8192 + ((a >> 5) * 16 + ((a & 31) >> 2) + (a & 1) * 8) * 4, __float_as_uint((a & 1) ? kv[34] : kv[32]));
      bar_arrive(4, 352);
    }
    if (tid == 0) OSTAMP(4);
    if (tid == 128) OSTAMP(5);
    float acc[64];
    {
      uint32_t kvok;
      gemm2(aq, IC<0>(), IC<SK2>(), [&]() {
        kvok = mbar_try(bars + B_KVB * 8, 0);
        if (kvok) fence_async_smem();
      });
      if (tid == 0) OSTAMP(6);
      if (tid == 128) OSTAMP(7);
      constexpr uint64_t dk = cdesc(KVB_OFF, 640, 128, 0);
      const uint32_t id2 = job(); IDS(id2);
      float nu[4][20];
      uint32_t pq[4][8], o[4][2][4];
      const int t2 = fresh_tid();
      const uint32_t oo = (t2 & 96) * 32 + (t2 & 28) * 16 + ((t2 ^ (t2 >> 3)) & 3) * 16;
      uint4* og = P.o + ((m2 * 8 + n2) * 4 + wg) * 512 + (oo >> 4);
      auto o_put = [&](int h, int e) {
        asm volatile("st.global.v4.b32 [%0], {%1,%2,%3,%4};" :: "l"(og + (h >> 1) * 1024 + (h & 1) * 256 + e * 32),
          "r"(o[h][e][0]), "r"(o[h][e][1]), "r"(o[h][e][2]), "r"(o[h][e][3]) : "memory");
      };
      auto o_out = [&](int h) {
        pinv<20>(nu[h]);
        #pragma unroll
        for (int e = 0; e < 2; e++) {
          const float* n = nu[h] + 2 * e;
          const float iv = rcp_fast(n[16] + 1e-6f);
          #pragma unroll
          for (int i = 0; i < 4; i++) o[h][e][i] = pack_bf16(n[4 * i] * iv, n[4 * i + 1] * iv);
          o_put(h, e);
        }
      };
      auto o_mma = [&](int h) {
        wg_fence();
        rs40z<1>(nu[h], pq[h], dk + h * (2560 >> 4));
        rs40a<1>(nu[h], pq[h] + 4, dk + h * (2560 >> 4) + (1280 >> 4));
        wg_commit();
      };
      phi_s(aq, pq[0]); phi_e(aq); phi_s(aq + 16, pq[1]);
      if (!kvok) { mbar_wait(bars + B_KVB * 8, 0); fence_async_smem(); }
      const uint32_t gen = lds32(sb + D_OFF + 40), far = lds32(sb + D_OFF + 48);
      #pragma unroll
      for (int u = 0; u < 4; u++) {
        if (u < 3) phi_e(aq + 16 * u + 16);
        phi_b(aq + 16 * u, pq[u]);
        o_mma(u);
        if (u < 2) phi_s(aq + 16 * u + 32, pq[u + 2]);
        if (u > 0) { wg_wait<1>(); o_out(u - 1); }
        sched_fence(key++);
      }
      wg_wait<0>(); o_out(3);
      asm volatile(ELECT "st.relaxed.gpu.global.u32 [%0], %1;\n}" :: "l"(&P.cnt[(32 + m2 * 2 + wg) * 32 + n2 * 4 + (warp & 3)]), "r"(gen) : "memory");
      bar_arrive(6, 288);
      arrive_at(bars + B_OD * 8, t2 == 128);
      if ((t2 & 127) == 0) OSTAMP(8 + wg * 2);
      {
        sched_fence(key++);
        #pragma unroll
        for (int i = 0; i < 32; i++) asm volatile("lop3.b32 %0, %1, %2, 0, 0xf0 | 0xcc;" : "=r"(o[i >> 3][(i >> 2) & 1][i & 3]) : "r"(o[i >> 3][(i >> 2) & 1][i & 3]), "r"(P.one - 1));
      }
      if (wg == 0) mbar_wait(bars + B_OD * 8, 0);
      mbar_wait(bars + (B_FULL2 + 1) * 8, 0);
      wg_fence();
      #pragma unroll
      for (int i = 0; i < 8; i++) {
        const uint32_t f[4] = {o[i >> 1][0][i & 1], o[i >> 1][1][i & 1], o[i >> 1][0][2 + (i & 1)], o[i >> 1][1][2 + (i & 1)]};
        constexpr uint64_t dw = cdesc(SLOT, 16384, 2048, 1);
        if (i == 0) rs128z<1>(acc, f, dw); else rs128a<1>(acc, f, dw + (((i >> 1) * 4096 + (i & 1) * 1024) >> 4));
      }
      wg_commit();
      if ((t2 & 127) == 0) OSTAMP(37 + wg);
      const uint32_t ab = bars + B_FA * 8 + wg * 32;
      const int k2 = g2_k(2, n2);
      const bool doubt = (uni(far) >> (k2 >> 1)) & 1;
      auto look = [&](int j) {
        if (doubt) {
          const uint32_t a = sb + (2 + j) * SLOT + wg * 8192 + (t2 & 96) * 32;
          if (__any_sync(0xffffffffu, lds32(a + (t2 & 16) * 256 + (t2 & 15) * 64 + (t2 & 30) * 2) == ~0u)) {
            const uint4* src = P.o + (m2 * 16 + k2 + j) * 1024 + wg * 512 + (t2 & 96) * 2 + (t2 & 31);
            if ((t2 & 31) == 0) OSTAMP(34);
            #pragma unroll 1
            for (int i = 0; i < 4; i++) {
              uint32_t v[4];
              int n = 0;
              do asm volatile("ld.relaxed.gpu.global.v4.u32 {%0,%1,%2,%3}, [%4];" : "=r"(v[0]), "=r"(v[1]), "=r"(v[2]), "=r"(v[3]) : "l"(src + (i & 1) * 32 + (i >> 1) * 256) : "memory");
              while (__any_sync(0xffffffffu, v[0] == ~0u) && ++n < 64);
              sts128(a + (t2 & 31) * 16 + (i & 1) * 512 + (i >> 1) * 4096, v[0], v[1], v[2], v[3]);
            }
            fence_async_smem();
            __syncwarp();
          }
        }
      };
      ring_step<true, true>(c, B_FULL2 + 2, 0, B_EMPTY2 + 1, c.lead, [&]() { look(0); if ((t2 & 127) == 0) OSTAMP(11 + wg * 24); g2_issue<1, 2>(acc, c); }, ab + 16, 0);
      ring_step<true, true>(c, B_FULL2 + 3, 0, B_EMPTY2 + 2, c.lead, [&]() { look(1); g2_issue<1, 3>(acc, c); }, ab + 24, 0);
    }
    gemm2(acc, IC<1>(), IC<SK3>(), []() {});
    if (tid == 0) OSTAMP(13);
    if (tid == 128) OSTAMP(14);
    {
      const uint32_t id2 = job(); IDS(id2);
      const int t2 = fresh_tid();
      const int row = ((t2 >> 5) & 3) * 16 + (t2 & 15);
      const int cq = (t2 >> 4) & 1, sw = t2 & 7;
      const uint32_t stg = sb + (EHI ? T_OFF : 0) + wg * 8192;
      constexpr uint32_t HS = EHI ? 16384 : SLOT;
      if (EHI) mbar_wait(bars + B_CD * 8, 0);
      #pragma unroll 1
      for (int pass = 0;; pass++) {
      const bool bad = acc[0] != acc[0] || acc[2] != acc[2];
      #pragma unroll
      for (int hf = 0; hf < 2; hf++) {
        #pragma unroll
        for (int jj = 0; jj < 4; jj++) {
          const int o = hf * 32 + jj * 8;
          stsm4(stg + hf * HS + row * 128 + (((2 * jj + cq) ^ sw) << 4),
                pack_bf16(acc[o], acc[o + 1]), pack_bf16(acc[o + 2], acc[o + 3]),
                pack_bf16(acc[o + 4], acc[o + 5]), pack_bf16(acc[o + 6], acc[o + 7]));
        }
        fence_async_smem();
        __syncwarp();
        tma2d_store(&mOut, 1024 + n2 * 128 + hf * 64, m2 * 128 + warp * 16, sb + (EHI ? T_OFF : 0) + hf * HS + warp * 2048);
      }
      bulk_commit();
      uint32_t redo;
      asm volatile("{\n.reg .pred p, q;\nsetp.ne.b32 p, %1, 0;\nbar.red.or.pred q, %2, 128, p;\nselp.u32 %0, 1, 0, q;\n}" : "=r"(redo) : "r"((uint32_t)bad), "r"(1 + wg) : "memory");
      if (!uni(redo) || pass) break;
      if ((t2 & 127) == 0) OSTAMP(48 + wg);
      asm volatile("cp.async.bulk.wait_group 0;" ::: "memory");
      spin_until(&P.cnt[(16 + m2) * 32 + (t2 & 7)], lds32(sb + D_OFF + 40));
      fence_async_global();
      const uint32_t ab = bars + B_FA * 8 + wg * 32;
      #pragma unroll 1
      for (int k = 0; k < 16; k++) {
        bar_sync(1 + wg, 128);
        if ((warp & 3) == 0) {
          mbar_expect_tx(ab, 24576);
          bulk_load(sb + c.wofs, P.o + (m2 * 16 + k) * 1024 + wg * 512, 8192, ab);
          tma2d(sb + SLOT + c.wofs, &mWo, n2 * 128, k * 64, ab);
          tma2d(sb + 2 * SLOT + c.wofs, &mWo, n2 * 128 + 64, k * 64, ab);
        }
        mbar_wait(ab, ~k & 1);
        const uint64_t da = dofs(cdesc(0, 16, 512, 2), c.wofs), db = dofs(cdesc(SLOT, SLOT, 1024, 1), c.wofs);
        wg_fence();
        ss128p<0, 1>(acc, da, db, k);
        ss128a<0, 1>(acc, dofs(da, 32), dofs(db, 2048));
        ss128a<0, 1>(acc, dofs(da, 4096), dofs(db, 4096));
        ss128a<0, 1>(acc, dofs(da, 4128), dofs(db, 6144));
        wg_commit();
        wg_wait<0>(); pinv<64>(acc);
      }
      }
      bulk_wait_read();
    }
  }
}

typedef CUresult (*EncodeFn)(CUtensorMap*, CUtensorMapDataType, cuuint32_t, void*, const cuuint64_t*, const cuuint64_t*,
                             const cuuint32_t*, const cuuint32_t*, CUtensorMapInterleave, CUtensorMapSwizzle,
                             CUtensorMapL2promotion, CUtensorMapFloatOOBfill);

void encode(EncodeFn fn, CUtensorMap* m, const void* ptr, int rank, const cuuint64_t* dims, const cuuint64_t* strides,
            const cuuint32_t* box, CUtensorMapSwizzle sw, CUtensorMapL2promotion pr) {
  const cuuint32_t es[5] = {1, 1, 1, 1, 1};
  fn(m, CU_TENSOR_MAP_DATA_TYPE_BFLOAT16, rank, const_cast<void*>(ptr), dims, strides, box, es,
     CU_TENSOR_MAP_INTERLEAVE_NONE, sw, pr, CU_TENSOR_MAP_FLOAT_OOB_FILL_NONE);
}

}

extern "C" void kernel_launch(void* const* d_in, const int* in_sizes, int n_in, void* d_out, int out_size) {
  (void)in_sizes; (void)n_in; (void)out_size;
  static EncodeFn fn = nullptr;
  static void *po, *pkv, *pcnt;
  if (!fn) {
    void* p = nullptr; cudaDriverEntryPointQueryResult qr;
    cudaGetDriverEntryPoint("cuTensorMapEncodeTiled", &p, cudaEnableDefault, &qr);
    fn = (EncodeFn)p;
    cudaGetSymbolAddress(&po, g_O); cudaGetSymbolAddress(&pkv, g_kv); cudaGetSymbolAddress(&pcnt, g_cnt);
    cudaFuncSetAttribute(fused_kernel, cudaFuncAttributeMaxDynamicSharedMemorySize, SMEM_BYTES);
  }
  const CUtensorMapL2promotion P128 = CU_TENSOR_MAP_L2_PROMOTION_L2_128B, P0 = CU_TENSOR_MAP_L2_PROMOTION_NONE;
  CUtensorMap mX, mW, mWq, mWo, mK, mV, mH, mQ, mOut, mOutA, mWp;
  { cuuint64_t d[2] = {1024, 2048}, s[1] = {2048}; cuuint32_t bx[2] = {64, 128}, bq[2] = {16, 128};
    encode(fn, &mX, d_in[6], 2, d, s, bx, CU_TENSOR_MAP_SWIZZLE_128B, P128);
    encode(fn, &mQ, d_in[0], 2, d, s, bq, CU_TENSOR_MAP_SWIZZLE_NONE, P128); }
  { cuuint64_t d[3] = {1024, 1024, 3}, s[2] = {6144, 2048}; cuuint32_t bx[3] = {64, 32, 2};
    encode(fn, &mW, d_in[7], 3, d, s, bx, CU_TENSOR_MAP_SWIZZLE_128B, P128); }
  { cuuint64_t d[2] = {1024, 1024}, s[1] = {6144}, so[1] = {2048}; cuuint32_t bx[2] = {64, 64};
    encode(fn, &mWq, d_in[7], 2, d, s, bx, CU_TENSOR_MAP_SWIZZLE_128B, P128);
    encode(fn, &mWo, d_in[8], 2, d, so, bx, CU_TENSOR_MAP_SWIZZLE_128B, P128); }
  { cuuint64_t d[5] = {1024, 2, 4, 4, 32}, s[4] = {2048, 16384, 4096, 65536}; cuuint32_t bx[5] = {64, 2, 4, 4, 4};
    encode(fn, &mWp, d_in[8], 5, d, s, bx, CU_TENSOR_MAP_SWIZZLE_128B, P128); }
  { cuuint64_t d[3] = {1024, 128, 16}, s[2] = {32768, 2048}; cuuint32_t bk[3] = {16, 17, 8}, bv[3] = {16, 16, 8};
    encode(fn, &mK, d_in[1], 3, d, s, bk, CU_TENSOR_MAP_SWIZZLE_32B, P128);
    encode(fn, &mV, d_in[2], 3, d, s, bv, CU_TENSOR_MAP_SWIZZLE_32B, P128); }
  { cuuint64_t d[2] = {16, 131072}, s[1] = {32}; cuuint32_t bx[2] = {16, 128};
    encode(fn, &mH, d_in[4], 2, d, s, bx, CU_TENSOR_MAP_SWIZZLE_32B, CU_TENSOR_MAP_L2_PROMOTION_L2_256B); }
  { cuuint64_t d[2] = {2048, 2048}, s[1] = {4096}; cuuint32_t bx[2] = {64, 16}, ba[2] = {16, 32};
    encode(fn, &mOut, d_out, 2, d, s, bx, CU_TENSOR_MAP_SWIZZLE_128B, P0);
    encode(fn, &mOutA, d_out, 2, d, s, ba, CU_TENSOR_MAP_SWIZZLE_NONE, P0); }
  Params P;
  P.shift = (const __nv_bfloat16*)d_in[3]; P.ssmD = (const __nv_bfloat16*)d_in[5];
  P.x = (const __nv_bfloat16*)d_in[6]; P.w = (const __nv_bfloat16*)d_in[7]; P.out = (__nv_bfloat16*)d_out; P.one = 1;
  P.o = (uint4*)po; P.kv = (float*)pkv; P.cnt = (unsigned*)pcnt;
  P.k = (const char*)d_in[1]; P.v = (const char*)d_in[2];
  P.pt[0] = {(const char*)d_in[6], 16 * 32768, 64 * 32768, 65536, 32768, 256, 4096, 2048};
  P.pt[1] = {(const char*)d_in[7] + 2048, 256, 1024, 16 * 6144, 8 * 6144, 128 * 6144, 6144, 2048};
  P.pt[2] = {(const char*)d_in[7], 512, 128 * 6144, 16 * 6144, 8 * 6144, 256 * 6144, 6144, 256};
  P.pt[3] = {(const char*)d_in[8], 512, 128 * 2048, 16 * 2048, 8 * 2048, 256 * 2048, 2048, 256};
  P.pt[4] = {(const char*)d_in[0], 256, 1024, 32768, 2097152, 262144, 4096, 2048};
  P.pt[5] = {(const char*)d_in[4], 16 * 32768, 64 * 32768, 65536, 32768, 4096, 512, 256};
  const uint8_t pf[32] = {PF_LIST};
  for (int i = 0; i < 32; i++) P.pf[i] = pf[i];
  const uint64_t cd[18] = {CONV_DESC};
  for (int i = 0; i < 18; i++) P.cd[i] = cd[i];
  fused_kernel<<<NCTA, NTHREADS, SMEM_BYTES, cudaStreamPerThread>>>(P, mX, mW, mWq, mWo, mK, mV, mH, mQ, mOut, mOutA, mWp);
}
```

```cpp
#include <cuda_runtime.h>
#include <cuda_bf16.h>
#include <cuda.h>
#include <stdint.h>

#define PARAM(name, value) constexpr int name = value
#define TUNE
namespace dflt {
PARAM(SK1, 2); PARAM(SK2, 3); PARAM(SK3, 3);
PARAM(MID, 3);
PARAM(STG_T0, 700); PARAM(STG_DT, 540);
PARAM(RS_T0, 12000); PARAM(RS_DT, 600);
PARAM(FAR_DT, 500);
PARAM(OA_END, 7400); PARAM(OA_MIN, 200); PARAM(OA_MAX, 450);
PARAM(PF_DT0, 400); PARAM(PF_DT1, 1100); PARAM(PF_DT2, 540); PARAM(PF_N1, 9);
PARAM(TEST, 0);
PARAM(EHI, 1); PARAM(FG, 2); PARAM(CI, 1); PARAM(CW, 2);
}
#define PF_LIST 0x01, 0x11, 0x02, 0x12, 0x03, 0x13, 0x04, 0x14, 0x05, 0x15, 0x51, 0x06, 0x16, 0x20, 0x07, 0x17, 0x21, 0x22, 0x23, \
                0x40, 0x41, 0x42, 0x43, 0x44, 0x45, 0x46, 0x47, 0x30, 0x31, 0x32, 0x33
#define PF_N 31
#define WAIT_BOUND 262144

namespace {
using namespace dflt;
TUNE

constexpr int S_LEN = 2048;
constexpr int DM    = 1024;
constexpr int NCTA  = 128;
constexpr int NTHREADS = 512;
constexpr int SLOT  = 32768;
constexpr int W_OFF = 3 * SLOT;
constexpr int M_OFF = 4 * SLOT;
constexpr int VT    = 16 * 1152;
constexpr int T_OFF = M_OFF + 43008;
constexpr int XS    = 4096 + 16;
constexpr int YX    = 2048 + 16;
constexpr int X_OFF = T_OFF + 8192 + 2176;
constexpr int H_OFF = X_OFF + 8 * XS;
constexpr int A_OFF = H_OFF + 4096;
constexpr int F_OFF = A_OFF + 8192;
constexpr int BAR_OFF = F_OFF + 2048;
constexpr int D_OFF = BAR_OFF + 384;
constexpr int SMEM_BYTES = D_OFF + 64 + 256;
constexpr int KB = 8704;
constexpr int KVB_OFF = M_OFF + 32768;
static_assert(H_OFF % 256 == 0 && X_OFF % 128 == 0 && SMEM_BYTES <= 232448, "layout");
constexpr int B_XF = 0, B_F0 = 3, B_FULL = 4, B_FA = 4, B_FULL2 = 25, B_KVL = 24, B_STG = 8, B_X = 12, B_Z = 13, B_H = 14, B_Q = 15, B_YR = 16,
              B_SK = 29, B_GO = 30, B_QE = 31,
              B_EMPTY = 32, B_KVB = 36, B_EMPTY2 = 37, B_SFREE = 41, B_CD = 43, B_MF = 44, B_OD = 45, B_EX = 46;
constexpr int KV_PER_HP = 2 * 1056;

__device__ __align__(1024) uint4 g_O[S_LEN * DM / 8];
__device__ __align__(128) float g_kv[16 * KV_PER_HP];
__device__ __align__(128) unsigned g_cnt[81 * 32];

#define OSTAMP(i) do {} while (0)
#define TSTAMP(k, i) do {} while (0)

__device__ __forceinline__ uint32_t wanted_job() {
  uint32_t t;
  asm volatile("mov.u32 %0, %%smid;" : "=r"(t));
  if (TEST & 1) t = t * 3 % 100;
  t >>= 1;
  const uint32_t q = ((t - 32) * 37) >> 8;
  uint32_t r;
  asm("{\n.reg .pred p, q;\nsetp.lt.u32 p, %3, 32;\nsetp.lt.u32 q, %3, 62;\nselp.u32 %0, %1, %2, q;\nselp.u32 %0, %3, %0, p;\n}" : "=&r"(r) : "r"(t + 1 + q), "r"((t - 58) * 8), "r"(t));
  return (r & 7) | ((((r & 7 ? 0x76154032 : 0x76543012) >> ((r >> 1) & 28)) & 7) << 3);
}

#define ELECT "{\n.reg .pred e;\nelect.sync _|e, 0xffffffff;\n@e "
__device__ __forceinline__ uint32_t uni(uint32_t v) { return __shfl_sync(0xffffffffu, v, 0); }
__device__ __forceinline__ uint32_t fresh(uint32_t v) { asm volatile("" : "+r"(v)); return v; }
__device__ __forceinline__ uint32_t smem_u32(const void* p) { return (uint32_t)__cvta_generic_to_shared(p); }
__device__ __forceinline__ void mbar_init(uint32_t b, uint32_t c) { asm volatile(ELECT "mbarrier.init.shared::cta.b64 [%0], %1;\n}" :: "r"(b), "r"(c) : "memory"); }
__device__ __forceinline__ void mbar_expect_tx(uint32_t b, uint32_t bytes) { asm volatile(ELECT "mbarrier.arrive.expect_tx.shared::cta.b64 _, [%0], %1;\n}" :: "r"(b), "r"(bytes) : "memory"); }
__device__ __forceinline__ void mbar_arrive(uint32_t b) { asm volatile(ELECT "mbarrier.arrive.shared::cluster.b64 _, [%0];\n}" :: "r"(b) : "memory"); }
__device__ __forceinline__ void mbar_wait(uint32_t b, uint32_t ph) {
  asm volatile("{\n.reg .pred p;\nWAIT_LOOP:\nmbarrier.try_wait.parity.shared::cta.b64 p, [%0], %1;\n@!p bra.uni WAIT_LOOP;\n}" :: "r"(b), "r"(ph) : "memory");
}
__device__ __forceinline__ void tma2d(uint32_t dst, const CUtensorMap* m, int c0, int c1, uint32_t bar) {
  asm volatile(ELECT "cp.async.bulk.tensor.2d.shared::cluster.global.mbarrier::complete_tx::bytes [%0], [%1, {%3, %4}], [%2];\n}"
    :: "r"(dst), "l"(m), "r"(bar), "r"(c0), "r"(c1) : "memory"); }
__device__ __forceinline__ void tma2d_mc(uint32_t dst, const CUtensorMap* m, int c0, int c1, uint32_t bar) {
  asm volatile(ELECT "cp.async.bulk.tensor.2d.shared::cluster.global.mbarrier::complete_tx::bytes.multicast::cluster [%0], [%1, {%3, %4}], [%2], %5;\n}"
    :: "r"(dst), "l"(m), "r"(bar), "r"(c0), "r"(c1), "h"((uint16_t)3) : "memory"); }
__device__ __forceinline__ void tma3d(uint32_t dst, const CUtensorMap* m, int c0, int c1, int c2, uint32_t bar) {
  asm volatile(ELECT "cp.async.bulk.tensor.3d.shared::cluster.global.mbarrier::complete_tx::bytes [%0], [%1, {%3, %4, %5}], [%2];\n}"
    :: "r"(dst), "l"(m), "r"(bar), "r"(c0), "r"(c1), "r"(c2) : "memory"); }
__device__ __forceinline__ void tma2d_store(const CUtensorMap* m, int c0, int c1, uint32_t src) {
  asm volatile(ELECT "cp.async.bulk.tensor.2d.global.shared::cta.bulk_group [%0, {%2, %3}], [%1];\n}"
    :: "l"(m), "r"(src), "r"(c0), "r"(c1) : "memory"); }
__device__ __forceinline__ void bulk_load(uint32_t dst, const void* src, uint32_t bytes, uint32_t bar) {
  asm volatile(ELECT "cp.async.bulk.shared::cluster.global.mbarrier::complete_tx::bytes [%0], [%1], %2, [%3];\n}"
    :: "r"(dst), "l"(src), "r"(bytes), "r"(bar) : "memory"); }
__device__ __forceinline__ void bulk_commit() { asm volatile("cp.async.bulk.commit_group;" ::: "memory"); }
__device__ __forceinline__ void bulk_wait_read() { asm volatile("cp.async.bulk.wait_group.read 0;" ::: "memory"); }
__device__ __forceinline__ void fence_async_smem() { asm volatile("fence.proxy.async.shared::cta;" ::: "memory"); }
__device__ __forceinline__ void bar_sync(int id, int n) { asm volatile("bar.sync %0, %1;" :: "r"(id), "r"(n) : "memory"); }
__device__ __forceinline__ void bar_arrive(int id, int n) { asm volatile("bar.arrive %0, %1;" :: "r"(id), "r"(n) : "memory"); }
__device__ __forceinline__ void wg_fence() { asm volatile("wgmma.fence.sync.aligned;" ::: "memory"); }
__device__ __forceinline__ void wg_commit() { asm volatile("wgmma.commit_group.sync.aligned;" ::: "memory"); }
template <int N> __device__ __forceinline__ void wg_wait() { asm volatile("wgmma.wait_group.sync.aligned %0;" :: "n"(N) : "memory"); }
constexpr uint32_t SB0 = 1024;
__host__ __device__ constexpr uint64_t cdesc(uint32_t off, uint32_t lbo, uint32_t sbo, uint32_t swz) {
  return (uint64_t)((SB0 + off) >> 4) | ((uint64_t)(lbo >> 4) << 16) | ((uint64_t)(sbo >> 4) << 32) | ((uint64_t)swz << 62); }
__device__ __forceinline__ uint64_t dofs(uint64_t d, uint32_t bytes) { return (d & 0xffffffff00000000ull) | (uint32_t)((uint32_t)d + (bytes >> 4)); }
__device__ __forceinline__ uint32_t mbar_try(uint32_t b, uint32_t ph) {
  uint32_t ok;
  asm volatile("{\n.reg .pred p;\nmbarrier.test_wait.parity.shared::cta.b64 p, [%1], %2;\nselp.u32 %0, 1, 0, p;\n}" : "=r"(ok) : "r"(b), "r"(ph) : "memory");
  return ok; }
__device__ __forceinline__ void arrive_at(uint32_t a, uint32_t on) {
  asm volatile("{\n.reg .pred p;\nsetp.ne.b32 p, %1, 0;\n@p mbarrier.arrive.shared::cluster.b64 _, [%0];\n}" :: "r"(a), "r"(on) : "memory"); }
__device__ __forceinline__ void ldsm4(uint32_t* r, uint32_t a) {
  asm volatile("ldmatrix.sync.aligned.m8n8.x4.shared.b16 {%0,%1,%2,%3}, [%4];" : "=r"(r[0]), "=r"(r[1]), "=r"(r[2]), "=r"(r[3]) : "r"(a) : "memory"); }
__device__ __forceinline__ void ldsm4t(uint32_t* r, uint32_t a) {
  asm volatile("ldmatrix.sync.aligned.m8n8.x4.trans.shared.b16 {%0,%1,%2,%3}, [%4];" : "=r"(r[0]), "=r"(r[1]), "=r"(r[2]), "=r"(r[3]) : "r"(a) : "memory"); }
__device__ __forceinline__ void stsm4(uint32_t a, uint32_t r0, uint32_t r1, uint32_t r2, uint32_t r3) {
  asm volatile("stmatrix.sync.aligned.m8n8.x4.shared.b16 [%0], {%1,%2,%3,%4};" :: "r"(a), "r"(r0), "r"(r1), "r"(r2), "r"(r3) : "memory"); }
__device__ __forceinline__ void stsm4t(uint32_t a, uint32_t r0, uint32_t r1, uint32_t r2, uint32_t r3) {
  asm volatile("stmatrix.sync.aligned.m8n8.x4.trans.shared.b16 [%0], {%1,%2,%3,%4};" :: "r"(a), "r"(r0), "r"(r1), "r"(r2), "r"(r3) : "memory"); }
__device__ __forceinline__ uint32_t lds32(uint32_t a) { uint32_t v; asm volatile("ld.shared.b32 %0, [%1];" : "=r"(v) : "r"(a) : "memory"); return v; }
__device__ __forceinline__ void lds128(uint32_t* v, uint32_t a) { asm volatile("ld.shared.v4.b32 {%0,%1,%2,%3}, [%4];" : "=r"(v[0]), "=r"(v[1]), "=r"(v[2]), "=r"(v[3]) : "r"(a) : "memory"); }
__device__ __forceinline__ void sts32(uint32_t a, uint32_t v) { asm volatile("st.shared.b32 [%0], %1;" :: "r"(a), "r"(v) : "memory"); }
__device__ __forceinline__ void sts128(uint32_t a, uint32_t v0, uint32_t v1, uint32_t v2, uint32_t v3) {
  asm volatile("st.shared.v4.b32 [%0], {%1,%2,%3,%4};" :: "r"(a), "r"(v0), "r"(v1), "r"(v2), "r"(v3) : "memory"); }
__device__ __forceinline__ uint32_t pack_bf16(float lo, float hi) { uint32_t r; asm("cvt.rn.bf16x2.f32 %0, %1, %2;" : "=r"(r) : "f"(hi), "f"(lo)); return r; }
template <int ID = 0> __device__ __forceinline__ void sched_fence(uint32_t key) {
  asm volatile("{\n.reg .pred p;\nsetp.eq.u32 p, %0, %1;\nSF_LOOP:\n@p pmevent 1;\n@p bra.uni SF_LOOP;\n}" :: "r"(key), "n"(ID) : "memory");
}
template <int N> __device__ __forceinline__ void pinv(float* v) {
  #pragma unroll
  for (int i = 0; i < N; i++) asm volatile("" : "+f"(v[i]) :: "memory"); }
__device__ __forceinline__ uint32_t bmul2(uint32_t a, uint32_t b) { uint32_t r; asm("mul.rn.bf16x2 %0, %1, %2;" : "=r"(r) : "r"(a), "r"(b)); return r; }
__device__ __forceinline__ uint32_t badd2(uint32_t a, uint32_t b) { uint32_t r; asm("add.rn.bf16x2 %0, %1, %2;" : "=r"(r) : "r"(a), "r"(b)); return r; }
__device__ __forceinline__ void spin_until(const unsigned* p, unsigned target) {
  int n = 0;
  unsigned v;
  do { asm volatile("ld.relaxed.gpu.global.u32 %0, [%1];" : "=r"(v) : "l"(p) : "memory"); } while ((int)(v - target) < 0 && ++n < WAIT_BOUND);
  asm volatile("fence.acquire.gpu;" ::: "memory");
}
__device__ __forceinline__ void cluster_wait() { asm volatile("barrier.cluster.wait.aligned;" ::: "memory"); }
__device__ __forceinline__ void fence_gpu() { asm volatile("fence.release.gpu;" ::: "memory"); }
__device__ __forceinline__ void fence_async_global() { asm volatile("fence.proxy.async.global;" ::: "memory"); }
__device__ __forceinline__ void red_add(unsigned* p) { asm volatile(ELECT "red.relaxed.gpu.global.add.u32 [%0], 1;\n}" :: "l"(p) : "memory"); }
__device__ __forceinline__ float rcp_fast(float x) { float r; asm("rcp.approx.ftz.f32 %0, %1;" : "=f"(r) : "f"(x)); return r; }
__device__ __forceinline__ uint32_t mapa(uint32_t a, uint32_t rank) { uint32_t r; asm("mapa.shared::cluster.u32 %0, %1, %2;" : "=r"(r) : "r"(a), "r"(rank)); return r; }
__device__ __forceinline__ void st_async128(uint32_t a, uint32_t bar, uint32_t v0, uint32_t v1, uint32_t v2, uint32_t v3) {
  asm volatile("st.async.weak.shared::cluster.mbarrier::complete_tx::bytes.v4.b32 [%0], {%2,%3,%4,%5}, [%1];"
    :: "r"(a), "r"(bar), "r"(v0), "r"(v1), "r"(v2), "r"(v3) : "memory"); }
__device__ __forceinline__ int fresh_tid() { int t; asm volatile("mov.u32 %0, %%tid.x;" : "=r"(t)); return t; }
__device__ __forceinline__ void pace(uint32_t& t, uint32_t dt) {
  uint32_t c;
  while ((int)((c = uni((uint32_t)clock())) - t) < 0) __nanosleep(40);
  t = ((int)(c - t) > (int)dt ? c : t) + dt;
}
template <int LOG> __device__ __forceinline__ void unit_root(int a, float& c, float& s) {
  const float x = (float)((a << (32 - LOG)) >> (32 - LOG)) * (6.283185307179586f / (1 << LOG));
  c = __cosf(x); s = __sinf(x); }

struct D2 { uint64_t a, b; };
template <int TA, int TB> __device__ __forceinline__ void ss128p(float* d, uint64_t da, uint64_t db, int sd) {
  asm volatile("{\n.reg .pred p;\nsetp.ne.b32 p, %68, 0;\n"
    "wgmma.mma_async.sync.aligned.m64n128k16.f32.bf16.bf16 "
    "{%0, %1, %2, %3, %4, %5, %6, %7, %8, %9, %10, %11, %12, %13, %14, %15, "
    "%16, %17, %18, %19, %20, %21, %22, %23, %24, %25, %26, %27, %28, %29, %30, %31, "
    "%32, %33, %34, %35, %36, %37, %38, %39, %40, %41, %42, %43, %44, %45, %46, %47, "
    "%48, %49, %50, %51, %52, %53, %54, %55, %56, %57, %58, %59, %60, %61, %62, %63}, %64, %65, p, 1, 1, %66, %67;\n}\n"
    : "+f"(d[0]), "+f"(d[1]), "+f"(d[2]), "+f"(d[3]), "+f"(d[4]), "+f"(d[5]), "+f"(d[6]), "+f"(d[7]),
      "+f"(d[8]), "+f"(d[9]), "+f"(d[10]), "+f"(d[11]), "+f"(d[12]), "+f"(d[13]), "+f"(d[14]), "+f"(d[15]),
      "+f"(d[16]), "+f"(d[17]), "+f"(d[18]), "+f"(d[19]), "+f"(d[20]), "+f"(d[21]), "+f"(d[22]), "+f"(d[23]),
      "+f"(d[24]), "+f"(d[25]), "+f"(d[26]), "+f"(d[27]), "+f"(d[28]), "+f"(d[29]), "+f"(d[30]), "+f"(d[31]),
      "+f"(d[32]), "+f"(d[33]), "+f"(d[34]), "+f"(d[35]), "+f"(d[36]), "+f"(d[37]), "+f"(d[38]), "+f"(d[39]),
      "+f"(d[40]), "+f"(d[41]), "+f"(d[42]), "+f"(d[43]), "+f"(d[44]), "+f"(d[45]), "+f"(d[46]), "+f"(d[47]),
      "+f"(d[48]), "+f"(d[49]), "+f"(d[50]), "+f"(d[51]), "+f"(d[52]), "+f"(d[53]), "+f"(d[54]), "+f"(d[55]),
      "+f"(d[56]), "+f"(d[57]), "+f"(d[58]), "+f"(d[59]), "+f"(d[60]), "+f"(d[61]), "+f"(d[62]), "+f"(d[63])
    : "l"(da), "l"(db), "n"(TA), "n"(TB), "r"(sd));
}
template <int TA, int TB> __device__ __forceinline__ void ss128a(float* d, uint64_t da, uint64_t db) {
  asm volatile("{\n.reg .pred p;\nsetp.eq.b32 p, 0, 0;\n"
    "wgmma.mma_async.sync.aligned.m64n128k16.f32.bf16.bf16 "
    "{%0, %1, %2, %3, %4, %5, %6, %7, %8, %9, %10, %11, %12, %13, %14, %15, "
    "%16, %17, %18, %19, %20, %21, %22, %23, %24, %25, %26, %27, %28, %29, %30, %31, "
    "%32, %33, %34, %35, %36, %37, %38, %39, %40, %41, %42, %43, %44, %45, %46, %47, "
    "%48, %49, %50, %51, %52, %53, %54, %55, %56, %57, %58, %59, %60, %61, %62, %63}, %64, %65, p, 1, 1, %66, %67;\n}\n"
    : "+f"(d[0]), "+f"(d[1]), "+f"(d[2]), "+f"(d[3]), "+f"(d[4]), "+f"(d[5]), "+f"(d[6]), "+f"(d[7]),
      "+f"(d[8]), "+f"(d[9]), "+f"(d[10]), "+f"(d[11]), "+f"(d[12]), "+f"(d[13]), "+f"(d[14]), "+f"(d[15]),
      "+f"(d[16]), "+f"(d[17]), "+f"(d[18]), "+f"(d[19]), "+f"(d[20]), "+f"(d[21]), "+f"(d[22]), "+f"(d[23]),
      "+f"(d[24]), "+f"(d[25]), "+f"(d[26]), "+f"(d[27]), "+f"(d[28]), "+f"(d[29]), "+f"(d[30]), "+f"(d[31]),
      "+f"(d[32]), "+f"(d[33]), "+f"(d[34]), "+f"(d[35]), "+f"(d[36]), "+f"(d[37]), "+f"(d[38]), "+f"(d[39]),
      "+f"(d[40]), "+f"(d[41]), "+f"(d[42]), "+f"(d[43]), "+f"(d[44]), "+f"(d[45]), "+f"(d[46]), "+f"(d[47]),
      "+f"(d[48]), "+f"(d[49]), "+f"(d[50]), "+f"(d[51]), "+f"(d[52]), "+f"(d[53]), "+f"(d[54]), "+f"(d[55]),
      "+f"(d[56]), "+f"(d[57]), "+f"(d[58]), "+f"(d[59]), "+f"(d[60]), "+f"(d[61]), "+f"(d[62]), "+f"(d[63])
    : "l"(da), "l"(db), "n"(TA), "n"(TB));
}
template <int TA, int TB> __device__ __forceinline__ void ss128z(float* d, uint64_t da, uint64_t db) {
  asm volatile("{\n.reg .pred p;\nsetp.ne.b32 p, 0, 0;\n"
    "wgmma.mma_async.sync.aligned.m64n128k16.f32.bf16.bf16 "
    "{%0, %1, %2, %3, %4, %5, %6, %7, %8, %9, %10, %11, %12, %13, %14, %15, "
    "%16, %17, %18, %19, %20, %21, %22, %23, %24, %25, %26, %27, %28, %29, %30, %31, "
    "%32, %33, %34, %35, %36, %37, %38, %39, %40, %41, %42, %43, %44, %45, %46, %47, "
    "%48, %49, %50, %51, %52, %53, %54, %55, %56, %57, %58, %59, %60, %61, %62, %63}, %64, %65, p, 1, 1, %66, %67;\n}\n"
    : "=f"(d[0]), "=f"(d[1]), "=f"(d[2]), "=f"(d[3]), "=f"(d[4]), "=f"(d[5]), "=f"(d[6]), "=f"(d[7]),
      "=f"(d[8]), "=f"(d[9]), "=f"(d[10]), "=f"(d[11]), "=f"(d[12]), "=f"(d[13]), "=f"(d[14]), "=f"(d[15]),
      "=f"(d[16]), "=f"(d[17]), "=f"(d[18]), "=f"(d[19]), "=f"(d[20]), "=f"(d[21]), "=f"(d[22]), "=f"(d[23]),
      "=f"(d[24]), "=f"(d[25]), "=f"(d[26]), "=f"(d[27]), "=f"(d[28]), "=f"(d[29]), "=f"(d[30]), "=f"(d[31]),
      "=f"(d[32]), "=f"(d[33]), "=f"(d[34]), "=f"(d[35]), "=f"(d[36]), "=f"(d[37]), "=f"(d[38]), "=f"(d[39]),
      "=f"(d[40]), "=f"(d[41]), "=f"(d[42]), "=f"(d[43]), "=f"(d[44]), "=f"(d[45]), "=f"(d[46]), "=f"(d[47]),
      "=f"(d[48]), "=f"(d[49]), "=f"(d[50]), "=f"(d[51]), "=f"(d[52]), "=f"(d[53]), "=f"(d[54]), "=f"(d[55]),
      "=f"(d[56]), "=f"(d[57]), "=f"(d[58]), "=f"(d[59]), "=f"(d[60]), "=f"(d[61]), "=f"(d[62]), "=f"(d[63])
    : "l"(da), "l"(db), "n"(TA), "n"(TB));
}
template <int TA, int TB> __device__ __forceinline__ void ss64a(float* d, uint64_t da, uint64_t db) {
  asm volatile("{\n.reg .pred p;\nsetp.eq.b32 p, 0, 0;\n"
    "wgmma.mma_async.sync.aligned.m64n64k16.f32.bf16.bf16 "
    "{%0, %1, %2, %3, %4, %5, %6, %7, %8, %9, %10, %11, %12, %13, %14, %15, "
    "%16, %17, %18, %19, %20, %21, %22, %23, %24, %25, %26, %27, %28, %29, %30, %31}, %32, %33, p, 1, 1, %34, %35;\n}\n"
    : "+f"(d[0]), "+f"(d[1]), "+f"(d[2]), "+f"(d[3]), "+f"(d[4]), "+f"(d[5]), "+f"(d[6]), "+f"(d[7]),
      "+f"(d[8]), "+f"(d[9]), "+f"(d[10]), "+f"(d[11]), "+f"(d[12]), "+f"(d[13]), "+f"(d[14]), "+f"(d[15]),
      "+f"(d[16]), "+f"(d[17]), "+f"(d[18]), "+f"(d[19]), "+f"(d[20]), "+f"(d[21]), "+f"(d[22]), "+f"(d[23]),
      "+f"(d[24]), "+f"(d[25]), "+f"(d[26]), "+f"(d[27]), "+f"(d[28]), "+f"(d[29]), "+f"(d[30]), "+f"(d[31])
    : "l"(da), "l"(db), "n"(TA), "n"(TB));
}
template <int TA, int TB> __device__ __forceinline__ void ss64z(float* d, uint64_t da, uint64_t db) {
  asm volatile("{\n.reg .pred p;\nsetp.ne.b32 p, 0, 0;\n"
    "wgmma.mma_async.sync.aligned.m64n64k16.f32.bf16.bf16 "
    "{%0, %1, %2, %3, %4, %5, %6, %7, %8, %9, %10, %11, %12, %13, %14, %15, "
    "%16, %17, %18, %19, %20, %21, %22, %23, %24, %25, %26, %27, %28, %29, %30, %31}, %32, %33, p, 1, 1, %34, %35;\n}\n"
    : "=f"(d[0]), "=f"(d[1]), "=f"(d[2]), "=f"(d[3]), "=f"(d[4]), "=f"(d[5]), "=f"(d[6]), "=f"(d[7]),
      "=f"(d[8]), "=f"(d[9]), "=f"(d[10]), "=f"(d[11]), "=f"(d[12]), "=f"(d[13]), "=f"(d[14]), "=f"(d[15]),
      "=f"(d[16]), "=f"(d[17]), "=f"(d[18]), "=f"(d[19]), "=f"(d[20]), "=f"(d[21]), "=f"(d[22]), "=f"(d[23]),
      "=f"(d[24]), "=f"(d[25]), "=f"(d[26]), "=f"(d[27]), "=f"(d[28]), "=f"(d[29]), "=f"(d[30]), "=f"(d[31])
    : "l"(da), "l"(db), "n"(TA), "n"(TB));
}
__device__ __forceinline__ void ss64x4(float* d, const D2* c, int on) {
  asm volatile("{\n.reg .pred p, z, c;\nsetp.eq.b32 p, 0, 0;\nsetp.ne.b32 z, 0, 0;\nsetp.eq.b32 c, %40, 0;\n"
    "wgmma.mma_async.sync.aligned.m64n64k16.f32.bf16.bf16 "
    "{%0, %1, %2, %3, %4, %5, %6, %7, %8, %9, %10, %11, %12, %13, %14, %15, "
    "%16, %17, %18, %19, %20, %21, %22, %23, %24, %25, %26, %27, %28, %29, %30, %31}, %32, %33, z, 1, 1, 0, 1;\n"
    "wgmma.commit_group.sync.aligned;\n@c bra.uni X4_DONE;\n"
    "wgmma.mma_async.sync.aligned.m64n64k16.f32.bf16.bf16 "
    "{%0, %1, %2, %3, %4, %5, %6, %7, %8, %9, %10, %11, %12, %13, %14, %15, "
    "%16, %17, %18, %19, %20, %21, %22, %23, %24, %25, %26, %27, %28, %29, %30, %31}, %34, %35, p, 1, 1, 0, 1;\n"
    "wgmma.mma_async.sync.aligned.m64n64k16.f32.bf16.bf16 "
    "{%0, %1, %2, %3, %4, %5, %6, %7, %8, %9, %10, %11, %12, %13, %14, %15, "
    "%16, %17, %18, %19, %20, %21, %22, %23, %24, %25, %26, %27, %28, %29, %30, %31}, %36, %37, p, 1, 1, 0, 1;\n"
    "wgmma.mma_async.sync.aligned.m64n64k16.f32.bf16.bf16 "
    "{%0, %1, %2, %3, %4, %5, %6, %7, %8, %9, %10, %11, %12, %13, %14, %15, "
    "%16, %17, %18, %19, %20, %21, %22, %23, %24, %25, %26, %27, %28, %29, %30, %31}, %38, %39, p, 1, 1, 0, 1;\n"
    "wgmma.commit_group.sync.aligned;\nX4_DONE:\n}\n"
    : "=f"(d[0]), "=f"(d[1]), "=f"(d[2]), "=f"(d[3]), "=f"(d[4]), "=f"(d[5]), "=f"(d[6]), "=f"(d[7]),
      "=f"(d[8]), "=f"(d[9]), "=f"(d[10]), "=f"(d[11]), "=f"(d[12]), "=f"(d[13]), "=f"(d[14]), "=f"(d[15]),
      "=f"(d[16]), "=f"(d[17]), "=f"(d[18]), "=f"(d[19]), "=f"(d[20]), "=f"(d[21]), "=f"(d[22]), "=f"(d[23]),
      "=f"(d[24]), "=f"(d[25]), "=f"(d[26]), "=f"(d[27]), "=f"(d[28]), "=f"(d[29]), "=f"(d[30]), "=f"(d[31])
    : "l"(c[0].a), "l"(c[0].b), "l"(c[1].a), "l"(c[1].b), "l"(c[2].a), "l"(c[2].b), "l"(c[3].a), "l"(c[3].b), "r"(on));
}
template <int TB> __device__ __forceinline__ void rs32a(float* d, const uint32_t* a, uint64_t db) {
  asm volatile("{\n.reg .pred p;\nsetp.eq.b32 p, 0, 0;\n"
    "wgmma.mma_async.sync.aligned.m64n32k16.f32.bf16.bf16 "
    "{%0, %1, %2, %3, %4, %5, %6, %7, %8, %9, %10, %11, %12, %13, %14, %15}, {%16, %17, %18, %19}, %20, p, 1, 1, %21;\n}\n"
    : "+f"(d[0]), "+f"(d[1]), "+f"(d[2]), "+f"(d[3]), "+f"(d[4]), "+f"(d[5]), "+f"(d[6]), "+f"(d[7]),
      "+f"(d[8]), "+f"(d[9]), "+f"(d[10]), "+f"(d[11]), "+f"(d[12]), "+f"(d[13]), "+f"(d[14]), "+f"(d[15])
    : "r"(a[0]), "r"(a[1]), "r"(a[2]), "r"(a[3]), "l"(db), "n"(TB));
}
template <int TB> __device__ __forceinline__ void rs32z(float* d, const uint32_t* a, uint64_t db) {
  asm volatile("{\n.reg .pred p;\nsetp.ne.b32 p, 0, 0;\n"
    "wgmma.mma_async.sync.aligned.m64n32k16.f32.bf16.bf16 "
    "{%0, %1, %2, %3, %4, %5, %6, %7, %8, %9, %10, %11, %12, %13, %14, %15}, {%16, %17, %18, %19}, %20, p, 1, 1, %21;\n}\n"
    : "=&f"(d[0]), "=&f"(d[1]), "=&f"(d[2]), "=&f"(d[3]), "=&f"(d[4]), "=&f"(d[5]), "=&f"(d[6]), "=&f"(d[7]),
      "=&f"(d[8]), "=&f"(d[9]), "=&f"(d[10]), "=&f"(d[11]), "=&f"(d[12]), "=&f"(d[13]), "=&f"(d[14]), "=&f"(d[15])
    : "r"(a[0]), "r"(a[1]), "r"(a[2]), "r"(a[3]), "l"(db), "n"(TB));
}
template <int TB> __device__ __forceinline__ void rs40a(float* d, const uint32_t* a, uint64_t db) {
  asm volatile("{\n.reg .pred p;\nsetp.eq.b32 p, 0, 0;\n"
    "wgmma.mma_async.sync.aligned.m64n40k16.f32.bf16.bf16 "
    "{%0, %1, %2, %3, %4, %5, %6, %7, %8, %9, %10, %11, %12, %13, %14, %15, "
    "%16, %17, %18, %19}, {%20, %21, %22, %23}, %24, p, 1, 1, %25;\n}\n"
    : "+f"(d[0]), "+f"(d[1]), "+f"(d[2]), "+f"(d[3]), "+f"(d[4]), "+f"(d[5]), "+f"(d[6]), "+f"(d[7]),
      "+f"(d[8]), "+f"(d[9]), "+f"(d[10]), "+f"(d[11]), "+f"(d[12]), "+f"(d[13]), "+f"(d[14]), "+f"(d[15]),
      "+f"(d[16]), "+f"(d[17]), "+f"(d[18]), "+f"(d[19])
    : "r"(a[0]), "r"(a[1]), "r"(a[2]), "r"(a[3]), "l"(db), "n"(TB));
}
template <int TB> __device__ __forceinline__ void rs40z(float* d, const uint32_t* a, uint64_t db) {
  asm volatile("{\n.reg .pred p;\nsetp.ne.b32 p, 0, 0;\n"
    "wgmma.mma_async.sync.aligned.m64n40k16.f32.bf16.bf16 "
    "{%0, %1, %2, %3, %4, %5, %6, %7, %8, %9, %10, %11, %12, %13, %14, %15, "
    "%16, %17, %18, %19}, {%20, %21, %22, %23}, %24, p, 1, 1, %25;\n}\n"
    : "=&f"(d[0]), "=&f"(d[1]), "=&f"(d[2]), "=&f"(d[3]), "=&f"(d[4]), "=&f"(d[5]), "=&f"(d[6]), "=&f"(d[7]),
      "=&f"(d[8]), "=&f"(d[9]), "=&f"(d[10]), "=&f"(d[11]), "=&f"(d[12]), "=&f"(d[13]), "=&f"(d[14]), "=&f"(d[15]),
      "=&f"(d[16]), "=&f"(d[17]), "=&f"(d[18]), "=&f"(d[19])
    : "r"(a[0]), "r"(a[1]), "r"(a[2]), "r"(a[3]), "l"(db), "n"(TB));
}
template <int TB> __device__ __forceinline__ void rs72a(float* d, const uint32_t* a, uint64_t db) {
  asm volatile("{\n.reg .pred p;\nsetp.eq.b32 p, 0, 0;\n"
    "wgmma.mma_async.sync.aligned.m64n72k16.f32.bf16.bf16 "
    "{%0, %1, %2, %3, %4, %5, %6, %7, %8, %9, %10, %11, %12, %13, %14, %15, "
    "%16, %17, %18, %19, %20, %21, %22, %23, %24, %25, %26, %27, %28, %29, %30, %31, "
    "%32, %33, %34, %35}, {%36, %37, %38, %39}, %40, p, 1, 1, %41;\n}\n"
    : "+f"(d[0]), "+f"(d[1]), "+f"(d[2]), "+f"(d[3]), "+f"(d[4]), "+f"(d[5]), "+f"(d[6]), "+f"(d[7]),
      "+f"(d[8]), "+f"(d[9]), "+f"(d[10]), "+f"(d[11]), "+f"(d[12]), "+f"(d[13]), "+f"(d[14]), "+f"(d[15]),
      "+f"(d[16]), "+f"(d[17]), "+f"(d[18]), "+f"(d[19]), "+f"(d[20]), "+f"(d[21]), "+f"(d[22]), "+f"(d[23]),
      "+f"(d[24]), "+f"(d[25]), "+f"(d[26]), "+f"(d[27]), "+f"(d[28]), "+f"(d[29]), "+f"(d[30]), "+f"(d[31]),
      "+f"(d[32]), "+f"(d[33]), "+f"(d[34]), "+f"(d[35])
    : "r"(a[0]), "r"(a[1]), "r"(a[2]), "r"(a[3]), "l"(db), "n"(TB));
}
template <int TB> __device__ __forceinline__ void rs72z(float* d, const uint32_t* a, uint64_t db) {
  asm volatile("{\n.reg .pred p;\nsetp.ne.b32 p, 0, 0;\n"
    "wgmma.mma_async.sync.aligned.m64n72k16.f32.bf16.bf16 "
    "{%0, %1, %2, %3, %4, %5, %6, %7, %8, %9, %10, %11, %12, %13, %14, %15, "
    "%16, %17, %18, %19, %20, %21, %22, %23, %24, %25, %26, %27, %28, %29, %30, %31, "
    "%32, %33, %34, %35}, {%36, %37, %38, %39}, %40, p, 1, 1, %41;\n}\n"
    : "=&f"(d[0]), "=&f"(d[1]), "=&f"(d[2]), "=&f"(d[3]), "=&f"(d[4]), "=&f"(d[5]), "=&f"(d[6]), "=&f"(d[7]),
      "=&f"(d[8]), "=&f"(d[9]), "=&f"(d[10]), "=&f"(d[11]), "=&f"(d[12]), "=&f"(d[13]), "=&f"(d[14]), "=&f"(d[15]),
      "=&f"(d[16]), "=&f"(d[17]), "=&f"(d[18]), "=&f"(d[19]), "=&f"(d[20]), "=&f"(d[21]), "=&f"(d[22]), "=&f"(d[23]),
      "=&f"(d[24]), "=&f"(d[25]), "=&f"(d[26]), "=&f"(d[27]), "=&f"(d[28]), "=&f"(d[29]), "=&f"(d[30]), "=&f"(d[31]),
      "=&f"(d[32]), "=&f"(d[33]), "=&f"(d[34]), "=&f"(d[35])
    : "r"(a[0]), "r"(a[1]), "r"(a[2]), "r"(a[3]), "l"(db), "n"(TB));
}
template <int TB> __device__ __forceinline__ void rs128a(float* d, const uint32_t* a, uint64_t db) {
  asm volatile("{\n.reg .pred p;\nsetp.eq.b32 p, 0, 0;\n"
    "wgmma.mma_async.sync.aligned.m64n128k16.f32.bf16.bf16 "
    "{%0, %1, %2, %3, %4, %5, %6, %7, %8, %9, %10, %11, %12, %13, %14, %15, "
    "%16, %17, %18, %19, %20, %21, %22, %23, %24, %25, %26, %27, %28, %29, %30, %31, "
    "%32, %33, %34, %35, %36, %37, %38, %39, %40, %41, %42, %43, %44, %45, %46, %47, "
    "%48, %49, %50, %51, %52, %53, %54, %55, %56, %57, %58, %59, %60, %61, %62, %63}, {%64, %65, %66, %67}, %68, p, 1, 1, %69;\n}\n"
    : "+f"(d[0]), "+f"(d[1]), "+f"(d[2]), "+f"(d[3]), "+f"(d[4]), "+f"(d[5]), "+f"(d[6]), "+f"(d[7]),
      "+f"(d[8]), "+f"(d[9]), "+f"(d[10]), "+f"(d[11]), "+f"(d[12]), "+f"(d[13]), "+f"(d[14]), "+f"(d[15]),
      "+f"(d[16]), "+f"(d[17]), "+f"(d[18]), "+f"(d[19]), "+f"(d[20]), "+f"(d[21]), "+f"(d[22]), "+f"(d[23]),
      "+f"(d[24]), "+f"(d[25]), "+f"(d[26]), "+f"(d[27]), "+f"(d[28]), "+f"(d[29]), "+f"(d[30]), "+f"(d[31]),
      "+f"(d[32]), "+f"(d[33]), "+f"(d[34]), "+f"(d[35]), "+f"(d[36]), "+f"(d[37]), "+f"(d[38]), "+f"(d[39]),
      "+f"(d[40]), "+f"(d[41]), "+f"(d[42]), "+f"(d[43]), "+f"(d[44]), "+f"(d[45]), "+f"(d[46]), "+f"(d[47]),
      "+f"(d[48]), "+f"(d[49]), "+f"(d[50]), "+f"(d[51]), "+f"(d[52]), "+f"(d[53]), "+f"(d[54]), "+f"(d[55]),
      "+f"(d[56]), "+f"(d[57]), "+f"(d[58]), "+f"(d[59]), "+f"(d[60]), "+f"(d[61]), "+f"(d[62]), "+f"(d[63])
    : "r"(a[0]), "r"(a[1]), "r"(a[2]), "r"(a[3]), "l"(db), "n"(TB));
}
template <int TB> __device__ __forceinline__ void rs128z(float* d, const uint32_t* a, uint64_t db) {
  asm volatile("{\n.reg .pred p;\nsetp.ne.b32 p, 0, 0;\n"
    "wgmma.mma_async.sync.aligned.m64n128k16.f32.bf16.bf16 "
    "{%0, %1, %2, %3, %4, %5, %6, %7, %8, %9, %10, %11, %12, %13, %14, %15, "
    "%16, %17, %18, %19, %20, %21, %22, %23, %24, %25, %26, %27, %28, %29, %30, %31, "
    "%32, %33, %34, %35, %36, %37, %38, %39, %40, %41, %42, %43, %44, %45, %46, %47, "
    "%48, %49, %50, %51, %52, %53, %54, %55, %56, %57, %58, %59, %60, %61, %62, %63}, {%64, %65, %66, %67}, %68, p, 1, 1, %69;\n}\n"
    : "=&f"(d[0]), "=&f"(d[1]), "=&f"(d[2]), "=&f"(d[3]), "=&f"(d[4]), "=&f"(d[5]), "=&f"(d[6]), "=&f"(d[7]),
      "=&f"(d[8]), "=&f"(d[9]), "=&f"(d[10]), "=&f"(d[11]), "=&f"(d[12]), "=&f"(d[13]), "=&f"(d[14]), "=&f"(d[15]),
      "=&f"(d[16]), "=&f"(d[17]), "=&f"(d[18]), "=&f"(d[19]), "=&f"(d[20]), "=&f"(d[21]), "=&f"(d[22]), "=&f"(d[23]),
      "=&f"(d[24]), "=&f"(d[25]), "=&f"(d[26]), "=&f"(d[27]), "=&f"(d[28]), "=&f"(d[29]), "=&f"(d[30]), "=&f"(d[31]),
      "=&f"(d[32]), "=&f"(d[33]), "=&f"(d[34]), "=&f"(d[35]), "=&f"(d[36]), "=&f"(d[37]), "=&f"(d[38]), "=&f"(d[39]),
      "=&f"(d[40]), "=&f"(d[41]), "=&f"(d[42]), "=&f"(d[43]), "=&f"(d[44]), "=&f"(d[45]), "=&f"(d[46]), "=&f"(d[47]),
      "=&f"(d[48]), "=&f"(d[49]), "=&f"(d[50]), "=&f"(d[51]), "=&f"(d[52]), "=&f"(d[53]), "=&f"(d[54]), "=&f"(d[55]),
      "=&f"(d[56]), "=&f"(d[57]), "=&f"(d[58]), "=&f"(d[59]), "=&f"(d[60]), "=&f"(d[61]), "=&f"(d[62]), "=&f"(d[63])
    : "r"(a[0]), "r"(a[1]), "r"(a[2]), "r"(a[3]), "l"(db), "n"(TB));
}

template <int V> struct IC { static constexpr int value = V; };
struct PfType { const char* base; uint32_t gl, gh, sp, sr, su, l4, l2; };
struct Params {
  const __nv_bfloat16 *x, *w;
  unsigned* cnt;
  uint32_t one;
  const __nv_bfloat16 *shift, *ssmD;
  __nv_bfloat16* out;
  uint4* o; float* kv;
  const char *k, *v;
  PfType pt[6];
  uint8_t pf[32];
  uint64_t cd[18];
};

struct Tmp { float t0, t1; };
__device__ __forceinline__ void mul2(Tmp& t, float a0, float b0, float a1, float b1) {
  asm volatile("@p_one mul.rn.f32 %0, %2, %3;\n@p_one mul.rn.f32 %1, %4, %5;" : "+f"(t.t0), "+f"(t.t1) : "f"(a0), "f"(b0), "f"(a1), "f"(b1)); }
__device__ __forceinline__ void add2(Tmp& t, float a0, float b0, float a1, float b1) {
  asm volatile("@p_one add.rn.f32 %0, %2, %3;\n@p_one add.rn.f32 %1, %4, %5;" : "+f"(t.t0), "+f"(t.t1) : "f"(a0), "f"(b0), "f"(a1), "f"(b1)); }
__device__ __forceinline__ void fma2(Tmp& t, float a0, float b0, float a1, float b1) { t.t0 = fmaf(a0, b0, t.t0); t.t1 = fmaf(a1, b1, t.t1); }
struct Tw { uint32_t c[2], s[2], ns[2]; };
__device__ __forceinline__ void rot(uint32_t& u, uint32_t& v, const Tw& w, int k) {
  asm("{\n.reg .b32 a, b;\nmul.rn.bf16x2 a, %0, %2;\nmul.rn.bf16x2 b, %0, %3;\nfma.rn.bf16x2 %0, %1, %4, a;\nfma.rn.bf16x2 %1, %1, %2, b;\n}"
    : "+r"(u), "+r"(v) : "r"(w.c[k]), "r"(w.s[k]), "r"(w.ns[k]));
}
__device__ __forceinline__ void pack_fwd(uint32_t (&f)[2][2][4], const float* a) {
  #pragma unroll
  for (int j = 0; j < 16; j++) f[j >> 3][(j >> 1) & 1][2 * (j & 1) + ((j >> 2) & 1)] = fresh(pack_bf16(a[2 * j], a[2 * j + 1]));
}
__device__ __forceinline__ void rot_fwd(uint32_t (&f)[2][2][4], const Tw& w) {
  #pragma unroll
  for (int j = 0; j < 8; j++) rot(f[j >> 2][j & 1][(j >> 1) & 1], f[j >> 2][j & 1][2 + ((j >> 1) & 1)], w, j & 1);
}
__device__ __forceinline__ void add_skip(float* h, float d) {
  asm volatile("add.rn.f32 %0, %0, %4;\nadd.rn.f32 %1, %1, %4;\nadd.rn.f32 %2, %2, %4;\nadd.rn.f32 %3, %3, %4;" : "+f"(h[0]), "+f"(h[1]), "+f"(h[4]), "+f"(h[5]) : "f"(d)); }
__device__ __forceinline__ void dft16h(float* d, const uint32_t (&f)[2][4], const D2& dF) { rs32z<0>(d, f[0], dF.a); rs32a<0>(d, f[1], dF.b); }
#define SP(h, p, im, k) (((p) >> 1 ? hi : lo) + 16 * (h) + 8 * (im) + 4 * (k) + 2 * ((p) & 1))
template <int PH, int G0 = 0, int G1 = 8> __device__ __forceinline__ void prod(Tmp& t, uint32_t (&f)[2][4], const float* lo, const float* hi) {
  #pragma unroll
  for (int g = G0; g < G1; g++) {
    const int p = 2 * PH + 1 - (g >> 2), k = (g >> 1) & 1, im = g & 1;
    #pragma unroll
    for (int q = 0; q <= p; q++) {
      const float *hr = SP(1, q, 0, k), *hi_ = SP(1, q, 1, k), *xa = SP(0, p - q, im, k), *xb = SP(0, p - q, 1 - im, k);
      if (q == 0) mul2(t, hr[0], xa[0], hr[1], xa[1]); else fma2(t, hr[0], xa[0], hr[1], xa[1]);
      if (im) fma2(t, hi_[0], xb[0], hi_[1], xb[1]); else fma2(t, -hi_[0], xb[0], -hi_[1], xb[1]);
    }
    f[k][2 * (1 - im) + (p & 1)] = pack_bf16(t.t0, t.t1);
  }
}

constexpr uint64_t dA = cdesc(A_OFF, 2048, 128, 0), dAi = cdesc(A_OFF, 128, 1024, 0), dF0 = cdesc(F_OFF, 128, 512, 0),
                   dT0 = cdesc(T_OFF, 1024, 128, 0), dH0 = cdesc(H_OFF, 1024, 256, 3), dX0 = cdesc(X_OFF, 1024, 128, 0);
#define CONV_DESC dF0, dF0 + 16, dAi, dT0, dAi + 16, dT0 + 128, dAi + 32, dT0 + 256, dAi + 48, dT0 + 384, dA, dH0, dA + 256, dH0 + 32, dA, dX0, dA + 256, dX0 + 128
__device__ __forceinline__ void make_tw(Tw& tw, int ht) {
  #pragma unroll
  for (int i = 0; i < 2; i++) {
    float c0, s0, c1, s1;
    unit_root<11>((4 * (ht >> 2) + 1) * (i * 8 + 2 * (ht & 3)), c0, s0);
    unit_root<11>((4 * (ht >> 2) + 1) * (i * 8 + 2 * (ht & 3) + 1), c1, s1);
    tw.c[i] = pack_bf16(c0, c1); tw.s[i] = pack_bf16(s0, s1); tw.ns[i] = fresh(tw.s[i] ^ 0x80008000u);
  }
}
template <bool COMMIT = true> __device__ __forceinline__ void dft32_h(float* r, const D2* d) {
  ss64z<1, 1>(r, d[0].a, d[0].b); ss64a<1, 1>(r, d[1].a, d[1].b);
  if (COMMIT) wg_commit();
}
template <bool COMMIT = true> __device__ __forceinline__ void dft32_x(float* r, D2* d) {
  ss64z<1, 0>(r, d[0].a, d[0].b); ss64a<1, 0>(r, d[1].a, d[1].b);
  if (COMMIT) wg_commit();
  d[0].b = dofs(d[0].b, XS); d[1].b = dofs(d[1].b, XS);
}
__device__ __forceinline__ void pack_inv(uint32_t (&u)[2][2][4], const float* r) {
  #pragma unroll
  for (int j = 0; j < 16; j++) u[j >> 3][(j >> 2) & 1][2 * (j & 1) + ((j >> 1) & 1)] = fresh(pack_bf16(r[2 * j], r[2 * j + 1]));
}
__device__ __forceinline__ void rot_inv(uint32_t (&u)[2][2][4], const Tw& tw, uint32_t ta) {
  #pragma unroll
  for (int m = 0; m < 2; m++) {
    #pragma unroll
    for (int j = 0; j < 4; j++) rot(u[m][0][j], u[m][1][j], tw, j & 1);
    stsm4(ta + m * 512, u[m][1][0], u[m][1][1], u[m][1][2], u[m][1][3]);
    stsm4(ta + 1024 + m * 512, u[m][0][0], u[m][0][1], u[m][0][2], u[m][0][3]);
  }
}
__device__ __forceinline__ void idft32(float* r, const D2* d) {
  wg_fence();
  ss64z<0, 1>(r, d[0].a, d[0].b);
  #pragma unroll
  for (int j = 1; j < 4; j++) ss64a<0, 1>(r, d[j].a, d[j].b);
  wg_commit();
}
__device__ __forceinline__ void finish(Tmp& t, const float* r, int ch, int ht, int rank, uint32_t y0, uint32_t y1) {
  const uint32_t ya = X_OFF + ch * XS + (ch & 1) * 16, yb = BAR_OFF + (B_YR + ch) * 8;
  uint32_t y[8];
  #pragma unroll
  for (int j = 0; j < 8; j++) {
    if (j >= 2) add2(t, r[4 * j], r[4 * j - 6], r[4 * j + 1], r[4 * j - 5]);
    y[j] = j < 2 ? pack_bf16(r[4 * j], r[4 * j + 1]) : pack_bf16(t.t0, t.t1);
  }
  st_async128(y0 + ya + (ht ^ (rank * 4)) * 16 + rank * (YX - XS), y0 + yb, y[0], y[1], y[2], y[3]);
  st_async128(y1 + ya + (ht ^ (rank * 4) ^ 4) * 16 + (rank ^ 1) * (YX - XS), y1 + yb, y[4], y[5], y[6], y[7]);
}

struct Team { uint32_t bars, rel, wofs, lead; };
struct Nop { __device__ __forceinline__ void operator()() const {} };
template <bool M, class F> __device__ __forceinline__ void mid_wait(F f) { if (M) wg_commit(); f(); if (M) { wg_wait<0>(); wg_fence(); } }
template <int J, bool M = false, class F = Nop> __device__ __forceinline__ void kv_issue(float* aK, float* aV, uint32_t xo, int sd, F f = F()) {
  constexpr uint64_t dw = cdesc(W_OFF + J * 8192, 8192, 1024, 1);
  const uint64_t dx = dofs(cdesc((J & 1) * 64, 16, 1024, 1), xo);
  wg_fence();
  ss128p<1, 0>(aV, dw + (4096 >> 4), dx, sd);
  ss128p<1, 0>(aK, dw, dx, sd);
  mid_wait<M>(f);
  ss128a<1, 0>(aV, dw + (6144 >> 4), dofs(dx, 32));
  ss128a<1, 0>(aK, dw + (2048 >> 4), dofs(dx, 32));
  wg_commit();
}
template <int O, int J, int H> __device__ __forceinline__ void g2_half(float* acc, const Team& c) {
  constexpr uint64_t db = cdesc(J * SLOT + 16384 + H * 4096, 8192, 1024, 1);
  const uint64_t da = dofs(O ? cdesc(J * SLOT + H * 4096, 16, 512, 2) : cdesc(J * SLOT + H * 64, 16, 1024, 1), c.wofs);
  wg_fence();
  ss128a<0, 1>(acc, da, db);
  ss128a<0, 1>(acc, dofs(da, 32), db + (2048 >> 4));
  wg_commit();
}
template <int O, int J, bool M = false, bool FIRST = false, class F = Nop> __device__ __forceinline__ void g2_issue(float* acc, const Team& c, F f = F()) {
  constexpr uint64_t db = cdesc(J * SLOT + 16384, 8192, 1024, 1);
  const uint64_t da = dofs(O ? cdesc(J * SLOT, 16, 512, 2) : cdesc(J * SLOT, 16, 1024, 1), c.wofs);
  wg_fence();
  if (FIRST) ss128z<0, 1>(acc, da, db); else ss128a<0, 1>(acc, da, db);
  ss128a<0, 1>(acc, dofs(da, 32), db + (2048 >> 4));
  mid_wait<M>(f);
  ss128a<0, 1>(acc, dofs(da, O ? 4096 : 64), db + (4096 >> 4));
  ss128a<0, 1>(acc, dofs(da, O ? 4128 : 96), db + (6144 >> 4));
  wg_commit();
}
template <bool DEEP, bool AB = false, class F>
__device__ __forceinline__ void ring_step(const Team& c, int fb, uint32_t ph, int eb, uint32_t rel, F issue, uint32_t ab = 0, uint32_t aph = 0) {
  uint32_t ok = mbar_try(c.bars + fb * 8, ph);
  if (AB) ok &= mbar_try(ab, aph);
  if (!ok) {
    wg_wait<0>();
    arrive_at(c.rel + eb * 8, rel);
    rel = 0;
    mbar_wait(c.bars + fb * 8, ph);
    if (AB) mbar_wait(ab, aph);
  }
  if constexpr (!DEEP) {
    wg_wait<0>();
    issue([&]() { arrive_at(c.rel + eb * 8, rel); });
  } else {
    issue();
    wg_wait<1>(); arrive_at(c.rel + eb * 8, rel);
  }
}
template <int N, int I = 0, class R> __device__ __forceinline__ void tail_release(R rel) {
  if constexpr (I <= N) { wg_wait<N - I>(); rel(I - 1); tail_release<N, I + 1>(rel); }
}
template <int N, class F, class R> __device__ __forceinline__ void skew_tail(const Team& c, int ph, F issue, R rel) {
  if (c.wofs) { wg_wait<0>(); rel(-1); mbar_wait(c.bars + B_SK * 8, ph); }
  issue();
  arrive_at(c.bars + B_SK * 8, fresh_tid() == 0);
  tail_release<N>([&](int i) { if (i >= 0 || !c.wofs) rel(i); });
}
__device__ __forceinline__ void phi_a(float* a, uint32_t* f) {
  #pragma unroll
  for (int i = 0; i < 8; i++) {
    asm("cvt.rn.relu.bf16x2.f32 %0, %1, %2;" : "=r"(f[i]) : "f"(a[2 * i + 1]), "f"(a[2 * i]));
    asm("ex2.approx.ftz.f32 %0, %1;" : "=f"(a[2 * i]) : "f"(a[2 * i] * 1.4426950408889634f));
    asm("ex2.approx.ftz.f32 %0, %1;" : "=f"(a[2 * i + 1]) : "f"(a[2 * i + 1] * 1.4426950408889634f));
  }
  pinv<16>(a);
}
__device__ __forceinline__ void phi_s(float* a, uint32_t* f) {
  #pragma unroll
  for (int i = 0; i < 8; i++) {
    asm("cvt.rn.relu.bf16x2.f32 %0, %1, %2;" : "=r"(f[i]) : "f"(a[2 * i + 1]), "f"(a[2 * i]));
    a[2 * i] *= 1.4426950408889634f; a[2 * i + 1] *= 1.4426950408889634f;
  }
  pinv<16>(a);
}
__device__ __forceinline__ void phi_e(float* a) {
  #pragma unroll
  for (int i = 0; i < 16; i++) asm("ex2.approx.ftz.f32 %0, %0;" : "+f"(a[i]));
  pinv<16>(a);
}
__device__ __forceinline__ void phi_b(const float* e, uint32_t* f) {
  #pragma unroll
  for (int i = 0; i < 8; i++) f[i] = badd2(f[i], pack_bf16(__saturatef(e[2 * i] + 1e-6f), __saturatef(e[2 * i + 1] + 1e-6f)));
}
__device__ __forceinline__ int g2_k(int st, int n2) {
  const int j = (st >> 1) - 1;
  return 2 * (j == 0 ? n2 == 0 : (j == max(n2, 1) ? 7 : j)) + (st & 1);
}

__global__ void __cluster_dims__(2, 1, 1) __launch_bounds__(NTHREADS, 1)
fused_kernel(const __grid_constant__ Params P, const __grid_constant__ CUtensorMap mX, const __grid_constant__ CUtensorMap mW,
             const __grid_constant__ CUtensorMap mWq, const __grid_constant__ CUtensorMap mWo,
             const __grid_constant__ CUtensorMap mK, const __grid_constant__ CUtensorMap mV, const __grid_constant__ CUtensorMap mH,
             const __grid_constant__ CUtensorMap mQ, const __grid_constant__ CUtensorMap mOut, const __grid_constant__ CUtensorMap mOutA,
             const __grid_constant__ CUtensorMap mWp) {
  extern __shared__ __align__(1024) uint8_t smem[];
  asm volatile(".reg .pred p_one;");
  const int tid = threadIdx.x, lane = tid & 31;
  const int warp = __shfl_sync(0xffffffffu, tid >> 5, 0);
  if (warp == 0) {
    asm volatile(ELECT "prefetch.tensormap [%0];\n}" :: "l"(&mW) : "memory");
    asm volatile(ELECT "prefetch.tensormap [%0];\n}" :: "l"(&mX) : "memory");
  }
  {
    const uint32_t t = threadIdx.x, bb = blockIdx.x;
    asm volatile("{\n.reg .pred p, q;\nsetp.eq.u32 p, %2, 2;\nsetp.eq.u32 q, %3, 8;\n@p prefetch.global.L2 [%0];\n@q prefetch.global.L2 [%1];\n}"
      :: "l"(reinterpret_cast<const char*>(P.x) + ((bb * 16 + t - 32) * 2048)),
         "l"(reinterpret_cast<const char*>(P.w) + ((bb >> 2) * 2048 + bb * 1024 + t * 128 - 6144)), "r"(t >> 4), "r"(t >> 3));
  }
  const uint32_t sb = uni(smem_u32(smem));
  const uint32_t bars = sb + BAR_OFF;
  const uint32_t ids = uni(wanted_job() * 2 + (blockIdx.x & 1));
#define IDS(w) const int rank = (w) & 1, hp = (w) & 15, g = hp >> 1, mb = (w) >> 4, m2 = hp, n2 = mb, cp = g * 8 + mb; \
               (void)rank; (void)m2; (void)n2; (void)cp
  auto job = [&]() { return (uni(lds32(sb + D_OFF + 52)) & 126) | (ids & 1); };
  auto wrong_job = [&]() {
    mbar_wait(bars + B_EX * 8, 0);
    return uni(lds32(sb + D_OFF + 52) ^ lds32(sb + D_OFF + 56)) != 1;
  };

  if (warp == 0) {
    IDS(ids);
    mbar_init(bars + (B_XF + 2) * 8, 1); mbar_init(bars + B_F0 * 8, 1); mbar_init(bars + B_FULL * 8, 1);
    mbar_expect_tx(bars + B_FULL * 8, 8192);
    tma3d(sb + W_OFF, &mW, hp * 64, 0, 1, bars + B_FULL * 8);
    mbar_expect_tx(bars + (B_XF + 2) * 8, 16384);
    tma2d(sb + 2 * SLOT, &mX, 0, mb * 256, bars + (B_XF + 2) * 8);
    mbar_expect_tx(bars + B_F0 * 8, 16384);
    tma2d(sb + 2 * SLOT + 16384, &mX, 0, mb * 256 + 128, bars + B_F0 * 8);
    #pragma unroll
    for (int i = 1; i < 4; i++) mbar_init(bars + (B_FULL + i) * 8, 1);
    #pragma unroll
    for (int i = 1; i < 4; i++) {
      mbar_expect_tx(bars + (B_FULL + i) * 8, 8192);
      tma3d(sb + W_OFF + i * 8192, &mW, hp * 64, i * 32, 1, bars + (B_FULL + i) * 8);
    }
    mbar_init(bars + B_XF * 8, 1); mbar_init(bars + (B_XF + 1) * 8, 1);
  } else if (warp >= 6) {
    const uint32_t cnt = warp < 12 || warp == 15 ? 1 : 4, b0 = bars + (warp - 4) * 32;
    #pragma unroll
    for (int i = 0; i < 4; i++) mbar_init(b0 + i * 8, i == 3 && warp == 15 ? 4 : cnt);
    if (warp == 8 || warp == 9) {
      #pragma unroll
      for (int i = 0; i < 4; i++) mbar_expect_tx(b0 + i * 8, 4096);
    } else if ((warp & 13) == 13) {
      mbar_expect_tx(bars + (warp == 13 ? B_KVB : B_EX) * 8, warp == 13 ? 5120 : 8);
    }
  }
  asm volatile("fence.mbarrier_init.release.cluster;" ::: "memory");
  __syncwarp();
  asm volatile("barrier.cluster.arrive.relaxed.aligned;" ::: "memory");

  if ((warp >> 2) == 2) {
    asm volatile("setmaxnreg.inc.sync.aligned.u32 %0;" :: "n"(160));
    const int ht = tid - 256, w = warp - 8;
    const int kap = w & 1;
    {
      uint32_t c4[4], s4[4];
      #pragma unroll
      for (int i = 0; i < 4; i++) {
        float c0, s0, c1, s1;
        unit_root<7>((32 * (ht & 3) + 8 * i + 1) * (ht >> 2), c0, s0);
        unit_root<7>((32 * (ht & 3) + 8 * i + 5) * (ht >> 2), c1, s1);
        c4[i] = pack_bf16(c0 * 0.125f, c1 * 0.125f); s4[i] = pack_bf16(s0 * 0.125f, s1 * 0.125f);
      }
      const uint32_t aa = sb + A_OFF + w * 2048 + (ht & 3) * 256 + ((ht >> 2) & 7) * 16;
      sts128(aa, c4[0], c4[1], c4[2], c4[3]);
      sts128(aa + 128, s4[0], s4[1], s4[2], s4[3]);
      sts128(aa + 1024, s4[0] ^ 0x80008000u, s4[1] ^ 0x80008000u, s4[2] ^ 0x80008000u, s4[3] ^ 0x80008000u);
      sts128(aa + 1024 + 128, c4[0], c4[1], c4[2], c4[3]);
      float c0, s0, c1, s1;
      unit_root<4>((ht >> 3) * (2 * (ht & 7)), c0, s0);
      unit_root<4>((ht >> 3) * (2 * (ht & 7) + 1), c1, s1);
      const uint32_t fa = sb + F_OFF + (ht >> 6) * 512 + ((ht >> 2) & 1) * 256 + ((ht >> 3) & 7) * 16 + (ht & 3) * 4;
      const uint32_t cc = pack_bf16(c0, c1), ss = pack_bf16(s0, s1);
      sts32(fa, cc); sts32(fa + 128, ss ^ 0x80008000u); sts32(fa + 1024, ss); sts32(fa + 1024 + 128, cc);
    }
    cluster_wait();
    mbar_wait(bars + B_EX * 8, 0);
    const uint32_t id2 = job(); IDS(id2);
    if (id2 != ids) bar_sync(8, 160);
    const uint4 sw = *reinterpret_cast<const uint4*>(P.shift + (cp * 16 + kap * 8 + 2 * (lane & 3)) * 4);
    const float dv = __bfloat162float(P.ssmD[cp * 16 + rank * 8 + (ht & 7)]) * 0.125f;
    Tw tw;
    make_tw(tw, ht);
    D2 cd[9];
    {
      const uint64_t v = P.cd[min(lane, 17)];
      #pragma unroll
      for (int i = 0; i < 9; i++) { cd[i].a = __shfl_sync(0xffffffffu, v, 2 * i); cd[i].b = __shfl_sync(0xffffffffu, v, 2 * i + 1); }
    }
    const D2 &dF = cd[0], *dT = cd + 1, *dH = cd + 5;
    D2* dX = cd + 7;
#define CFENCE(n) sched_fence<n>((uint32_t)dF.a)
    if (ht < 8) sts32(sb + D_OFF + ht * 4, __float_as_uint(dv));
    const uint32_t w0 = __byte_perm(sw.x, sw.z, 0x5410), w1 = __byte_perm(sw.x, sw.z, 0x7632);
    const uint32_t w2 = __byte_perm(sw.y, sw.w, 0x5410), w3 = __byte_perm(sw.y, sw.w, 0x7632);
    const uint32_t psb = uni(mapa(sb, rank ^ 1));
    if (ht == 0) OSTAMP(20);
    {
      const int m = lane >> 3, n1 = (w >> 1) * 8 + (lane & 7);
      const int rk = 17 * m + n1 + 1, rh = 17 * (12 + m) + n1, rv = 16 * m + n1;
      const uint32_t ka = rk * 32 + ((kap ^ (rk >> 2)) & 1) * 16, ha = rh * 32 + ((kap ^ (rh >> 2)) & 1) * 16;
      const uint32_t va = rv * 32 + ((kap ^ (rv >> 2)) & 1) * 16;
      const uint32_t po = sb + T_OFF + (w >> 1) * 2176;
      #pragma unroll 1
      for (int rd = 0; rd < 4; rd++) {
        const uint32_t kb = sb + M_OFF + (rd & 1) * KB, vb = sb + M_OFF + 2 * KB + (rd & 1) * 8192;
        const uint32_t xo = X_OFF + ((rd & 1) * 2 + (w >> 1)) * 1024 + (2 * rank + (rd >> 1)) * 256;
        const uint32_t xa = (kap == rank ? sb + xo + (lane & 7) * XS : po + (lane & 7) * 272) + m * 16;
        mbar_wait(bars + (B_STG + (rd & 1) * 2) * 8, rd >> 1);
        uint32_t kk[20], vv[16];
        const uint32_t zero = P.one - 1;
        ldsm4(kk, kb + ha);
        ldsm4(kk + 4, kb + ka);
        #pragma unroll
        for (int i = 0; i < 16; i++) {
          if ((i & 3) == 0 && i < 12) ldsm4(kk + 8 + i, kb + (ka ^ ((~i & 4) * 4)) + (i + 4) * 544 + (kk[i + 4] & zero));
          uint32_t t = bmul2(kk[i + 1], w3);
          t = badd2(t, bmul2(kk[i + 2], w2));
          t = badd2(t, bmul2(kk[i + 3], w1));
          kk[i] = badd2(t, bmul2(kk[i + 4], w0));
          asm volatile("" : "+r"(kk[i]));
        }
        mbar_wait(bars + (B_STG + (rd & 1) * 2 + 1) * 8, rd >> 1);
        ldsm4(vv, vb + va);
        #pragma unroll
        for (int i = 0; i < 16; i += 4) {
          if (i < 12) ldsm4(vv + 4 + i, vb + va + (i + 4) * 512 + (i == 4 ? vv[0] & zero : 0));
          stsm4t(xa + (i >> 2) * 64, bmul2(kk[i], vv[i]), bmul2(kk[i + 1], vv[i + 1]), bmul2(kk[i + 2], vv[i + 2]), bmul2(kk[i + 3], vv[i + 3]));
        }
        if (rd < 2) {
          fence_async_smem();
          __syncwarp();
          mbar_arrive(bars + (B_SFREE + (rd & 1)) * 8);
        }
        __syncwarp();
        if (kap != rank) {
          #pragma unroll
          for (int i = 0; i < 4; i++) lds128(vv + 4 * i, po + (2 * i + (lane >> 4)) * 272 + (lane & 15) * 16);
          #pragma unroll
          for (int i = 0; i < 4; i++)
            st_async128(psb + xo + (2 * i + (lane >> 4)) * XS + (lane & 15) * 16, psb + BAR_OFF + B_X * 8, vv[4 * i], vv[4 * i + 1], vv[4 * i + 2], vv[4 * i + 3]);
          __syncwarp();
        }
      }
    }
    bar_sync(3, 128);
    if (w == 0) mbar_expect_tx(bars + B_X * 8, 16384);
    {
      constexpr int NC = 8;
      Tmp t; t.t0 = 0.f; t.t1 = 0.f;
      asm volatile("setp.ne.b32 p_one, %0, 0;" :: "r"(lds32(sb + F_OFF)));
      float ra[32], lo[32], hi[32];
      uint32_t fa[2][2][4], fb[2][2][4];
      const uint32_t ta = sb + T_OFF + w * 2048 + lane * 16;
      const uint32_t y0 = rank ? psb : sb, y1 = rank ? sb : psb;
      auto fin = [&](int ch) {
        if (ch > 0) mbar_wait(bars + (B_YR + ch - 1) * 8, 0);
        finish(t, ra, ch, ht, rank, y0, y1);
      };
      auto load_h = [&](int i) {
        mbar_expect_tx(bars + B_H * 8, 4096);
        tma2d(sb + H_OFF, &mH, 0, (cp * 16 + rank * 8 + i) * 128, bars + B_H * 8);
      };
      auto skip = [&](int i) {
        const float dn = __uint_as_float(lds32(sb + D_OFF + i * 4));
        return dn;
      };
      mbar_wait(bars + B_H * 8, 0);
      wg_fence();
      dft32_h(lo, dH);
      mbar_wait(bars + B_X * 8, 0);
      fence_async_smem();
      if (ht == 0) OSTAMP(21);
      wg_fence();
      dft32_x(hi, dX);
      float dn = skip(0);
      wg_wait<1>(); pinv<32>(lo);
      if (w == 0) load_h(1);
      pack_fwd(fa, lo); CFENCE(0); rot_fwd(fa, tw); CFENCE(1);
      wg_wait<0>(); pinv<32>(hi);
      pack_fwd(fb, hi); CFENCE(2); rot_fwd(fb, tw); CFENCE(3);
      wg_fence();
      dft16h(hi, fb[1], dF); dft16h(hi + 16, fa[1], dF); dft16h(lo, fb[0], dF); dft16h(lo + 16, fa[0], dF);
      wg_commit();
      wg_wait<0>(); pinv<32>(lo); pinv<32>(hi);
#define CSTAMP(n) do {} while (0)
      #pragma unroll 1
      for (int i = 0;; i++) {
        CSTAMP(0);
        add_skip(lo + 16, dn);
        prod<1, 0, FG>(t, fa[1], lo, hi);
        CFENCE(4);
        CSTAMP(1);
        fence_async_smem();
        bar_sync(3, 128);
        CSTAMP(2);
        float rg[32];
        wg_fence();
        ss64x4(rg, dT, i);
        CFENCE(5);
        CSTAMP(3);
        const uint32_t yr = bars + (i < 2 ? B_X : B_YR + i - 2) * 8;
        const uint32_t oky = mbar_try(yr, 0);
        dn = skip(i + 1);
        prod<1, FG, 8>(t, fa[1], lo, hi);
        pinv<32>(lo);
        if (!oky) mbar_wait(yr, 0);
        CSTAMP(4);
        wg_wait<0>(); pinv<32>(rg);
        if (i > 0) finish(t, rg, i - 1, ht, rank, y0, y1);
        if (i == NC - 1) break;
        CSTAMP(5);
        wg_fence();
        dft32_x<false>(hi, dX);
        dft16h(ra + 16, fa[1], dF);
        wg_commit();
        CFENCE(7);
        CSTAMP(6);
        const uint32_t okh = mbar_try(bars + B_H * 8, (i + 1) & 1);
        prod<0>(t, fa[0], lo, lo);
        if (!okh) mbar_wait(bars + B_H * 8, (i + 1) & 1);
        CSTAMP(7);
        wg_fence();
        dft32_h<false>(lo, dH);
        dft16h(ra, fa[0], dF);
        wg_commit();
        wg_wait<1>(); pinv<32>(hi);
        if (ht == 64) OSTAMP(22 + i);
        CSTAMP(8);
        pack_fwd(fb, hi); CFENCE(9); rot_fwd(fb, tw); CFENCE(10);
        CSTAMP(9);
        wg_wait<0>(); pinv<32>(lo); pinv<32>(ra);
        CSTAMP(10);
        if (w == 0 && i < NC - 2) load_h(i + 2);
        pack_fwd(fa, lo);
        CFENCE(11);
        wg_fence();
        dft16h(hi, fb[1], dF); dft16h(lo, fb[0], dF);
        wg_commit();
        CFENCE(12);
        rot_fwd(fa, tw);
        uint32_t u[2][2][4];
        CFENCE(13);
        pack_inv(u, ra);
        CFENCE(14);
        CSTAMP(11);
        wg_fence();
        dft16h(hi + 16, fa[1], dF); dft16h(lo + 16, fa[0], dF);
        wg_commit();
        CFENCE(15);
        CSTAMP(12);
        rot_inv(u, tw, ta);
        CSTAMP(13);
        CFENCE(16);
        wg_wait<0>(); pinv<32>(lo); pinv<32>(hi);
        CSTAMP(14);
      }
      wg_fence();
      dft16h(hi + 16, fa[1], dF);
      wg_commit();
      CFENCE(17);
      prod<0>(t, fa[0], lo, lo);
      CFENCE(18);
      wg_fence();
      dft16h(hi, fa[0], dF);
      wg_commit();
      if (ht == 64) OSTAMP(29);
      wg_wait<0>(); pinv<32>(hi);
      pack_inv(fb, hi); CFENCE(19); rot_inv(fb, tw, ta);
      fence_async_smem();
      bar_sync(3, 128);
      idft32(ra, dT);
      const int l3 = fresh_tid() & 31;
      uint32_t qa = sb + M_OFF + ((l3 >> 4) * 512 + w * 128 + (l3 & 8) + ((l3 >> 2) & 1) + (l3 & 2)) * 32 + (l3 & 1) * 16;
      uint32_t yb = sb + X_OFF + (l3 & 1) * (XS + 16) + w * 512
                    + (((l3 >> 1) & 1) == rank ? (l3 >> 2) * 16 : YX - XS + ((l3 >> 2) ^ 4) * 16);
      mbar_wait(bars + B_Q * 8, 0);
      wg_wait<0>(); pinv<32>(ra);
      fin(NC - 1);
      if (ht == 64) OSTAMP(30);
      uint32_t t0 = 0, dt = 0;
      #pragma unroll 1
      for (int sg = 0; sg < 4; sg++, qa += 1024, yb += 128) {
        uint32_t qv[4][4], yv[4][4];
        #pragma unroll
        for (int i = 0; i < 4; i++) lds128(qv[i], qa + (i >> 1) * 512 + (i & 1) * 128);
        #pragma unroll
        for (int m = 0; m < 4; m++) {
          if (m == 3 && sg == 0) mbar_wait(bars + (B_YR + NC - 1) * 8, 0);
          ldsm4t(yv[m], yb + 2 * m * XS);
        }
        #pragma unroll
        for (int i = 0; i < 4; i++)
          sts128(qa + (i >> 1) * 512 + (i & 1) * 128, bmul2(qv[i][0], yv[0][i]), bmul2(qv[i][1], yv[1][i]), bmul2(qv[i][2], yv[2][i]), bmul2(qv[i][3], yv[3][i]));
        if (sg == 3) mbar_arrive(bars + B_CD * 8);
        fence_async_smem();
        __syncwarp();
        if (sg == 0) {
          mbar_wait(bars + B_GO * 8, 0);
          t0 = uni((uint32_t)clock());
          dt = uni(min(max((int)(lds32(sb + D_OFF + 44) + OA_END - t0) >> 2, 4 * OA_MIN), 4 * OA_MAX));
          t0 += w * (dt >> 2);
        }
        pace(t0, dt);
        #pragma unroll
        for (int hf = 0; hf < 2; hf++) {
          const int r = w * 128 + sg * 32 + hf * 512;
          tma2d_store(&mOutA, cp * 16, rank * 1024 + r, sb + M_OFF + r * 32);
        }
      }
      bulk_commit(); bulk_wait_read();
      if (ht == 0) OSTAMP(31);
    }
  } else if (warp >= 12) {
    asm volatile("setmaxnreg.dec.sync.aligned.u32 %0;" :: "n"(32));
    const uint32_t t_pf = (uint32_t)clock();
    if (warp >= 14) {
      const uint32_t id2 = fresh(ids); IDS(id2);
      if (warp == 14) {
        asm volatile("prefetch.global.L2 [%0];" :: "l"(((lane & 1) ? P.v : P.k) + (rank * 2097152 + cp * 32 + (lane >> 1) * 131072)));
      } else {
        uint32_t t0 = t_pf + id2 * 2;
        #pragma unroll 1
        for (int i = 0; i < PF_N; i++) {
          const int u = P.pf[i];
          const PfType& f = P.pt[u >> 4];
          pace(t0, i == 0 ? PF_DT0 : (i < PF_N1 ? PF_DT1 : PF_DT2));
          asm volatile("prefetch.global.L2 [%0];" :: "l"(f.base + ((g & 3) * f.gl + (g >> 2) * f.gh + mb * f.sp + rank * f.sr + (u & 15) * f.su
                                                                   + (lane >> 2) * f.l4 + ((lane >> 1) & 1) * f.l2 + (lane & 1) * 128)));
        }
      }
    }
    cluster_wait();
    if (warp == 13) {
      unsigned* const asked = P.cnt + 80 * 32;
      uint32_t j = ids, taken = 0;
      if (lane + (ids & 1) == 0) taken = atomicExch(P.cnt + 64 * 32 + ids * 4, 1u);
      if (uni(taken)) {
        fence_gpu();
        unsigned n = 0;
        if (lane == 0) n = atomicAdd(asked, 1u);
        spin_until(asked, (uni(n) | 63) + 1);
        #pragma unroll 1
        for (j = 0; j < 126; j += 2) {
          if (lane == 0) n = atomicExch(P.cnt + 64 * 32 + j * 4, 1u);
          if (!uni(n)) break;
        }
        if (lane == 0) P.cnt[64 * 32 + j * 4] = 1;
        j |= 128;
      }
      asm volatile("{\n.reg .pred p;\nsetp.lt.u32 p, %3, 2;\n@p st.async.weak.shared::cluster.mbarrier::complete_tx::bytes.b32 [%0], %2, [%1];\n}"
        :: "r"(mapa(sb + D_OFF + 52 + (j & 1) * 4, lane & 1)), "r"(mapa(bars + B_EX * 8, lane & 1)), "r"(j), "r"(lane) : "memory");
      if (!(j & 129)) { fence_gpu(); red_add(asked); }
    }
    if (warp == 12) {
      uint32_t xs = 0, idk = fresh(ids);
      auto load_x = [&](int k) {
        IDS(idk);
        tma2d_mc(sb + xs * SLOT + rank * 16384, &mX, k, mb * 256 + rank * 128, bars + (B_XF + xs) * 8);
        mbar_expect_tx(bars + (B_XF + xs) * 8, SLOT);
        xs = xs == 2 ? 0 : xs + 1;
      };
      load_x(64); load_x(128);
      mbar_expect_tx(bars + B_Q * 8, 32768);
      int look = 5;
      #pragma unroll 1
      for (int it = 1; it < 8; it++) {
        #pragma unroll
        for (int j = 0; j < 4; j++) {
          bool again = false;
          if (j == 3 && it == look) again = wrong_job();
          mbar_wait(bars + (B_EMPTY + j) * 8, (it - 1) & 1);
          TSTAMP(1, 4 * it + j);
          tma3d(sb + W_OFF + j * 8192, &mW, (idk & 15) * 64, it * 128 + j * 32, 1, bars + (B_FULL + j) * 8);
          if (again) { it = look = -1; idk = job(); }
          if (j == 1 || (j == 3 && it < 7)) load_x(it * 128 + j * 32 + 32);
          mbar_expect_tx(bars + (B_FULL + j) * 8, 8192);
        }
      }
    }
    if (warp == 14) {
      uint32_t t0 = t_pf + STG_T0, idk = fresh(ids);
      #pragma unroll 1
      for (int pc = 0; pc < 16; pc++) {
        if (pc == 2) {
          mbar_wait(bars + B_EX * 8, 0);
          if (job() != idk) { mbar_wait(bars + B_STG * 8, 0); mbar_arrive(bars + B_STG * 8); bar_sync(8, 160); idk = job(); pc = 0; }
        }
        IDS(idk);
        const int rd = pc >> 2, u = pc & 3;
        const uint32_t gb = bars + (B_STG + (rd & 1) * 2 + (u >> 1)) * 8;
        if (pc == 8 || pc == 12) mbar_wait(bars + (B_SFREE + (rd & 1)) * 8, 0);
        if (!(u & 1)) mbar_expect_tx(gb, u ? 8192 : KB);
        pace(t0, STG_DT);
        TSTAMP(3, 16 + pc);
        tma3d(sb + M_OFF + (u < 2 ? (rd & 1) * KB + u * (KB / 2) : 2 * KB + (rd & 1) * 8192 + (u & 1) * 4096), u < 2 ? &mK : &mV,
              cp * 16, rank * 64 + rd * 16 - (u < 2), (u & 1) * 8, gb);
      }
      IDS(idk);
      mbar_expect_tx(bars + B_H * 8, 4096);
      tma2d(sb + H_OFF, &mH, 0, (cp * 16 + rank * 8) * 128, bars + B_H * 8);
    }
    mbar_wait(bars + B_EX * 8, 0);
    const uint32_t id2 = job(); IDS(id2);
    if (warp == 12) {
      #pragma unroll 1
      for (int it = 0; it < 4; it++) {
        #pragma unroll
        for (int j = 0; j < 4; j++) {
          const uint32_t fb = bars + (B_FULL2 + j) * 8;
          if (j || it) mbar_wait(bars + (it ? B_EMPTY2 + j : B_EMPTY + (j | 1)) * 8, (it - 1) & 1);
          TSTAMP(5, 4 * it + j);
          tma2d_mc(sb + j * SLOT + 16384 + rank * 8192, &mWq, n2 * 128 + rank * 64, it * 256 + j * 64, fb);
          tma2d(sb + j * SLOT, &mX, it * 256 + j * 64, m2 * 128, fb);
          mbar_expect_tx(fb, SLOT);
        }
      }
      mbar_wait(bars + B_MF * 8, 0);
      #pragma unroll 1
      for (int pc = 0; pc < 8; pc++) tma2d(sb + M_OFF + pc * 4096, &mQ, cp * 16, rank * 1024 + pc * 128, bars + B_Q * 8);
      auto load_wo = [&](int st, uint32_t ph) {
        const uint32_t j = st & 3, fb = bars + (B_FULL2 + j) * 8, k = fresh(g2_k(st, n2) * 64);
        mbar_wait(bars + (B_EMPTY2 + j) * 8, ph);
        TSTAMP(5, 16 + st);
        tma2d_mc(sb + j * SLOT + 16384 + rank * 8192, &mWo, n2 * 128 + rank * 64, k, fb);
        mbar_expect_tx(fb, 16384);
      };
      load_wo(4, 1);
      mbar_wait(bars + (B_EMPTY2 + 1) * 8, 1);
      asm volatile(ELECT "cp.async.bulk.tensor.5d.shared::cluster.global.mbarrier::complete_tx::bytes.multicast::cluster [%0], [%1, {%3, %4, %4, %4, %5}], [%2], %6;\n}"
        :: "r"(sb + SLOT + rank * 16384), "l"(&mWp), "r"(bars + (B_FULL2 + 1) * 8), "r"(n2 * 128 + rank * 64), "r"(0), "r"(n2 * 4), "h"((uint16_t)3) : "memory");
      mbar_expect_tx(bars + (B_FULL2 + 1) * 8, SLOT);
      load_wo(2, 1);
      load_wo(3, 1);
      mbar_arrive(bars + B_QE * 8);
      #pragma unroll 1
      for (int it = 1; it < 4; it++) {
        load_wo(4 * it + 1, (it - 1) & 1); load_wo(4 * it + 2, (it - 1) & 1); load_wo(4 * it + 3, (it - 1) & 1);
        if (it < 3) load_wo(4 * it + 4, (it - 1) & 1);
      }
    } else {
      if (warp == 13) {
      if ((sb & 0xffffff) != SB0) __trap();
      float4* zp = reinterpret_cast<float4*>(P.kv + hp * KV_PER_HP + mb * 264);
      const float4 z4 = make_float4(0.f, 0.f, 0.f, 0.f);
      zp[lane] = z4; zp[lane + 32] = z4;
      if (lane < 2) zp[lane + 64] = z4;
      if (lane == 0) P.cnt[hp * 32 + 8 + mb] = t_pf;
      {
        uint4* op = P.o + (m2 * 8 + n2) * 2048 + lane;
        uint32_t t0 = t_pf + RS_T0 + mb * (RS_DT / 8);
        #pragma unroll 1
        for (int i = 0; i < 8; i++) {
          while ((int)((uint32_t)clock() - t0) < 0) __nanosleep(100);
          t0 += RS_DT;
          #pragma unroll
          for (int j = 0; j < 8; j++) op[(i * 8 + j) * 32] = make_uint4(~0u, ~0u, ~0u, ~0u);
        }
      }
      fence_gpu();
      __syncwarp();
      unsigned gen = 0;
      if (lane == 0) gen = (atomicAdd(&P.cnt[hp * 32], 1u) >> 3) + 1;
      gen = uni(gen);
      sts32(sb + D_OFF + 40, gen);
      spin_until(&P.cnt[hp * 32], gen * 8);
      sts32(sb + D_OFF + 48, __ballot_sync(0xffffffffu, (TEST & 4) || __ldcg(&P.cnt[hp * 32 + 8 + (lane & 7)]) - t_pf + 4096 >= 8192));
      mbar_arrive(bars + B_Z * 8);
      }
      {
        float* kr = P.kv + hp * KV_PER_HP;
        mbar_wait(bars + B_Z * 8, 0);
        bar_sync(4, 352);
        #pragma unroll 1
        for (int i0 = max(warp * 6 - 80, 0); i0 < warp * 6 - 74; i0 += 2) {
          uint32_t p[2][4], q[2][4];
          const int i = (i0 + 2 * mb) & 15;
          const uint32_t pa = sb + M_OFF + (i & 3) * 2048 + (i >> 2) * 512 + (lane & 7) * 64 + (((lane >> 3) ^ (lane >> 1)) & 3) * 16;
          lds128(p[0], pa); lds128(q[0], pa + VT); lds128(p[1], pa + 2048); lds128(q[1], pa + VT + 2048);
          #pragma unroll
          for (int j = 0; j < 2; j++)
            asm volatile("red.relaxed.gpu.global.add.v4.f32 [%0], {%1,%2,%3,%4};" :: "l"(kr + (i + j) * 128 + lane * 4),
              "f"(__uint_as_float(p[j][0]) + __uint_as_float(q[j][0])), "f"(__uint_as_float(p[j][1]) + __uint_as_float(q[j][1])),
              "f"(__uint_as_float(p[j][2]) + __uint_as_float(q[j][2])), "f"(__uint_as_float(p[j][3]) + __uint_as_float(q[j][3])) : "memory");
        }
        if (warp == 13) {
          const uint32_t za = sb + M_OFF + 8192 + lane * 4;
          #pragma unroll
          for (int h = 0; h < 2; h++)
            asm volatile("red.relaxed.gpu.global.add.f32 [%0], %1;" :: "l"(kr + 2048 + h * 32 + lane),
              "f"(__uint_as_float(lds32(za + h * 128)) + __uint_as_float(lds32(za + h * 128 + VT))) : "memory");
        }
        bar_sync(5, 96);
        if (warp == 13) {
          mbar_arrive(mapa(bars, rank ^ 1) + B_KVL * 8);
          mbar_arrive(bars + B_MF * 8);
          OSTAMP(17);
          fence_gpu();
          red_add(&P.cnt[hp * 32 + 1]);
          OSTAMP(15);
        }
      }
      const unsigned gen = uni(lds32(sb + D_OFF + 40));
      {
        const int u0 = (15 - warp) * 3;
        const float* kg = P.kv + (2 * n2 + rank) * KV_PER_HP + u0 * 256;
        const uint32_t psb = uni(mapa(sb, rank ^ 1));
        auto put = [&](uint32_t o, uint32_t v0, uint32_t v1, uint32_t v2, uint32_t v3) {
          st_async128(psb + o, psb + BAR_OFF + B_KVB * 8, v0, v1, v2, v3);
          sts128(sb + o, v0, v1, v2, v3);
        };
        auto put8 = [&](int j, const float4* v) {
          put(KVB_OFF + (rank * 8 + u0 + j) * 640 + lane * 16, pack_bf16(v[0].x, v[0].y), pack_bf16(v[0].z, v[0].w), pack_bf16(v[1].x, v[1].y), pack_bf16(v[1].z, v[1].w));
        };
        mbar_wait(bars + B_KVL * 8, 0);
        spin_until(&P.cnt[(2 * n2 + rank) * 32 + 1], gen * 8);
        float4 v[3][2];
        #pragma unroll
        for (int j = 0; j < 2; j++) {
          const float4* kr = reinterpret_cast<const float4*>(kg + j * 256) + lane;
          v[j][0] = __ldcg(kr); v[j][1] = __ldcg(kr + 32);
        }
        if (warp == 13) {
          const float z0 = __ldcg(kg + 512 + lane), z1 = __ldcg(kg + 544 + lane);
          const uint32_t za = KVB_OFF + (rank * 8 + (lane >> 3)) * 640 + 512 + (lane & 7) * 16, a = pack_bf16(z0, z0), b = pack_bf16(z1, z1);
          put(za, a, a, a, a); put(za + 2560, b, b, b, b);
        } else {
          const float4* kr = reinterpret_cast<const float4*>(kg + 512) + lane;
          v[2][0] = __ldcg(kr); v[2][1] = __ldcg(kr + 32);
          put8(2, v[2]);
        }
        put8(0, v[0]); put8(1, v[1]);
        fence_async_smem();
        __syncwarp();
        mbar_arrive(bars + B_KVB * 8);
      }
      if (warp == 13) {
        bar_sync(6, 288);
        fence_gpu();
        asm volatile(ELECT "st.relaxed.gpu.global.u32 [%0], %1;\n}" :: "l"(&P.cnt[(16 + m2) * 32 + n2]), "r"(gen) : "memory");
        OSTAMP(32);
      } else {
        const int wg = 15 - warp;
        const uint32_t ab = bars + B_FA * 8 + wg * 32, far = uni(lds32(sb + D_OFF + 48));
        const unsigned* fp = &P.cnt[(32 + m2 * 2 + wg) * 32 + lane];
        uint32_t miss = ~0u, safe = t_pf;
        auto poll = [&]() {
          unsigned v;
          asm volatile("ld.relaxed.gpu.global.u32 %0, [%1];" : "=r"(v) : "l"(fp) : "memory");
          miss = __ballot_sync(0xffffffffu, v != gen);
        };
        mbar_arrive(ab + 8);
        mbar_wait(bars + B_QE * 8, 0);
        #pragma unroll 1
        for (int st = 2; st < 16; st += 2) {
          const int k = g2_k(st, n2), j = st & 3;
          const uint4* src = P.o + (m2 * 16 + k) * 1024 + wg * 512;
          const uint32_t eb = bars + (B_EMPTY2 + j) * 8, ph = ((st >> 2) - 1) & 1, dst = sb + j * SLOT + wg * 8192;
          if ((!(TEST & 2) || st > 6) && ((miss >> (2 * k)) & 15)) {
            #pragma unroll 1
            for (int n = 0; n < WAIT_BOUND && ((miss >> (2 * k)) & 15); n++) poll();
            fence_async_global();
            safe = (uint32_t)clock() + FAR_DT;
          }
          if (st >= 4) {
            if ((far >> (k >> 1)) & 1) while ((int)(uni((uint32_t)clock()) - safe) < 0) {}
            mbar_wait(eb, j ? ph : ph ^ 1);
          }
          bulk_load(dst, src, 8192, ab + j * 8);
          mbar_expect_tx(ab + j * 8, 8192);
          if (st >= 4) mbar_wait(eb + 8, ph);
          bulk_load(dst + SLOT, src + 1024, 8192, ab + j * 8 + 8);
          mbar_expect_tx(ab + j * 8 + 8, 8192);
          if (st == 2) { OSTAMP(18 + wg * 15); if (wg) { sts32(sb + D_OFF + 44, (uint32_t)clock()); mbar_arrive(bars + B_GO * 8); } }
        }
        if (wg + rank + lane == 0) P.cnt[64 * 32 + id2 * 4] = 0;
      }
    }
  } else {
    asm volatile("setmaxnreg.inc.sync.aligned.u32 %0;" :: "n"(160));
    const int wg = warp >> 2;
    Team c;
    c.bars = bars; c.rel = mapa(bars, tid & 1); c.wofs = wg * 8192; c.lead = fresh((tid & 127) < 2);
    uint32_t key = P.one;
    auto gemm2 = [&](float* a, auto O_, auto SK_, auto last) {
      constexpr int O = O_.value, SK = SK_.value;
      static_assert(SK >= 1 && SK <= 3, "tail");
      uint32_t ph = 1;
      const uint32_t ab = bars + B_FA * 8 + wg * 32;
      #pragma unroll 1
      for (int it = 1; it < 4; it++, ph ^= 1) {
        c.wofs += P.one - 1;
        ring_step<false, O>(c, B_FULL2, ph ^ O, B_EMPTY2 + 3, c.lead, [&](auto f) { g2_issue<O, 0, (MID >> (1 + O)) & 1>(a, c, f); }, ab, ph ^ 1);
        if (!O && (tid & 127) == 0) OSTAMP(55 + wg * 4 + it);
        if (O && (tid & 127) == 0) OSTAMP(40 + wg * 4 + it);
        if (SK == 3 && it == 3) break;
        ring_step<false, O>(c, B_FULL2 + 1, ph, B_EMPTY2, (!O || it < 3 ? c.lead : 0), [&](auto f) { g2_issue<O, 1, (MID >> (1 + O)) & 1>(a, c, f); }, ab + 8, ph);
        if (SK == 2 && it == 3) break;
        ring_step<false, O>(c, B_FULL2 + 2, ph, B_EMPTY2 + 1, (!O || it < 3 ? c.lead : 0), [&](auto f) { g2_issue<O, 2, (MID >> (1 + O)) & 1>(a, c, f); }, ab + 16, ph);
        if (SK == 1 && it == 3) break;
        ring_step<false, O>(c, B_FULL2 + 3, ph, B_EMPTY2 + 2, c.lead, [&](auto f) { g2_issue<O, 3, (MID >> (1 + O)) & 1>(a, c, f); }, ab + 24, ph);
      }
      if (!O) {
        auto rel = [&](int jj, bool on) { arrive_at(c.rel + (B_EMPTY2 + jj) * 8, on ? c.lead : 0); };
        if (wg) { wg_wait<0>(); rel(3 - SK, true); mbar_wait(bars + B_SK * 8, 1); }
        auto st = [&](auto J_) {
          constexpr int J = J_.value;
          mbar_wait(bars + (B_FULL2 + J) * 8, 1);
          g2_half<0, J, 0>(a, c);
          wg_wait<1>(); rel(J - 1, J > 4 - SK || !wg);
          g2_half<0, J, 1>(a, c);
          if (J < 3) wg_wait<1>();
        };
        if (SK >= 3) st(IC<1>());
        if (SK >= 2) st(IC<2>());
        st(IC<3>());
        arrive_at(bars + B_SK * 8, fresh_tid() == 0);
        last();
        wg_wait<0>(); rel(3, true);
      } else
      skew_tail<SK>(c, O ^ 1,
        [&]() {
          auto full = [&](int jj) { mbar_wait(bars + (B_FULL2 + jj) * 8, 1); mbar_wait(ab + jj * 8, 1); };
          if (SK >= 3) { full(1); g2_issue<O, 1>(a, c); }
          if (SK >= 2) { full(2); g2_issue<O, 2>(a, c); }
          full(3); g2_issue<O, 3>(a, c);
        },
        [](int) {});
      pinv<64>(a);
    };
    float aq[64];
    {
      float aK[64], aV[64];
      if (wg == 0) { kv_issue<0>(aK, aV, 0, 0); wg_wait<0>(); }
      cluster_wait();
      if (wg == 1) mbar_wait(bars + B_F0 * 8, 0);
      static_assert(SK1 >= 1 && SK1 <= 3, "tail");
      uint32_t ph = 0, xs = 2, xp = 0;
      auto next_x = [&]() { if (xs == 1) xp ^= 1; xs = xs == 2 ? 0 : xs + 1; };
      uint32_t rel = 0;
      int look = 5;
      uint32_t xo = xs * SLOT + wg * 16384;
      #pragma unroll 1
      for (int it = 0; it < 8; it++, ph ^= 1) {
        ring_step<false, true>(c, B_FULL, ph, B_EMPTY + 3, rel, [&](auto f) { kv_issue<0, MID & 1>(aK, aV, xo, it, f); if (tid == 0 && it == 0) OSTAMP(1); }, bars + (B_XF + xs) * 8, xp);
        if (SK1 == 3 && it == 7) break;
        next_x();
        ring_step<false>(c, B_FULL + 1, ph, B_EMPTY, c.lead, [&](auto f) { kv_issue<1, MID & 1>(aK, aV, xo, 1, f); });
        if (SK1 == 2 && it == 7) break;
        xo = xs * SLOT + wg * 16384;
        ring_step<false, true>(c, B_FULL + 2, ph, B_EMPTY + 1, c.lead, [&](auto f) { kv_issue<2, MID & 1>(aK, aV, xo, 1, f); }, bars + (B_XF + xs) * 8, xp);
        if (SK1 == 1 && it == 7) break;
        next_x();
        ring_step<false>(c, B_FULL + 3, ph, B_EMPTY + 2, c.lead, [&](auto f) { kv_issue<3, MID & 1>(aK, aV, xo, 1, f); });
        rel = c.lead;
        xo = xs * SLOT + wg * 16384;
        if (it == look && wrong_job()) { mbar_wait(bars + B_EX * 8, 0); it = look = -1; }
      }
      skew_tail<SK1>(c, 0,
        [&]() {
          auto wait = [&](uint32_t a) { mbar_wait(a, 1); };
          if (SK1 >= 3) { wait(bars + (B_FULL + 1) * 8); kv_issue<1>(aK, aV, SLOT + wg * 16384, 1); }
          if (SK1 >= 2) { wait(bars + (B_FULL + 2) * 8); wait(bars + (B_XF + 2) * 8); kv_issue<2>(aK, aV, 2 * SLOT + wg * 16384, 1); }
          wait(bars + (B_FULL + 3) * 8); kv_issue<3>(aK, aV, 2 * SLOT + wg * 16384, 1);
        },
        [&](int i) { arrive_at(c.rel + (B_EMPTY + ((32 - SK1 + i) & 3)) * 8, c.lead); });
      pinv<64>(aV); pinv<64>(aK);
      if (tid == 128) OSTAMP(3);
      const uint32_t vb = sb + M_OFF + wg * VT;
      float kv[36];
      uint32_t kf[4][8];
      const uint64_t dv = dofs(cdesc(M_OFF, 1152, 128, 0), wg * VT);
      const int t = fresh_tid();
      const uint32_t va = vb + ((t >> 4) & 1) * 1152 + ((t >> 5) & 3) * 256 + (t & 15) * 16;
      mbar_wait(bars + B_X * 8, 0);
      #pragma unroll
      for (int i = 0; i < 8; i++) {
        const float* a = aV + 8 * i;
        stsm4(va + i * 2304, pack_bf16(a[0], a[1]), pack_bf16(a[2], a[3]), pack_bf16(a[4], a[5]), pack_bf16(a[6], a[7]));
      }
      phi_a(aK + 48, kf[3]);
      mbar_wait(bars + B_FULL2 * 8, 0);
      if ((tid & 127) == 0) OSTAMP(50 + wg);
      g2_issue<0, 0, false, true>(aq, c);
      sched_fence(key++);
      sts128(vb + ((t & 127) >> 3) * 1152 + 1024 + (t & 7) * 16, 0x3f803f80u, 0x3f803f80u, 0x3f803f80u, 0x3f803f80u);
      phi_a(aK + 32, kf[2]); phi_b(aK + 48, kf[3]);
      sched_fence(key++);
      ring_step<true>(c, B_FULL2 + 1, 0, B_EMPTY2, c.lead, [&]() { g2_issue<0, 1>(aq, c); });
      sched_fence(key++);
      phi_a(aK + 16, kf[1]); phi_b(aK + 32, kf[2]);
      sched_fence(key++);
      ring_step<true>(c, B_FULL2 + 2, 0, B_EMPTY2 + 1, c.lead, [&]() { g2_issue<0, 2>(aq, c); });
      sched_fence(key++);
      phi_a(aK, kf[0]); phi_b(aK + 16, kf[1]);
      sched_fence(key++);
      fence_async_smem(); bar_sync(1 + wg, 128);
      phi_b(aK, kf[0]);
      sched_fence(key++);
      wg_fence();
      #pragma unroll
      for (int ks = 0; ks < 8; ks++) {
        if (ks == 0) rs72z<0>(kv, kf[0], dv); else rs72a<0>(kv, kf[ks >> 1] + 4 * (ks & 1), dofs(dv, ks * 2304));
      }
      wg_commit();
      wg_wait<1>();
      arrive_at(c.rel + (B_EMPTY2 + 2) * 8, c.lead);
      mbar_wait(bars + (B_FULL2 + 3) * 8, 0);
      g2_issue<0, 3>(aq, c);
      wg_wait<1>();
      pinv<36>(kv);
      const int a = fresh_tid() & 127;
      const bool hi = a >= 64;
      #pragma unroll
      for (int u = 0; u < 4; u++) {
        const int o = (u & 1) * 8 + (u & 2);
        sts128(vb + (a ^ ((a >> 3) & 3)) * 16 + u * 2048, __float_as_uint(hi ? kv[16 + o] : kv[o]), __float_as_uint(hi ? kv[17 + o] : kv[o + 1]),
               __float_as_uint(hi ? kv[20 + o] : kv[o + 4]), __float_as_uint(hi ? kv[21 + o] : kv[o + 5]));
      }
      if ((a & 3) < 2) sts32(vb + 8192 + ((a >> 5) * 16 + ((a & 31) >> 2) + (a & 1) * 8) * 4, __float_as_uint((a & 1) ? kv[34] : kv[32]));
      bar_arrive(4, 352);
    }
    if (tid == 0) OSTAMP(4);
    if (tid == 128) OSTAMP(5);
    float acc[64];
    {
      uint32_t kvok;
      gemm2(aq, IC<0>(), IC<SK2>(), [&]() {
        kvok = mbar_try(bars + B_KVB * 8, 0);
        if (kvok) fence_async_smem();
      });
      if (tid == 0) OSTAMP(6);
      if (tid == 128) OSTAMP(7);
      constexpr uint64_t dk = cdesc(KVB_OFF, 640, 128, 0);
      const uint32_t id2 = job(); IDS(id2);
      float nu[4][20];
      uint32_t pq[4][8], o[4][2][4];
      const int t2 = fresh_tid();
      const uint32_t oo = (t2 & 96) * 32 + (t2 & 28) * 16 + ((t2 ^ (t2 >> 3)) & 3) * 16;
      uint4* og = P.o + ((m2 * 8 + n2) * 4 + wg) * 512 + (oo >> 4);
      auto o_put = [&](int h, int e) {
        asm volatile("st.global.v4.b32 [%0], {%1,%2,%3,%4};" :: "l"(og + (h >> 1) * 1024 + (h & 1) * 256 + e * 32),
          "r"(o[h][e][0]), "r"(o[h][e][1]), "r"(o[h][e][2]), "r"(o[h][e][3]) : "memory");
      };
      auto o_out = [&](int h) {
        pinv<20>(nu[h]);
        #pragma unroll
        for (int e = 0; e < 2; e++) {
          const float* n = nu[h] + 2 * e;
          const float iv = rcp_fast(n[16] + 1e-6f);
          #pragma unroll
          for (int i = 0; i < 4; i++) o[h][e][i] = pack_bf16(n[4 * i] * iv, n[4 * i + 1] * iv);
          o_put(h, e);
        }
      };
      auto o_mma = [&](int h) {
        wg_fence();
        rs40z<1>(nu[h], pq[h], dk + h * (2560 >> 4));
        rs40a<1>(nu[h], pq[h] + 4, dk + h * (2560 >> 4) + (1280 >> 4));
        wg_commit();
      };
      phi_s(aq, pq[0]); phi_e(aq); phi_s(aq + 16, pq[1]);
      if (!kvok) { mbar_wait(bars + B_KVB * 8, 0); fence_async_smem(); }
      const uint32_t gen = lds32(sb + D_OFF + 40), far = lds32(sb + D_OFF + 48);
      #pragma unroll
      for (int u = 0; u < 4; u++) {
        if (u < 3) phi_e(aq + 16 * u + 16);
        phi_b(aq + 16 * u, pq[u]);
        o_mma(u);
        if (u < 2) phi_s(aq + 16 * u + 32, pq[u + 2]);
        if (u > 0) { wg_wait<1>(); o_out(u - 1); }
        sched_fence(key++);
      }
      wg_wait<0>(); o_out(3);
      asm volatile(ELECT "st.relaxed.gpu.global.u32 [%0], %1;\n}" :: "l"(&P.cnt[(32 + m2 * 2 + wg) * 32 + n2 * 4 + (warp & 3)]), "r"(gen) : "memory");
      bar_arrive(6, 288);
      arrive_at(bars + B_OD * 8, t2 == 128);
      if ((t2 & 127) == 0) OSTAMP(8 + wg * 2);
      {
        sched_fence(key++);
        #pragma unroll
        for (int i = 0; i < 32; i++) asm volatile("lop3.b32 %0, %1, %2, 0, 0xf0 | 0xcc;" : "=r"(o[i >> 3][(i >> 2) & 1][i & 3]) : "r"(o[i >> 3][(i >> 2) & 1][i & 3]), "r"(P.one - 1));
      }
      if (wg == 0) mbar_wait(bars + B_OD * 8, 0);
      mbar_wait(bars + (B_FULL2 + 1) * 8, 0);
      wg_fence();
      #pragma unroll
      for (int i = 0; i < 8; i++) {
        const uint32_t f[4] = {o[i >> 1][0][i & 1], o[i >> 1][1][i & 1], o[i >> 1][0][2 + (i & 1)], o[i >> 1][1][2 + (i & 1)]};
        constexpr uint64_t dw = cdesc(SLOT, 16384, 2048, 1);
        if (i == 0) rs128z<1>(acc, f, dw); else rs128a<1>(acc, f, dw + (((i >> 1) * 4096 + (i & 1) * 1024) >> 4));
      }
      wg_commit();
      if ((t2 & 127) == 0) OSTAMP(37 + wg);
      const uint32_t ab = bars + B_FA * 8 + wg * 32;
      const int k2 = g2_k(2, n2);
      const bool doubt = (uni(far) >> (k2 >> 1)) & 1;
      auto look = [&](int j) {
        if (doubt) {
          const uint32_t a = sb + (2 + j) * SLOT + wg * 8192 + (t2 & 96) * 32;
          if (__any_sync(0xffffffffu, lds32(a + (t2 & 16) * 256 + (t2 & 15) * 64 + (t2 & 30) * 2) == ~0u)) {
            const uint4* src = P.o + (m2 * 16 + k2 + j) * 1024 + wg * 512 + (t2 & 96) * 2 + (t2 & 31);
            if ((t2 & 31) == 0) OSTAMP(34);
            #pragma unroll 1
            for (int i = 0; i < 4; i++) {
              uint32_t v[4];
              int n = 0;
              do asm volatile("ld.relaxed.gpu.global.v4.u32 {%0,%1,%2,%3}, [%4];" : "=r"(v[0]), "=r"(v[1]), "=r"(v[2]), "=r"(v[3]) : "l"(src + (i & 1) * 32 + (i >> 1) * 256) : "memory");
              while (__any_sync(0xffffffffu, v[0] == ~0u) && ++n < 64);
              sts128(a + (t2 & 31) * 16 + (i & 1) * 512 + (i >> 1) * 4096, v[0], v[1], v[2], v[3]);
            }
            fence_async_smem();
            __syncwarp();
          }
        }
      };
      #pragma unroll 1
      for (int j = 0; j < 2; j += P.one)
        ring_step<true, true>(c, B_FULL2 + 2 + j, 0, B_EMPTY2 + 1 + j, c.lead, [&]() {
          look(j);
          if ((t2 & 127) == 0 && j == 0) OSTAMP(11 + wg * 24);
          const uint64_t da = dofs(cdesc(2 * SLOT, 16, 512, 2), c.wofs + j * SLOT), db = dofs(cdesc(2 * SLOT + 16384, 8192, 1024, 1), j * SLOT);
          wg_fence();
          #pragma unroll
          for (int i = 0; i < 4; i++) ss128a<0, 1>(acc, dofs(da, (i & 1) * 32 + (i >> 1) * 4096), dofs(db, i * 2048));
          wg_commit();
        }, ab + 16 + j * 8, 0);
    }
    gemm2(acc, IC<1>(), IC<SK3>(), []() {});
    if (tid == 0) OSTAMP(13);
    if (tid == 128) OSTAMP(14);
    {
      const uint32_t id2 = job(); IDS(id2);
      const int t2 = fresh_tid();
      const int row = ((t2 >> 5) & 3) * 16 + (t2 & 15);
      const int cq = (t2 >> 4) & 1, sw = t2 & 7;
      const uint32_t stg = sb + (EHI ? T_OFF : 0) + wg * 8192;
      constexpr uint32_t HS = EHI ? 16384 : SLOT;
      if (EHI) mbar_wait(bars + B_CD * 8, 0);
      #pragma unroll 1
      for (int pass = 0;; pass++) {
      const bool bad = acc[0] != acc[0] || acc[2] != acc[2];
      #pragma unroll
      for (int hf = 0; hf < 2; hf++) {
        #pragma unroll
        for (int jj = 0; jj < 4; jj++) {
          const int o = hf * 32 + jj * 8;
          stsm4(stg + hf * HS + row * 128 + (((2 * jj + cq) ^ sw) << 4),
                pack_bf16(acc[o], acc[o + 1]), pack_bf16(acc[o + 2], acc[o + 3]),
                pack_bf16(acc[o + 4], acc[o + 5]), pack_bf16(acc[o + 6], acc[o + 7]));
        }
        fence_async_smem();
        __syncwarp();
        tma2d_store(&mOut, 1024 + n2 * 128 + hf * 64, m2 * 128 + warp * 16, sb + (EHI ? T_OFF : 0) + hf * HS + warp * 2048);
      }
      bulk_commit();
      uint32_t redo;
      asm volatile("{\n.reg .pred p, q;\nsetp.ne.b32 p, %1, 0;\nbar.red.or.pred q, %2, 128, p;\nselp.u32 %0, 1, 0, q;\n}" : "=r"(redo) : "r"((uint32_t)bad), "r"(1 + wg) : "memory");
      if (!uni(redo) || pass) break;
      if ((t2 & 127) == 0) OSTAMP(48 + wg);
      asm volatile("cp.async.bulk.wait_group 0;" ::: "memory");
      spin_until(&P.cnt[(16 + m2) * 32 + (t2 & 7)], lds32(sb + D_OFF + 40));
      fence_async_global();
      const uint32_t ab = bars + B_FA * 8 + wg * 32;
      #pragma unroll 1
      for (int k = 0; k < 16; k += P.one) {
        bar_sync(1 + wg, 128);
        if ((warp & 3) == 0) {
          mbar_expect_tx(ab, 24576);
          bulk_load(sb + c.wofs, P.o + (m2 * 16 + k) * 1024 + wg * 512, 8192, ab);
          tma2d(sb + SLOT + c.wofs, &mWo, n2 * 128, k * 64, ab);
          tma2d(sb + 2 * SLOT + c.wofs, &mWo, n2 * 128 + 64, k * 64, ab);
        }
        mbar_wait(ab, ~k & 1);
        const uint64_t da = dofs(cdesc(0, 16, 512, 2), c.wofs), db = dofs(cdesc(SLOT, SLOT, 1024, 1), c.wofs);
        wg_fence();
        ss128p<0, 1>(acc, da, db, k);
        ss128a<0, 1>(acc, dofs(da, 32), dofs(db, 2048));
        ss128a<0, 1>(acc, dofs(da, 4096), dofs(db, 4096));
        ss128a<0, 1>(acc, dofs(da, 4128), dofs(db, 6144));
        wg_commit();
        wg_wait<0>(); pinv<64>(acc);
      }
      }
      bulk_wait_read();
    }
  }
}

typedef CUresult (*EncodeFn)(CUtensorMap*, CUtensorMapDataType, cuuint32_t, void*, const cuuint64_t*, const cuuint64_t*,
                             const cuuint32_t*, const cuuint32_t*, CUtensorMapInterleave, CUtensorMapSwizzle,
                             CUtensorMapL2promotion, CUtensorMapFloatOOBfill);

void encode(EncodeFn fn, CUtensorMap* m, const void* ptr, int rank, const cuuint64_t* dims, const cuuint64_t* strides,
            const cuuint32_t* box, CUtensorMapSwizzle sw, CUtensorMapL2promotion pr) {
  const cuuint32_t es[5] = {1, 1, 1, 1, 1};
  fn(m, CU_TENSOR_MAP_DATA_TYPE_BFLOAT16, rank, const_cast<void*>(ptr), dims, strides, box, es,
     CU_TENSOR_MAP_INTERLEAVE_NONE, sw, pr, CU_TENSOR_MAP_FLOAT_OOB_FILL_NONE);
}

}

extern "C" void kernel_launch(void* const* d_in, const int* in_sizes, int n_in, void* d_out, int out_size) {
  (void)in_sizes; (void)n_in; (void)out_size;
  static EncodeFn fn = nullptr;
  static void *po, *pkv, *pcnt;
  if (!fn) {
    void* p = nullptr; cudaDriverEntryPointQueryResult qr;
    cudaGetDriverEntryPoint("cuTensorMapEncodeTiled", &p, cudaEnableDefault, &qr);
    fn = (EncodeFn)p;
    cudaGetSymbolAddress(&po, g_O); cudaGetSymbolAddress(&pkv, g_kv); cudaGetSymbolAddress(&pcnt, g_cnt);
    cudaFuncSetAttribute(fused_kernel, cudaFuncAttributeMaxDynamicSharedMemorySize, SMEM_BYTES);
  }
  const CUtensorMapL2promotion P128 = CU_TENSOR_MAP_L2_PROMOTION_L2_128B, P0 = CU_TENSOR_MAP_L2_PROMOTION_NONE;
  CUtensorMap mX, mW, mWq, mWo, mK, mV, mH, mQ, mOut, mOutA, mWp;
  { cuuint64_t d[2] = {1024, 2048}, s[1] = {2048}; cuuint32_t bx[2] = {64, 128}, bq[2] = {16, 128};
    encode(fn, &mX, d_in[6], 2, d, s, bx, CU_TENSOR_MAP_SWIZZLE_128B, P128);
    encode(fn, &mQ, d_in[0], 2, d, s, bq, CU_TENSOR_MAP_SWIZZLE_NONE, P128); }
  { cuuint64_t d[3] = {1024, 1024, 3}, s[2] = {6144, 2048}; cuuint32_t bx[3] = {64, 32, 2};
    encode(fn, &mW, d_in[7], 3, d, s, bx, CU_TENSOR_MAP_SWIZZLE_128B, P128); }
  { cuuint64_t d[2] = {1024, 1024}, s[1] = {6144}, so[1] = {2048}; cuuint32_t bx[2] = {64, 64};
    encode(fn, &mWq, d_in[7], 2, d, s, bx, CU_TENSOR_MAP_SWIZZLE_128B, P128);
    encode(fn, &mWo, d_in[8], 2, d, so, bx, CU_TENSOR_MAP_SWIZZLE_128B, P128); }
  { cuuint64_t d[5] = {1024, 2, 4, 4, 32}, s[4] = {2048, 16384, 4096, 65536}; cuuint32_t bx[5] = {64, 2, 4, 4, 4};
    encode(fn, &mWp, d_in[8], 5, d, s, bx, CU_TENSOR_MAP_SWIZZLE_128B, P128); }
  { cuuint64_t d[3] = {1024, 128, 16}, s[2] = {32768, 2048}; cuuint32_t bk[3] = {16, 17, 8}, bv[3] = {16, 16, 8};
    encode(fn, &mK, d_in[1], 3, d, s, bk, CU_TENSOR_MAP_SWIZZLE_32B, P128);
    encode(fn, &mV, d_in[2], 3, d, s, bv, CU_TENSOR_MAP_SWIZZLE_32B, P128); }
  { cuuint64_t d[2] = {16, 131072}, s[1] = {32}; cuuint32_t bx[2] = {16, 128};
    encode(fn, &mH, d_in[4], 2, d, s, bx, CU_TENSOR_MAP_SWIZZLE_32B, CU_TENSOR_MAP_L2_PROMOTION_L2_256B); }
  { cuuint64_t d[2] = {2048, 2048}, s[1] = {4096}; cuuint32_t bx[2] = {64, 16}, ba[2] = {16, 32};
    encode(fn, &mOut, d_out, 2, d, s, bx, CU_TENSOR_MAP_SWIZZLE_128B, P0);
    encode(fn, &mOutA, d_out, 2, d, s, ba, CU_TENSOR_MAP_SWIZZLE_NONE, P0); }
  Params P;
  P.shift = (const __nv_bfloat16*)d_in[3]; P.ssmD = (const __nv_bfloat16*)d_in[5];
  P.x = (const __nv_bfloat16*)d_in[6]; P.w = (const __nv_bfloat16*)d_in[7]; P.out = (__nv_bfloat16*)d_out; P.one = 1;
  P.o = (uint4*)po; P.kv = (float*)pkv; P.cnt = (unsigned*)pcnt;
  P.k = (const char*)d_in[1]; P.v = (const char*)d_in[2];
  P.pt[0] = {(const char*)d_in[6], 16 * 32768, 64 * 32768, 65536, 32768, 256, 4096, 2048};
  P.pt[1] = {(const char*)d_in[7] + 2048, 256, 1024, 16 * 6144, 8 * 6144, 128 * 6144, 6144, 2048};
  P.pt[2] = {(const char*)d_in[7], 512, 128 * 6144, 16 * 6144, 8 * 6144, 256 * 6144, 6144, 256};
  P.pt[3] = {(const char*)d_in[8], 512, 128 * 2048, 16 * 2048, 8 * 2048, 256 * 2048, 2048, 256};
  P.pt[4] = {(const char*)d_in[0], 256, 1024, 32768, 2097152, 262144, 4096, 2048};
  P.pt[5] = {(const char*)d_in[4], 16 * 32768, 64 * 32768, 65536, 32768, 4096, 512, 256};
  const uint8_t pf[32] = {PF_LIST};
  for (int i = 0; i < 32; i++) P.pf[i] = pf[i];
  const uint64_t cd[18] = {CONV_DESC};
  for (int i = 0; i < 18; i++) P.cd[i] = cd[i];
  fused_kernel<<<NCTA, NTHREADS, SMEM_BYTES, cudaStreamPerThread>>>(P, mX, mW, mWq, mWo, mK, mV, mH, mQ, mOut, mOutA, mWp);
}
```

```cpp
#include <cuda_runtime.h>
#include <cuda_bf16.h>
#include <cuda.h>
#include <stdint.h>

#define PARAM(name, value) constexpr int name = value
#define TUNE
namespace dflt {
PARAM(SK1, 2); PARAM(SK2, 3); PARAM(SK3, 3);
PARAM(MID, 3);
PARAM(STG_T0, 700); PARAM(STG_DT, 540);
PARAM(RS_T0, 12000); PARAM(RS_DT, 600);
PARAM(FAR_DT, 400);
PARAM(OA_END, 7400); PARAM(OA_MIN, 200); PARAM(OA_MAX, 450);
PARAM(PF_DT0, 400); PARAM(PF_DT1, 1100); PARAM(PF_DT2, 540); PARAM(PF_N1, 9);
PARAM(TEST, 0);
PARAM(QP, 0); PARAM(EHI, 1); PARAM(FG, 2); PARAM(CI, 1); PARAM(CW, 2);
}
#define PF_LIST 0x01, 0x11, 0x02, 0x12, 0x03, 0x13, 0x04, 0x14, 0x05, 0x15, 0x51, 0x06, 0x16, 0x20, 0x07, 0x17, 0x21, 0x22, 0x23, \
                0x40, 0x41, 0x42, 0x43, 0x44, 0x45, 0x46, 0x47, 0x30, 0x31, 0x32, 0x33
#define PF_N 31
#define WAIT_BOUND 262144

namespace {
using namespace dflt;
TUNE

constexpr int S_LEN = 2048;
constexpr int DM    = 1024;
constexpr int NCTA  = 128;
constexpr int NTHREADS = 512;
constexpr int SLOT  = 32768;
constexpr int W_OFF = 3 * SLOT;
constexpr int M_OFF = 4 * SLOT;
constexpr int VT    = 16 * 1152;
constexpr int T_OFF = M_OFF + 43008;
constexpr int XS    = 4096 + 16;
constexpr int YX    = 2048 + 16;
constexpr int X_OFF = T_OFF + 8192 + 2176;
constexpr int H_OFF = X_OFF + 8 * XS;
constexpr int A_OFF = H_OFF + 4096;
constexpr int F_OFF = A_OFF + 8192;
constexpr int BAR_OFF = F_OFF + 2048;
constexpr int D_OFF = BAR_OFF + 384;
constexpr int SMEM_BYTES = D_OFF + 64 + 256;
constexpr int KB = 8704;
constexpr int KVB_OFF = M_OFF + 32768;
static_assert(H_OFF % 256 == 0 && X_OFF % 128 == 0 && SMEM_BYTES <= 232448, "layout");
constexpr int B_XF = 0, B_F0 = 3, B_FULL = 4, B_FA = 4, B_FULL2 = 25, B_KVL = 24, B_STG = 8, B_X = 12, B_Z = 13, B_H = 14, B_Q = 15, B_YR = 16,
              B_SK = 29, B_GO = 30, B_QE = 31,
              B_EMPTY = 32, B_KVB = 36, B_EMPTY2 = 37, B_SFREE = 41, B_CD = 43, B_MF = 44, B_OD = 45, B_EX = 46;
constexpr int KV_PER_HP = 2 * 1056;

__device__ __align__(1024) uint4 g_O[S_LEN * DM / 8];
__device__ __align__(128) float g_kv[16 * KV_PER_HP];
__device__ __align__(128) unsigned g_cnt[81 * 32];

#define OSTAMP(i) do {} while (0)
#define TSTAMP(k, i) do {} while (0)

__device__ __forceinline__ uint32_t wanted_job() {
  uint32_t t;
  asm volatile("mov.u32 %0, %%smid;" : "=r"(t));
  if (TEST & 1) t = t * 3 % 100;
  t >>= 1;
  const uint32_t q = ((t - 32) * 37) >> 8;
  uint32_t r;
  asm("{\n.reg .pred p, q;\nsetp.lt.u32 p, %3, 32;\nsetp.lt.u32 q, %3, 62;\nselp.u32 %0, %1, %2, q;\nselp.u32 %0, %3, %0, p;\n}" : "=&r"(r) : "r"(t + 1 + q), "r"((t - 58) * 8), "r"(t));
  return (r & 7) | ((((r & 7 ? 0x76154032 : 0x76543012) >> ((r >> 1) & 28)) & 7) << 3);
}

#define ELECT "{\n.reg .pred e;\nelect.sync _|e, 0xffffffff;\n@e "
__device__ __forceinline__ uint32_t uni(uint32_t v) { return __shfl_sync(0xffffffffu, v, 0); }
__device__ __forceinline__ uint32_t fresh(uint32_t v) { asm volatile("" : "+r"(v)); return v; }
__device__ __forceinline__ uint32_t smem_u32(const void* p) { return (uint32_t)__cvta_generic_to_shared(p); }
__device__ __forceinline__ void mbar_init(uint32_t b, uint32_t c) { asm volatile(ELECT "mbarrier.init.shared::cta.b64 [%0], %1;\n}" :: "r"(b), "r"(c) : "memory"); }
__device__ __forceinline__ void mbar_expect_tx(uint32_t b, uint32_t bytes) { asm volatile(ELECT "mbarrier.arrive.expect_tx.shared::cta.b64 _, [%0], %1;\n}" :: "r"(b), "r"(bytes) : "memory"); }
__device__ __forceinline__ void mbar_arrive(uint32_t b) { asm volatile(ELECT "mbarrier.arrive.shared::cluster.b64 _, [%0];\n}" :: "r"(b) : "memory"); }
__device__ __forceinline__ void mbar_wait(uint32_t b, uint32_t ph) {
  asm volatile("{\n.reg .pred p;\nWAIT_LOOP:\nmbarrier.try_wait.parity.shared::cta.b64 p, [%0], %1;\n@!p bra.uni WAIT_LOOP;\n}" :: "r"(b), "r"(ph) : "memory");
}
__device__ __forceinline__ void tma2d(uint32_t dst, const CUtensorMap* m, int c0, int c1, uint32_t bar) {
  asm volatile(ELECT "cp.async.bulk.tensor.2d.shared::cluster.global.mbarrier::complete_tx::bytes [%0], [%1, {%3, %4}], [%2];\n}"
    :: "r"(dst), "l"(m), "r"(bar), "r"(c0), "r"(c1) : "memory"); }
__device__ __forceinline__ void tma2d_mc(uint32_t dst, const CUtensorMap* m, int c0, int c1, uint32_t bar) {
  asm volatile(ELECT "cp.async.bulk.tensor.2d.shared::cluster.global.mbarrier::complete_tx::bytes.multicast::cluster [%0], [%1, {%3, %4}], [%2], %5;\n}"
    :: "r"(dst), "l"(m), "r"(bar), "r"(c0), "r"(c1), "h"((uint16_t)3) : "memory"); }
__device__ __forceinline__ void tma3d(uint32_t dst, const CUtensorMap* m, int c0, int c1, int c2, uint32_t bar) {
  asm volatile(ELECT "cp.async.bulk.tensor.3d.shared::cluster.global.mbarrier::complete_tx::bytes [%0], [%1, {%3, %4, %5}], [%2];\n}"
    :: "r"(dst), "l"(m), "r"(bar), "r"(c0), "r"(c1), "r"(c2) : "memory"); }
__device__ __forceinline__ void tma2d_store(const CUtensorMap* m, int c0, int c1, uint32_t src) {
  asm volatile(ELECT "cp.async.bulk.tensor.2d.global.shared::cta.bulk_group [%0, {%2, %3}], [%1];\n}"
    :: "l"(m), "r"(src), "r"(c0), "r"(c1) : "memory"); }
__device__ __forceinline__ void bulk_load(uint32_t dst, const void* src, uint32_t bytes, uint32_t bar) {
  asm volatile(ELECT "cp.async.bulk.shared::cluster.global.mbarrier::complete_tx::bytes [%0], [%1], %2, [%3];\n}"
    :: "r"(dst), "l"(src), "r"(bytes), "r"(bar) : "memory"); }
__device__ __forceinline__ void bulk_commit() { asm volatile("cp.async.bulk.commit_group;" ::: "memory"); }
__device__ __forceinline__ void bulk_wait_read() { asm volatile("cp.async.bulk.wait_group.read 0;" ::: "memory"); }
__device__ __forceinline__ void fence_async_smem() { asm volatile("fence.proxy.async.shared::cta;" ::: "memory"); }
__device__ __forceinline__ void bar_sync(int id, int n) { asm volatile("bar.sync %0, %1;" :: "r"(id), "r"(n) : "memory"); }
__device__ __forceinline__ void bar_arrive(int id, int n) { asm volatile("bar.arrive %0, %1;" :: "r"(id), "r"(n) : "memory"); }
__device__ __forceinline__ void wg_fence() { asm volatile("wgmma.fence.sync.aligned;" ::: "memory"); }
__device__ __forceinline__ void wg_commit() { asm volatile("wgmma.commit_group.sync.aligned;" ::: "memory"); }
template <int N> __device__ __forceinline__ void wg_wait() { asm volatile("wgmma.wait_group.sync.aligned %0;" :: "n"(N) : "memory"); }
constexpr uint32_t SB0 = 1024;
__host__ __device__ constexpr uint64_t cdesc(uint32_t off, uint32_t lbo, uint32_t sbo, uint32_t swz) {
  return (uint64_t)((SB0 + off) >> 4) | ((uint64_t)(lbo >> 4) << 16) | ((uint64_t)(sbo >> 4) << 32) | ((uint64_t)swz << 62); }
__device__ __forceinline__ uint64_t dofs(uint64_t d, uint32_t bytes) { return (d & 0xffffffff00000000ull) | (uint32_t)((uint32_t)d + (bytes >> 4)); }
__device__ __forceinline__ uint32_t mbar_try(uint32_t b, uint32_t ph) {
  uint32_t ok;
  asm volatile("{\n.reg .pred p;\nmbarrier.test_wait.parity.shared::cta.b64 p, [%1], %2;\nselp.u32 %0, 1, 0, p;\n}" : "=r"(ok) : "r"(b), "r"(ph) : "memory");
  return ok; }
__device__ __forceinline__ void arrive_at(uint32_t a, uint32_t on) {
  asm volatile("{\n.reg .pred p;\nsetp.ne.b32 p, %1, 0;\n@p mbarrier.arrive.shared::cluster.b64 _, [%0];\n}" :: "r"(a), "r"(on) : "memory"); }
__device__ __forceinline__ void ldsm4(uint32_t* r, uint32_t a) {
  asm volatile("ldmatrix.sync.aligned.m8n8.x4.shared.b16 {%0,%1,%2,%3}, [%4];" : "=r"(r[0]), "=r"(r[1]), "=r"(r[2]), "=r"(r[3]) : "r"(a) : "memory"); }
__device__ __forceinline__ void ldsm4t(uint32_t* r, uint32_t a) {
  asm volatile("ldmatrix.sync.aligned.m8n8.x4.trans.shared.b16 {%0,%1,%2,%3}, [%4];" : "=r"(r[0]), "=r"(r[1]), "=r"(r[2]), "=r"(r[3]) : "r"(a) : "memory"); }
__device__ __forceinline__ void stsm4(uint32_t a, uint32_t r0, uint32_t r1, uint32_t r2, uint32_t r3) {
  asm volatile("stmatrix.sync.aligned.m8n8.x4.shared.b16 [%0], {%1,%2,%3,%4};" :: "r"(a), "r"(r0), "r"(r1), "r"(r2), "r"(r3) : "memory"); }
__device__ __forceinline__ void stsm4t(uint32_t a, uint32_t r0, uint32_t r1, uint32_t r2, uint32_t r3) {
  asm volatile("stmatrix.sync.aligned.m8n8.x4.trans.shared.b16 [%0], {%1,%2,%3,%4};" :: "r"(a), "r"(r0), "r"(r1), "r"(r2), "r"(r3) : "memory"); }
__device__ __forceinline__ uint32_t lds32(uint32_t a) { uint32_t v; asm volatile("ld.shared.b32 %0, [%1];" : "=r"(v) : "r"(a) : "memory"); return v; }
__device__ __forceinline__ void lds128(uint32_t* v, uint32_t a) { asm volatile("ld.shared.v4.b32 {%0,%1,%2,%3}, [%4];" : "=r"(v[0]), "=r"(v[1]), "=r"(v[2]), "=r"(v[3]) : "r"(a) : "memory"); }
__device__ __forceinline__ void sts32(uint32_t a, uint32_t v) { asm volatile("st.shared.b32 [%0], %1;" :: "r"(a), "r"(v) : "memory"); }
__device__ __forceinline__ void sts128(uint32_t a, uint32_t v0, uint32_t v1, uint32_t v2, uint32_t v3) {
  asm volatile("st.shared.v4.b32 [%0], {%1,%2,%3,%4};" :: "r"(a), "r"(v0), "r"(v1), "r"(v2), "r"(v3) : "memory"); }
__device__ __forceinline__ uint32_t pack_bf16(float lo, float hi) { uint32_t r; asm("cvt.rn.bf16x2.f32 %0, %1, %2;" : "=r"(r) : "f"(hi), "f"(lo)); return r; }
template <int ID = 0> __device__ __forceinline__ void sched_fence(uint32_t key) {
  asm volatile("{\n.reg .pred p;\nsetp.eq.u32 p, %0, %1;\nSF_LOOP:\n@p pmevent 1;\n@p bra.uni SF_LOOP;\n}" :: "r"(key), "n"(ID) : "memory");
}
template <int N> __device__ __forceinline__ void pinv(float* v) {
  #pragma unroll
  for (int i = 0; i < N; i++) asm volatile("" : "+f"(v[i]) :: "memory"); }
__device__ __forceinline__ uint32_t bmul2(uint32_t a, uint32_t b) { uint32_t r; asm("mul.rn.bf16x2 %0, %1, %2;" : "=r"(r) : "r"(a), "r"(b)); return r; }
__device__ __forceinline__ uint32_t badd2(uint32_t a, uint32_t b) { uint32_t r; asm("add.rn.bf16x2 %0, %1, %2;" : "=r"(r) : "r"(a), "r"(b)); return r; }
__device__ __forceinline__ void spin_until(const unsigned* p, unsigned target) {
  int n = 0;
  unsigned v;
  do { asm volatile("ld.relaxed.gpu.global.u32 %0, [%1];" : "=r"(v) : "l"(p) : "memory"); } while ((int)(v - target) < 0 && ++n < WAIT_BOUND);
  asm volatile("fence.acquire.gpu;" ::: "memory");
}
__device__ __forceinline__ void cluster_wait() { asm volatile("barrier.cluster.wait.aligned;" ::: "memory"); }
__device__ __forceinline__ void fence_gpu() { asm volatile("fence.release.gpu;" ::: "memory"); }
__device__ __forceinline__ void fence_async_global() { asm volatile("fence.proxy.async.global;" ::: "memory"); }
__device__ __forceinline__ void red_add(unsigned* p) { asm volatile(ELECT "red.relaxed.gpu.global.add.u32 [%0], 1;\n}" :: "l"(p) : "memory"); }
__device__ __forceinline__ float rcp_fast(float x) { float r; asm("rcp.approx.ftz.f32 %0, %1;" : "=f"(r) : "f"(x)); return r; }
__device__ __forceinline__ uint32_t mapa(uint32_t a, uint32_t rank) { uint32_t r; asm("mapa.shared::cluster.u32 %0, %1, %2;" : "=r"(r) : "r"(a), "r"(rank)); return r; }
__device__ __forceinline__ void st_async128(uint32_t a, uint32_t bar, uint32_t v0, uint32_t v1, uint32_t v2, uint32_t v3) {
  asm volatile("st.async.weak.shared::cluster.mbarrier::complete_tx::bytes.v4.b32 [%0], {%2,%3,%4,%5}, [%1];"
    :: "r"(a), "r"(bar), "r"(v0), "r"(v1), "r"(v2), "r"(v3) : "memory"); }
__device__ __forceinline__ int fresh_tid() { int t; asm volatile("mov.u32 %0, %%tid.x;" : "=r"(t)); return t; }
__device__ __forceinline__ void pace(uint32_t& t, uint32_t dt) {
  uint32_t c;
  while ((int)((c = uni((uint32_t)clock())) - t) < 0) __nanosleep(40);
  t = ((int)(c - t) > (int)dt ? c : t) + dt;
}
template <int LOG> __device__ __forceinline__ void unit_root(int a, float& c, float& s) {
  const float x = (float)((a << (32 - LOG)) >> (32 - LOG)) * (6.283185307179586f / (1 << LOG));
  c = __cosf(x); s = __sinf(x); }

struct D2 { uint64_t a, b; };
template <int TA, int TB> __device__ __forceinline__ void ss128p(float* d, uint64_t da, uint64_t db, int sd) {
  asm volatile("{\n.reg .pred p;\nsetp.ne.b32 p, %68, 0;\n"
    "wgmma.mma_async.sync.aligned.m64n128k16.f32.bf16.bf16 "
    "{%0, %1, %2, %3, %4, %5, %6, %7, %8, %9, %10, %11, %12, %13, %14, %15, "
    "%16, %17, %18, %19, %20, %21, %22, %23, %24, %25, %26, %27, %28, %29, %30, %31, "
    "%32, %33, %34, %35, %36, %37, %38, %39, %40, %41, %42, %43, %44, %45, %46, %47, "
    "%48, %49, %50, %51, %52, %53, %54, %55, %56, %57, %58, %59, %60, %61, %62, %63}, %64, %65, p, 1, 1, %66, %67;\n}\n"
    : "+f"(d[0]), "+f"(d[1]), "+f"(d[2]), "+f"(d[3]), "+f"(d[4]), "+f"(d[5]), "+f"(d[6]), "+f"(d[7]),
      "+f"(d[8]), "+f"(d[9]), "+f"(d[10]), "+f"(d[11]), "+f"(d[12]), "+f"(d[13]), "+f"(d[14]), "+f"(d[15]),
      "+f"(d[16]), "+f"(d[17]), "+f"(d[18]), "+f"(d[19]), "+f"(d[20]), "+f"(d[21]), "+f"(d[22]), "+f"(d[23]),
      "+f"(d[24]), "+f"(d[25]), "+f"(d[26]), "+f"(d[27]), "+f"(d[28]), "+f"(d[29]), "+f"(d[30]), "+f"(d[31]),
      "+f"(d[32]), "+f"(d[33]), "+f"(d[34]), "+f"(d[35]), "+f"(d[36]), "+f"(d[37]), "+f"(d[38]), "+f"(d[39]),
      "+f"(d[40]), "+f"(d[41]), "+f"(d[42]), "+f"(d[43]), "+f"(d[44]), "+f"(d[45]), "+f"(d[46]), "+f"(d[47]),
      "+f"(d[48]), "+f"(d[49]), "+f"(d[50]), "+f"(d[51]), "+f"(d[52]), "+f"(d[53]), "+f"(d[54]), "+f"(d[55]),
      "+f"(d[56]), "+f"(d[57]), "+f"(d[58]), "+f"(d[59]), "+f"(d[60]), "+f"(d[61]), "+f"(d[62]), "+f"(d[63])
    : "l"(da), "l"(db), "n"(TA), "n"(TB), "r"(sd));
}
template <int TA, int TB> __device__ __forceinline__ void ss128a(float* d, uint64_t da, uint64_t db) {
  asm volatile("{\n.reg .pred p;\nsetp.eq.b32 p, 0, 0;\n"
    "wgmma.mma_async.sync.aligned.m64n128k16.f32.bf16.bf16 "
    "{%0, %1, %2, %3, %4, %5, %6, %7, %8, %9, %10, %11, %12, %13, %14, %15, "
    "%16, %17, %18, %19, %20, %21, %22, %23, %24, %25, %26, %27, %28, %29, %30, %31, "
    "%32, %33, %34, %35, %36, %37, %38, %39, %40, %41, %42, %43, %44, %45, %46, %47, "
    "%48, %49, %50, %51, %52, %53, %54, %55, %56, %57, %58, %59, %60, %61, %62, %63}, %64, %65, p, 1, 1, %66, %67;\n}\n"
    : "+f"(d[0]), "+f"(d[1]), "+f"(d[2]), "+f"(d[3]), "+f"(d[4]), "+f"(d[5]), "+f"(d[6]), "+f"(d[7]),
      "+f"(d[8]), "+f"(d[9]), "+f"(d[10]), "+f"(d[11]), "+f"(d[12]), "+f"(d[13]), "+f"(d[14]), "+f"(d[15]),
      "+f"(d[16]), "+f"(d[17]), "+f"(d[18]), "+f"(d[19]), "+f"(d[20]), "+f"(d[21]), "+f"(d[22]), "+f"(d[23]),
      "+f"(d[24]), "+f"(d[25]), "+f"(d[26]), "+f"(d[27]), "+f"(d[28]), "+f"(d[29]), "+f"(d[30]), "+f"(d[31]),
      "+f"(d[32]), "+f"(d[33]), "+f"(d[34]), "+f"(d[35]), "+f"(d[36]), "+f"(d[37]), "+f"(d[38]), "+f"(d[39]),
      "+f"(d[40]), "+f"(d[41]), "+f"(d[42]), "+f"(d[43]), "+f"(d[44]), "+f"(d[45]), "+f"(d[46]), "+f"(d[47]),
      "+f"(d[48]), "+f"(d[49]), "+f"(d[50]), "+f"(d[51]), "+f"(d[52]), "+f"(d[53]), "+f"(d[54]), "+f"(d[55]),
      "+f"(d[56]), "+f"(d[57]), "+f"(d[58]), "+f"(d[59]), "+f"(d[60]), "+f"(d[61]), "+f"(d[62]), "+f"(d[63])
    : "l"(da), "l"(db), "n"(TA), "n"(TB));
}
template <int TA, int TB> __device__ __forceinline__ void ss128z(float* d, uint64_t da, uint64_t db) {
  asm volatile("{\n.reg .pred p;\nsetp.ne.b32 p, 0, 0;\n"
    "wgmma.mma_async.sync.aligned.m64n128k16.f32.bf16.bf16 "
    "{%0, %1, %2, %3, %4, %5, %6, %7, %8, %9, %10, %11, %12, %13, %14, %15, "
    "%16, %17, %18, %19, %20, %21, %22, %23, %24, %25, %26, %27, %28, %29, %30, %31, "
    "%32, %33, %34, %35, %36, %37, %38, %39, %40, %41, %42, %43, %44, %45, %46, %47, "
    "%48, %49, %50, %51, %52, %53, %54, %55, %56, %57, %58, %59, %60, %61, %62, %63}, %64, %65, p, 1, 1, %66, %67;\n}\n"
    : "=f"(d[0]), "=f"(d[1]), "=f"(d[2]), "=f"(d[3]), "=f"(d[4]), "=f"(d[5]), "=f"(d[6]), "=f"(d[7]),
      "=f"(d[8]), "=f"(d[9]), "=f"(d[10]), "=f"(d[11]), "=f"(d[12]), "=f"(d[13]), "=f"(d[14]), "=f"(d[15]),
      "=f"(d[16]), "=f"(d[17]), "=f"(d[18]), "=f"(d[19]), "=f"(d[20]), "=f"(d[21]), "=f"(d[22]), "=f"(d[23]),
      "=f"(d[24]), "=f"(d[25]), "=f"(d[26]), "=f"(d[27]), "=f"(d[28]), "=f"(d[29]), "=f"(d[30]), "=f"(d[31]),
      "=f"(d[32]), "=f"(d[33]), "=f"(d[34]), "=f"(d[35]), "=f"(d[36]), "=f"(d[37]), "=f"(d[38]), "=f"(d[39]),
      "=f"(d[40]), "=f"(d[41]), "=f"(d[42]), "=f"(d[43]), "=f"(d[44]), "=f"(d[45]), "=f"(d[46]), "=f"(d[47]),
      "=f"(d[48]), "=f"(d[49]), "=f"(d[50]), "=f"(d[51]), "=f"(d[52]), "=f"(d[53]), "=f"(d[54]), "=f"(d[55]),
      "=f"(d[56]), "=f"(d[57]), "=f"(d[58]), "=f"(d[59]), "=f"(d[60]), "=f"(d[61]), "=f"(d[62]), "=f"(d[63])
    : "l"(da), "l"(db), "n"(TA), "n"(TB));
}
template <int TA, int TB> __device__ __forceinline__ void ss64a(float* d, uint64_t da, uint64_t db) {
  asm volatile("{\n.reg .pred p;\nsetp.eq.b32 p, 0, 0;\n"
    "wgmma.mma_async.sync.aligned.m64n64k16.f32.bf16.bf16 "
    "{%0, %1, %2, %3, %4, %5, %6, %7, %8, %9, %10, %11, %12, %13, %14, %15, "
    "%16, %17, %18, %19, %20, %21, %22, %23, %24, %25, %26, %27, %28, %29, %30, %31}, %32, %33, p, 1, 1, %34, %35;\n}\n"
    : "+f"(d[0]), "+f"(d[1]), "+f"(d[2]), "+f"(d[3]), "+f"(d[4]), "+f"(d[5]), "+f"(d[6]), "+f"(d[7]),
      "+f"(d[8]), "+f"(d[9]), "+f"(d[10]), "+f"(d[11]), "+f"(d[12]), "+f"(d[13]), "+f"(d[14]), "+f"(d[15]),
      "+f"(d[16]), "+f"(d[17]), "+f"(d[18]), "+f"(d[19]), "+f"(d[20]), "+f"(d[21]), "+f"(d[22]), "+f"(d[23]),
      "+f"(d[24]), "+f"(d[25]), "+f"(d[26]), "+f"(d[27]), "+f"(d[28]), "+f"(d[29]), "+f"(d[30]), "+f"(d[31])
    : "l"(da), "l"(db), "n"(TA), "n"(TB));
}
template <int TA, int TB> __device__ __forceinline__ void ss64z(float* d, uint64_t da, uint64_t db) {
  asm volatile("{\n.reg .pred p;\nsetp.ne.b32 p, 0, 0;\n"
    "wgmma.mma_async.sync.aligned.m64n64k16.f32.bf16.bf16 "
    "{%0, %1, %2, %3, %4, %5, %6, %7, %8, %9, %10, %11, %12, %13, %14, %15, "
    "%16, %17, %18, %19, %20, %21, %22, %23, %24, %25, %26, %27, %28, %29, %30, %31}, %32, %33, p, 1, 1, %34, %35;\n}\n"
    : "=f"(d[0]), "=f"(d[1]), "=f"(d[2]), "=f"(d[3]), "=f"(d[4]), "=f"(d[5]), "=f"(d[6]), "=f"(d[7]),
      "=f"(d[8]), "=f"(d[9]), "=f"(d[10]), "=f"(d[11]), "=f"(d[12]), "=f"(d[13]), "=f"(d[14]), "=f"(d[15]),
      "=f"(d[16]), "=f"(d[17]), "=f"(d[18]), "=f"(d[19]), "=f"(d[20]), "=f"(d[21]), "=f"(d[22]), "=f"(d[23]),
      "=f"(d[24]), "=f"(d[25]), "=f"(d[26]), "=f"(d[27]), "=f"(d[28]), "=f"(d[29]), "=f"(d[30]), "=f"(d[31])
    : "l"(da), "l"(db), "n"(TA), "n"(TB));
}
__device__ __forceinline__ void ss64x4(float* d, const D2* c, int on) {
  asm volatile("{\n.reg .pred p, z, c;\nsetp.eq.b32 p, 0, 0;\nsetp.ne.b32 z, 0, 0;\nsetp.eq.b32 c, %40, 0;\n"
    "wgmma.mma_async.sync.aligned.m64n64k16.f32.bf16.bf16 "
    "{%0, %1, %2, %3, %4, %5, %6, %7, %8, %9, %10, %11, %12, %13, %14, %15, "
    "%16, %17, %18, %19, %20, %21, %22, %23, %24, %25, %26, %27, %28, %29, %30, %31}, %32, %33, z, 1, 1, 0, 1;\n"
    "wgmma.commit_group.sync.aligned;\n@c bra.uni X4_DONE;\n"
    "wgmma.mma_async.sync.aligned.m64n64k16.f32.bf16.bf16 "
    "{%0, %1, %2, %3, %4, %5, %6, %7, %8, %9, %10, %11, %12, %13, %14, %15, "
    "%16, %17, %18, %19, %20, %21, %22, %23, %24, %25, %26, %27, %28, %29, %30, %31}, %34, %35, p, 1, 1, 0, 1;\n"
    "wgmma.mma_async.sync.aligned.m64n64k16.f32.bf16.bf16 "
    "{%0, %1, %2, %3, %4, %5, %6, %7, %8, %9, %10, %11, %12, %13, %14, %15, "
    "%16, %17, %18, %19, %20, %21, %22, %23, %24, %25, %26, %27, %28, %29, %30, %31}, %36, %37, p, 1, 1, 0, 1;\n"
    "wgmma.mma_async.sync.aligned.m64n64k16.f32.bf16.bf16 "
    "{%0, %1, %2, %3, %4, %5, %6, %7, %8, %9, %10, %11, %12, %13, %14, %15, "
    "%16, %17, %18, %19, %20, %21, %22, %23, %24, %25, %26, %27, %28, %29, %30, %31}, %38, %39, p, 1, 1, 0, 1;\n"
    "wgmma.commit_group.sync.aligned;\nX4_DONE:\n}\n"
    : "=f"(d[0]), "=f"(d[1]), "=f"(d[2]), "=f"(d[3]), "=f"(d[4]), "=f"(d[5]), "=f"(d[6]), "=f"(d[7]),
      "=f"(d[8]), "=f"(d[9]), "=f"(d[10]), "=f"(d[11]), "=f"(d[12]), "=f"(d[13]), "=f"(d[14]), "=f"(d[15]),
      "=f"(d[16]), "=f"(d[17]), "=f"(d[18]), "=f"(d[19]), "=f"(d[20]), "=f"(d[21]), "=f"(d[22]), "=f"(d[23]),
      "=f"(d[24]), "=f"(d[25]), "=f"(d[26]), "=f"(d[27]), "=f"(d[28]), "=f"(d[29]), "=f"(d[30]), "=f"(d[31])
    : "l"(c[0].a), "l"(c[0].b), "l"(c[1].a), "l"(c[1].b), "l"(c[2].a), "l"(c[2].b), "l"(c[3].a), "l"(c[3].b), "r"(on));
}
template <int TB> __device__ __forceinline__ void rs32a(float* d, const uint32_t* a, uint64_t db) {
  asm volatile("{\n.reg .pred p;\nsetp.eq.b32 p, 0, 0;\n"
    "wgmma.mma_async.sync.aligned.m64n32k16.f32.bf16.bf16 "
    "{%0, %1, %2, %3, %4, %5, %6, %7, %8, %9, %10, %11, %12, %13, %14, %15}, {%16, %17, %18, %19}, %20, p, 1, 1, %21;\n}\n"
    : "+f"(d[0]), "+f"(d[1]), "+f"(d[2]), "+f"(d[3]), "+f"(d[4]), "+f"(d[5]), "+f"(d[6]), "+f"(d[7]),
      "+f"(d[8]), "+f"(d[9]), "+f"(d[10]), "+f"(d[11]), "+f"(d[12]), "+f"(d[13]), "+f"(d[14]), "+f"(d[15])
    : "r"(a[0]), "r"(a[1]), "r"(a[2]), "r"(a[3]), "l"(db), "n"(TB));
}
template <int TB> __device__ __forceinline__ void rs32z(float* d, const uint32_t* a, uint64_t db) {
  asm volatile("{\n.reg .pred p;\nsetp.ne.b32 p, 0, 0;\n"
    "wgmma.mma_async.sync.aligned.m64n32k16.f32.bf16.bf16 "
    "{%0, %1, %2, %3, %4, %5, %6, %7, %8, %9, %10, %11, %12, %13, %14, %15}, {%16, %17, %18, %19}, %20, p, 1, 1, %21;\n}\n"
    : "=&f"(d[0]), "=&f"(d[1]), "=&f"(d[2]), "=&f"(d[3]), "=&f"(d[4]), "=&f"(d[5]), "=&f"(d[6]), "=&f"(d[7]),
      "=&f"(d[8]), "=&f"(d[9]), "=&f"(d[10]), "=&f"(d[11]), "=&f"(d[12]), "=&f"(d[13]), "=&f"(d[14]), "=&f"(d[15])
    : "r"(a[0]), "r"(a[1]), "r"(a[2]), "r"(a[3]), "l"(db), "n"(TB));
}
template <int TB> __device__ __forceinline__ void rs40a(float* d, const uint32_t* a, uint64_t db) {
  asm volatile("{\n.reg .pred p;\nsetp.eq.b32 p, 0, 0;\n"
    "wgmma.mma_async.sync.aligned.m64n40k16.f32.bf16.bf16 "
    "{%0, %1, %2, %3, %4, %5, %6, %7, %8, %9, %10, %11, %12, %13, %14, %15, "
    "%16, %17, %18, %19}, {%20, %21, %22, %23}, %24, p, 1, 1, %25;\n}\n"
    : "+f"(d[0]), "+f"(d[1]), "+f"(d[2]), "+f"(d[3]), "+f"(d[4]), "+f"(d[5]), "+f"(d[6]), "+f"(d[7]),
      "+f"(d[8]), "+f"(d[9]), "+f"(d[10]), "+f"(d[11]), "+f"(d[12]), "+f"(d[13]), "+f"(d[14]), "+f"(d[15]),
      "+f"(d[16]), "+f"(d[17]), "+f"(d[18]), "+f"(d[19])
    : "r"(a[0]), "r"(a[1]), "r"(a[2]), "r"(a[3]), "l"(db), "n"(TB));
}
template <int TB> __device__ __forceinline__ void rs40z(float* d, const uint32_t* a, uint64_t db) {
  asm volatile("{\n.reg .pred p;\nsetp.ne.b32 p, 0, 0;\n"
    "wgmma.mma_async.sync.aligned.m64n40k16.f32.bf16.bf16 "
    "{%0, %1, %2, %3, %4, %5, %6, %7, %8, %9, %10, %11, %12, %13, %14, %15, "
    "%16, %17, %18, %19}, {%20, %21, %22, %23}, %24, p, 1, 1, %25;\n}\n"
    : "=&f"(d[0]), "=&f"(d[1]), "=&f"(d[2]), "=&f"(d[3]), "=&f"(d[4]), "=&f"(d[5]), "=&f"(d[6]), "=&f"(d[7]),
      "=&f"(d[8]), "=&f"(d[9]), "=&f"(d[10]), "=&f"(d[11]), "=&f"(d[12]), "=&f"(d[13]), "=&f"(d[14]), "=&f"(d[15]),
      "=&f"(d[16]), "=&f"(d[17]), "=&f"(d[18]), "=&f"(d[19])
    : "r"(a[0]), "r"(a[1]), "r"(a[2]), "r"(a[3]), "l"(db), "n"(TB));
}
template <int TB> __device__ __forceinline__ void rs72a(float* d, const uint32_t* a, uint64_t db) {
  asm volatile("{\n.reg .pred p;\nsetp.eq.b32 p, 0, 0;\n"
    "wgmma.mma_async.sync.aligned.m64n72k16.f32.bf16.bf16 "
    "{%0, %1, %2, %3, %4, %5, %6, %7, %8, %9, %10, %11, %12, %13, %14, %15, "
    "%16, %17, %18, %19, %20, %21, %22, %23, %24, %25, %26, %27, %28, %29, %30, %31, "
    "%32, %33, %34, %35}, {%36, %37, %38, %39}, %40, p, 1, 1, %41;\n}\n"
    : "+f"(d[0]), "+f"(d[1]), "+f"(d[2]), "+f"(d[3]), "+f"(d[4]), "+f"(d[5]), "+f"(d[6]), "+f"(d[7]),
      "+f"(d[8]), "+f"(d[9]), "+f"(d[10]), "+f"(d[11]), "+f"(d[12]), "+f"(d[13]), "+f"(d[14]), "+f"(d[15]),
      "+f"(d[16]), "+f"(d[17]), "+f"(d[18]), "+f"(d[19]), "+f"(d[20]), "+f"(d[21]), "+f"(d[22]), "+f"(d[23]),
      "+f"(d[24]), "+f"(d[25]), "+f"(d[26]), "+f"(d[27]), "+f"(d[28]), "+f"(d[29]), "+f"(d[30]), "+f"(d[31]),
      "+f"(d[32]), "+f"(d[33]), "+f"(d[34]), "+f"(d[35])
    : "r"(a[0]), "r"(a[1]), "r"(a[2]), "r"(a[3]), "l"(db), "n"(TB));
}
template <int TB> __device__ __forceinline__ void rs72z(float* d, const uint32_t* a, uint64_t db) {
  asm volatile("{\n.reg .pred p;\nsetp.ne.b32 p, 0, 0;\n"
    "wgmma.mma_async.sync.aligned.m64n72k16.f32.bf16.bf16 "
    "{%0, %1, %2, %3, %4, %5, %6, %7, %8, %9, %10, %11, %12, %13, %14, %15, "
    "%16, %17, %18, %19, %20, %21, %22, %23, %24, %25, %26, %27, %28, %29, %30, %31, "
    "%32, %33, %34, %35}, {%36, %37, %38, %39}, %40, p, 1, 1, %41;\n}\n"
    : "=&f"(d[0]), "=&f"(d[1]), "=&f"(d[2]), "=&f"(d[3]), "=&f"(d[4]), "=&f"(d[5]), "=&f"(d[6]), "=&f"(d[7]),
      "=&f"(d[8]), "=&f"(d[9]), "=&f"(d[10]), "=&f"(d[11]), "=&f"(d[12]), "=&f"(d[13]), "=&f"(d[14]), "=&f"(d[15]),
      "=&f"(d[16]), "=&f"(d[17]), "=&f"(d[18]), "=&f"(d[19]), "=&f"(d[20]), "=&f"(d[21]), "=&f"(d[22]), "=&f"(d[23]),
      "=&f"(d[24]), "=&f"(d[25]), "=&f"(d[26]), "=&f"(d[27]), "=&f"(d[28]), "=&f"(d[29]), "=&f"(d[30]), "=&f"(d[31]),
      "=&f"(d[32]), "=&f"(d[33]), "=&f"(d[34]), "=&f"(d[35])
    : "r"(a[0]), "r"(a[1]), "r"(a[2]), "r"(a[3]), "l"(db), "n"(TB));
}
template <int TB> __device__ __forceinline__ void rs128a(float* d, const uint32_t* a, uint64_t db) {
  asm volatile("{\n.reg .pred p;\nsetp.eq.b32 p, 0, 0;\n"
    "wgmma.mma_async.sync.aligned.m64n128k16.f32.bf16.bf16 "
    "{%0, %1, %2, %3, %4, %5, %6, %7, %8, %9, %10, %11, %12, %13, %14, %15, "
    "%16, %17, %18, %19, %20, %21, %22, %23, %24, %25, %26, %27, %28, %29, %30, %31, "
    "%32, %33, %34, %35, %36, %37, %38, %39, %40, %41, %42, %43, %44, %45, %46, %47, "
    "%48, %49, %50, %51, %52, %53, %54, %55, %56, %57, %58, %59, %60, %61, %62, %63}, {%64, %65, %66, %67}, %68, p, 1, 1, %69;\n}\n"
    : "+f"(d[0]), "+f"(d[1]), "+f"(d[2]), "+f"(d[3]), "+f"(d[4]), "+f"(d[5]), "+f"(d[6]), "+f"(d[7]),
      "+f"(d[8]), "+f"(d[9]), "+f"(d[10]), "+f"(d[11]), "+f"(d[12]), "+f"(d[13]), "+f"(d[14]), "+f"(d[15]),
      "+f"(d[16]), "+f"(d[17]), "+f"(d[18]), "+f"(d[19]), "+f"(d[20]), "+f"(d[21]), "+f"(d[22]), "+f"(d[23]),
      "+f"(d[24]), "+f"(d[25]), "+f"(d[26]), "+f"(d[27]), "+f"(d[28]), "+f"(d[29]), "+f"(d[30]), "+f"(d[31]),
      "+f"(d[32]), "+f"(d[33]), "+f"(d[34]), "+f"(d[35]), "+f"(d[36]), "+f"(d[37]), "+f"(d[38]), "+f"(d[39]),
      "+f"(d[40]), "+f"(d[41]), "+f"(d[42]), "+f"(d[43]), "+f"(d[44]), "+f"(d[45]), "+f"(d[46]), "+f"(d[47]),
      "+f"(d[48]), "+f"(d[49]), "+f"(d[50]), "+f"(d[51]), "+f"(d[52]), "+f"(d[53]), "+f"(d[54]), "+f"(d[55]),
      "+f"(d[56]), "+f"(d[57]), "+f"(d[58]), "+f"(d[59]), "+f"(d[60]), "+f"(d[61]), "+f"(d[62]), "+f"(d[63])
    : "r"(a[0]), "r"(a[1]), "r"(a[2]), "r"(a[3]), "l"(db), "n"(TB));
}
template <int TB> __device__ __forceinline__ void rs128z(float* d, const uint32_t* a, uint64_t db) {
  asm volatile("{\n.reg .pred p;\nsetp.ne.b32 p, 0, 0;\n"
    "wgmma.mma_async.sync.aligned.m64n128k16.f32.bf16.bf16 "
    "{%0, %1, %2, %3, %4, %5, %6, %7, %8, %9, %10, %11, %12, %13, %14, %15, "
    "%16, %17, %18, %19, %20, %21, %22, %23, %24, %25, %26, %27, %28, %29, %30, %31, "
    "%32, %33, %34, %35, %36, %37, %38, %39, %40, %41, %42, %43, %44, %45, %46, %47, "
    "%48, %49, %50, %51, %52, %53, %54, %55, %56, %57, %58, %59, %60, %61, %62, %63}, {%64, %65, %66, %67}, %68, p, 1, 1, %69;\n}\n"
    : "=&f"(d[0]), "=&f"(d[1]), "=&f"(d[2]), "=&f"(d[3]), "=&f"(d[4]), "=&f"(d[5]), "=&f"(d[6]), "=&f"(d[7]),
      "=&f"(d[8]), "=&f"(d[9]), "=&f"(d[10]), "=&f"(d[11]), "=&f"(d[12]), "=&f"(d[13]), "=&f"(d[14]), "=&f"(d[15]),
      "=&f"(d[16]), "=&f"(d[17]), "=&f"(d[18]), "=&f"(d[19]), "=&f"(d[20]), "=&f"(d[21]), "=&f"(d[22]), "=&f"(d[23]),
      "=&f"(d[24]), "=&f"(d[25]), "=&f"(d[26]), "=&f"(d[27]), "=&f"(d[28]), "=&f"(d[29]), "=&f"(d[30]), "=&f"(d[31]),
      "=&f"(d[32]), "=&f"(d[33]), "=&f"(d[34]), "=&f"(d[35]), "=&f"(d[36]), "=&f"(d[37]), "=&f"(d[38]), "=&f"(d[39]),
      "=&f"(d[40]), "=&f"(d[41]), "=&f"(d[42]), "=&f"(d[43]), "=&f"(d[44]), "=&f"(d[45]), "=&f"(d[46]), "=&f"(d[47]),
      "=&f"(d[48]), "=&f"(d[49]), "=&f"(d[50]), "=&f"(d[51]), "=&f"(d[52]), "=&f"(d[53]), "=&f"(d[54]), "=&f"(d[55]),
      "=&f"(d[56]), "=&f"(d[57]), "=&f"(d[58]), "=&f"(d[59]), "=&f"(d[60]), "=&f"(d[61]), "=&f"(d[62]), "=&f"(d[63])
    : "r"(a[0]), "r"(a[1]), "r"(a[2]), "r"(a[3]), "l"(db), "n"(TB));
}

template <int V> struct IC { static constexpr int value = V; };
struct PfType { const char* base; uint32_t gl, gh, sp, sr, su, l4, l2; };
struct Params {
  const __nv_bfloat16 *x, *w;
  unsigned* cnt;
  uint32_t one;
  const __nv_bfloat16 *shift, *ssmD;
  __nv_bfloat16* out;
  uint4* o; float* kv;
  const char *k, *v;
  PfType pt[6];
  uint8_t pf[32];
  uint64_t cd[18];
};

struct Tmp { float t0, t1; };
__device__ __forceinline__ void mul2(Tmp& t, float a0, float b0, float a1, float b1) {
  asm volatile("@p_one mul.rn.f32 %0, %2, %3;\n@p_one mul.rn.f32 %1, %4, %5;" : "+f"(t.t0), "+f"(t.t1) : "f"(a0), "f"(b0), "f"(a1), "f"(b1)); }
__device__ __forceinline__ void add2(Tmp& t, float a0, float b0, float a1, float b1) {
  asm volatile("@p_one add.rn.f32 %0, %2, %3;\n@p_one add.rn.f32 %1, %4, %5;" : "+f"(t.t0), "+f"(t.t1) : "f"(a0), "f"(b0), "f"(a1), "f"(b1)); }
__device__ __forceinline__ void fma2(Tmp& t, float a0, float b0, float a1, float b1) { t.t0 = fmaf(a0, b0, t.t0); t.t1 = fmaf(a1, b1, t.t1); }
struct Tw { uint32_t c[2], s[2], ns[2]; };
__device__ __forceinline__ void rot(uint32_t& u, uint32_t& v, const Tw& w, int k) {
  asm("{\n.reg .b32 a, b;\nmul.rn.bf16x2 a, %0, %2;\nmul.rn.bf16x2 b, %0, %3;\nfma.rn.bf16x2 %0, %1, %4, a;\nfma.rn.bf16x2 %1, %1, %2, b;\n}"
    : "+r"(u), "+r"(v) : "r"(w.c[k]), "r"(w.s[k]), "r"(w.ns[k]));
}
__device__ __forceinline__ void pack_fwd(uint32_t (&f)[2][2][4], const float* a) {
  #pragma unroll
  for (int j = 0; j < 16; j++) f[j >> 3][(j >> 1) & 1][2 * (j & 1) + ((j >> 2) & 1)] = fresh(pack_bf16(a[2 * j], a[2 * j + 1]));
}
__device__ __forceinline__ void rot_fwd(uint32_t (&f)[2][2][4], const Tw& w) {
  #pragma unroll
  for (int j = 0; j < 8; j++) rot(f[j >> 2][j & 1][(j >> 1) & 1], f[j >> 2][j & 1][2 + ((j >> 1) & 1)], w, j & 1);
}
__device__ __forceinline__ void add_skip(float* h, float d) {
  asm volatile("add.rn.f32 %0, %0, %4;\nadd.rn.f32 %1, %1, %4;\nadd.rn.f32 %2, %2, %4;\nadd.rn.f32 %3, %3, %4;" : "+f"(h[0]), "+f"(h[1]), "+f"(h[4]), "+f"(h[5]) : "f"(d)); }
__device__ __forceinline__ void dft16h(float* d, const uint32_t (&f)[2][4], const D2& dF) { rs32z<0>(d, f[0], dF.a); rs32a<0>(d, f[1], dF.b); }
#define SP(h, p, im, k) (((p) >> 1 ? hi : lo) + 16 * (h) + 8 * (im) + 4 * (k) + 2 * ((p) & 1))
template <int PH, int G0 = 0, int G1 = 8> __device__ __forceinline__ void prod(Tmp& t, uint32_t (&f)[2][4], const float* lo, const float* hi) {
  #pragma unroll
  for (int g = G0; g < G1; g++) {
    const int p = 2 * PH + 1 - (g >> 2), k = (g >> 1) & 1, im = g & 1;
    #pragma unroll
    for (int q = 0; q <= p; q++) {
      const float *hr = SP(1, q, 0, k), *hi_ = SP(1, q, 1, k), *xa = SP(0, p - q, im, k), *xb = SP(0, p - q, 1 - im, k);
      if (q == 0) mul2(t, hr[0], xa[0], hr[1], xa[1]); else fma2(t, hr[0], xa[0], hr[1], xa[1]);
      if (im) fma2(t, hi_[0], xb[0], hi_[1], xb[1]); else fma2(t, -hi_[0], xb[0], -hi_[1], xb[1]);
    }
    f[k][2 * (1 - im) + (p & 1)] = pack_bf16(t.t0, t.t1);
  }
}

constexpr uint64_t dA = cdesc(A_OFF, 2048, 128, 0), dAi = cdesc(A_OFF, 128, 1024, 0), dF0 = cdesc(F_OFF, 128, 512, 0),
                   dT0 = cdesc(T_OFF, 1024, 128, 0), dH0 = cdesc(H_OFF, 1024, 256, 3), dX0 = cdesc(X_OFF, 1024, 128, 0);
#define CONV_DESC dF0, dF0 + 16, dAi, dT0, dAi + 16, dT0 + 128, dAi + 32, dT0 + 256, dAi + 48, dT0 + 384, dA, dH0, dA + 256, dH0 + 32, dA, dX0, dA + 256, dX0 + 128
__device__ __forceinline__ void make_tw(Tw& tw, int ht) {
  #pragma unroll
  for (int i = 0; i < 2; i++) {
    float c0, s0, c1, s1;
    unit_root<11>((4 * (ht >> 2) + 1) * (i * 8 + 2 * (ht & 3)), c0, s0);
    unit_root<11>((4 * (ht >> 2) + 1) * (i * 8 + 2 * (ht & 3) + 1), c1, s1);
    tw.c[i] = pack_bf16(c0, c1); tw.s[i] = pack_bf16(s0, s1); tw.ns[i] = fresh(tw.s[i] ^ 0x80008000u);
  }
}
template <bool COMMIT = true> __device__ __forceinline__ void dft32_h(float* r, const D2* d) {
  ss64z<1, 1>(r, d[0].a, d[0].b); ss64a<1, 1>(r, d[1].a, d[1].b);
  if (COMMIT) wg_commit();
}
template <bool COMMIT = true> __device__ __forceinline__ void dft32_x(float* r, D2* d) {
  ss64z<1, 0>(r, d[0].a, d[0].b); ss64a<1, 0>(r, d[1].a, d[1].b);
  if (COMMIT) wg_commit();
  d[0].b = dofs(d[0].b, XS); d[1].b = dofs(d[1].b, XS);
}
__device__ __forceinline__ void pack_inv(uint32_t (&u)[2][2][4], const float* r) {
  #pragma unroll
  for (int j = 0; j < 16; j++) u[j >> 3][(j >> 2) & 1][2 * (j & 1) + ((j >> 1) & 1)] = fresh(pack_bf16(r[2 * j], r[2 * j + 1]));
}
__device__ __forceinline__ void rot_inv(uint32_t (&u)[2][2][4], const Tw& tw, uint32_t ta) {
  #pragma unroll
  for (int m = 0; m < 2; m++) {
    #pragma unroll
    for (int j = 0; j < 4; j++) rot(u[m][0][j], u[m][1][j], tw, j & 1);
    stsm4(ta + m * 512, u[m][1][0], u[m][1][1], u[m][1][2], u[m][1][3]);
    stsm4(ta + 1024 + m * 512, u[m][0][0], u[m][0][1], u[m][0][2], u[m][0][3]);
  }
}
__device__ __forceinline__ void idft32(float* r, const D2* d) {
  wg_fence();
  ss64z<0, 1>(r, d[0].a, d[0].b);
  #pragma unroll
  for (int j = 1; j < 4; j++) ss64a<0, 1>(r, d[j].a, d[j].b);
  wg_commit();
}
__device__ __forceinline__ void finish(Tmp& t, const float* r, int ch, int ht, int rank, uint32_t y0, uint32_t y1) {
  const uint32_t ya = X_OFF + ch * XS + (ch & 1) * 16, yb = BAR_OFF + (B_YR + ch) * 8;
  uint32_t y[8];
  #pragma unroll
  for (int j = 0; j < 8; j++) {
    if (j >= 2) add2(t, r[4 * j], r[4 * j - 6], r[4 * j + 1], r[4 * j - 5]);
    y[j] = j < 2 ? pack_bf16(r[4 * j], r[4 * j + 1]) : pack_bf16(t.t0, t.t1);
  }
  st_async128(y0 + ya + (ht ^ (rank * 4)) * 16 + rank * (YX - XS), y0 + yb, y[0], y[1], y[2], y[3]);
  st_async128(y1 + ya + (ht ^ (rank * 4) ^ 4) * 16 + (rank ^ 1) * (YX - XS), y1 + yb, y[4], y[5], y[6], y[7]);
}

struct Team { uint32_t bars, rel, wofs, lead; };
struct Nop { __device__ __forceinline__ void operator()() const {} };
template <bool M, class F> __device__ __forceinline__ void mid_wait(F f) { if (M) wg_commit(); f(); if (M) { wg_wait<0>(); wg_fence(); } }
template <int J, bool M = false, class F = Nop> __device__ __forceinline__ void kv_issue(float* aK, float* aV, uint32_t xo, int sd, F f = F()) {
  constexpr uint64_t dw = cdesc(W_OFF + J * 8192, 8192, 1024, 1);
  const uint64_t dx = dofs(cdesc((J & 1) * 64, 16, 1024, 1), xo);
  wg_fence();
  ss128p<1, 0>(aV, dw + (4096 >> 4), dx, sd);
  ss128p<1, 0>(aK, dw, dx, sd);
  mid_wait<M>(f);
  ss128a<1, 0>(aV, dw + (6144 >> 4), dofs(dx, 32));
  ss128a<1, 0>(aK, dw + (2048 >> 4), dofs(dx, 32));
  wg_commit();
}
template <int O, int J, int H> __device__ __forceinline__ void g2_half(float* acc, const Team& c) {
  constexpr uint64_t db = cdesc(J * SLOT + 16384 + H * 4096, 8192, 1024, 1);
  const uint64_t da = dofs(O ? cdesc(J * SLOT + H * 4096, 16, 512, 2) : cdesc(J * SLOT + H * 64, 16, 1024, 1), c.wofs);
  wg_fence();
  ss128a<0, 1>(acc, da, db);
  ss128a<0, 1>(acc, dofs(da, 32), db + (2048 >> 4));
  wg_commit();
}
template <int O, int J, bool M = false, bool FIRST = false, class F = Nop> __device__ __forceinline__ void g2_issue(float* acc, const Team& c, F f = F()) {
  constexpr uint64_t db = cdesc(J * SLOT + 16384, 8192, 1024, 1);
  const uint64_t da = dofs(O ? cdesc(J * SLOT, 16, 512, 2) : cdesc(J * SLOT, 16, 1024, 1), c.wofs);
  wg_fence();
  if (FIRST) ss128z<0, 1>(acc, da, db); else ss128a<0, 1>(acc, da, db);
  ss128a<0, 1>(acc, dofs(da, 32), db + (2048 >> 4));
  mid_wait<M>(f);
  ss128a<0, 1>(acc, dofs(da, O ? 4096 : 64), db + (4096 >> 4));
  ss128a<0, 1>(acc, dofs(da, O ? 4128 : 96), db + (6144 >> 4));
  wg_commit();
}
template <bool DEEP, bool AB = false, class F>
__device__ __forceinline__ void ring_step(const Team& c, int fb, uint32_t ph, int eb, uint32_t rel, F issue, uint32_t ab = 0, uint32_t aph = 0) {
  uint32_t ok = mbar_try(c.bars + fb * 8, ph);
  if (AB) ok &= mbar_try(ab, aph);
  if (!ok) {
    wg_wait<0>();
    arrive_at(c.rel + eb * 8, rel);
    rel = 0;
    mbar_wait(c.bars + fb * 8, ph);
    if (AB) mbar_wait(ab, aph);
  }
  if constexpr (!DEEP) {
    wg_wait<0>();
    issue([&]() { arrive_at(c.rel + eb * 8, rel); });
  } else {
    issue();
    wg_wait<1>(); arrive_at(c.rel + eb * 8, rel);
  }
}
template <int N, int I = 0, class R> __device__ __forceinline__ void tail_release(R rel) {
  if constexpr (I <= N) { wg_wait<N - I>(); rel(I - 1); tail_release<N, I + 1>(rel); }
}
template <int N, class F, class R> __device__ __forceinline__ void skew_tail(const Team& c, int ph, F issue, R rel) {
  if (c.wofs) { wg_wait<0>(); rel(-1); mbar_wait(c.bars + B_SK * 8, ph); }
  issue();
  arrive_at(c.bars + B_SK * 8, fresh_tid() == 0);
  tail_release<N>([&](int i) { if (i >= 0 || !c.wofs) rel(i); });
}
__device__ __forceinline__ void phi_a(float* a, uint32_t* f) {
  #pragma unroll
  for (int i = 0; i < 8; i++) {
    asm("cvt.rn.relu.bf16x2.f32 %0, %1, %2;" : "=r"(f[i]) : "f"(a[2 * i + 1]), "f"(a[2 * i]));
    asm("ex2.approx.ftz.f32 %0, %1;" : "=f"(a[2 * i]) : "f"(a[2 * i] * 1.4426950408889634f));
    asm("ex2.approx.ftz.f32 %0, %1;" : "=f"(a[2 * i + 1]) : "f"(a[2 * i + 1] * 1.4426950408889634f));
  }
  pinv<16>(a);
}
__device__ __forceinline__ void phi_s(float* a, uint32_t* f) {
  #pragma unroll
  for (int i = 0; i < 8; i++) {
    asm("cvt.rn.relu.bf16x2.f32 %0, %1, %2;" : "=r"(f[i]) : "f"(a[2 * i + 1]), "f"(a[2 * i]));
    a[2 * i] *= 1.4426950408889634f; a[2 * i + 1] *= 1.4426950408889634f;
  }
  pinv<16>(a);
}
__device__ __forceinline__ void phi_e(float* a) {
  #pragma unroll
  for (int i = 0; i < 16; i++) asm("ex2.approx.ftz.f32 %0, %0;" : "+f"(a[i]));
  pinv<16>(a);
}
__device__ __forceinline__ void phi_b(const float* e, uint32_t* f) {
  #pragma unroll
  for (int i = 0; i < 8; i++) f[i] = badd2(f[i], pack_bf16(__saturatef(e[2 * i] + 1e-6f), __saturatef(e[2 * i + 1] + 1e-6f)));
}
__device__ __forceinline__ int g2_k(int st, int n2) {
  const int j = (st >> 1) - 1;
  return 2 * (j == 0 ? n2 == 0 : (j == max(n2, 1) ? 7 : j)) + (st & 1);
}

__global__ void __cluster_dims__(2, 1, 1) __launch_bounds__(NTHREADS, 1)
fused_kernel(const __grid_constant__ Params P, const __grid_constant__ CUtensorMap mX, const __grid_constant__ CUtensorMap mW,
             const __grid_constant__ CUtensorMap mWq, const __grid_constant__ CUtensorMap mWo,
             const __grid_constant__ CUtensorMap mK, const __grid_constant__ CUtensorMap mV, const __grid_constant__ CUtensorMap mH,
             const __grid_constant__ CUtensorMap mQ, const __grid_constant__ CUtensorMap mOut, const __grid_constant__ CUtensorMap mOutA,
             const __grid_constant__ CUtensorMap mWp) {
  extern __shared__ __align__(1024) uint8_t smem[];
  asm volatile(".reg .pred p_one;");
  const int tid = threadIdx.x, lane = tid & 31;
  const int warp = __shfl_sync(0xffffffffu, tid >> 5, 0);
  if (warp == 0) {
    asm volatile(ELECT "prefetch.tensormap [%0];\n}" :: "l"(&mW) : "memory");
    asm volatile(ELECT "prefetch.tensormap [%0];\n}" :: "l"(&mX) : "memory");
  }
  {
    const uint32_t t = threadIdx.x, bb = blockIdx.x;
    asm volatile("{\n.reg .pred p, q;\nsetp.eq.u32 p, %2, 2;\nsetp.eq.u32 q, %3, 8;\n@p prefetch.global.L2 [%0];\n@q prefetch.global.L2 [%1];\n}"
      :: "l"(reinterpret_cast<const char*>(P.x) + ((bb * 16 + t - 32) * 2048)),
         "l"(reinterpret_cast<const char*>(P.w) + ((bb >> 2) * 2048 + bb * 1024 + t * 128 - 6144)), "r"(t >> 4), "r"(t >> 3));
  }
  const uint32_t sb = uni(smem_u32(smem));
  const uint32_t bars = sb + BAR_OFF;
  const uint32_t ids = uni(wanted_job() * 2 + (blockIdx.x & 1));
#define IDS(w) const int rank = (w) & 1, hp = (w) & 15, g = hp >> 1, mb = (w) >> 4, m2 = hp, n2 = mb, cp = g * 8 + mb; \
               (void)rank; (void)m2; (void)n2; (void)cp
  auto job = [&]() { return (uni(lds32(sb + D_OFF + 52)) & 126) | (ids & 1); };
  auto wrong_job = [&]() {
    mbar_wait(bars + B_EX * 8, 0);
    return uni(lds32(sb + D_OFF + 52) ^ lds32(sb + D_OFF + 56)) != 1;
  };

  if (warp == 0) {
    IDS(ids);
    mbar_init(bars + (B_XF + 2) * 8, 1); mbar_init(bars + B_F0 * 8, 1); mbar_init(bars + B_FULL * 8, 1);
    mbar_expect_tx(bars + B_FULL * 8, 8192);
    tma3d(sb + W_OFF, &mW, hp * 64, 0, 1, bars + B_FULL * 8);
    mbar_expect_tx(bars + (B_XF + 2) * 8, 16384);
    tma2d(sb + 2 * SLOT, &mX, 0, mb * 256, bars + (B_XF + 2) * 8);
    mbar_expect_tx(bars + B_F0 * 8, 16384);
    tma2d(sb + 2 * SLOT + 16384, &mX, 0, mb * 256 + 128, bars + B_F0 * 8);
    #pragma unroll
    for (int i = 1; i < 4; i++) mbar_init(bars + (B_FULL + i) * 8, 1);
    #pragma unroll
    for (int i = 1; i < 4; i++) {
      mbar_expect_tx(bars + (B_FULL + i) * 8, 8192);
      tma3d(sb + W_OFF + i * 8192, &mW, hp * 64, i * 32, 1, bars + (B_FULL + i) * 8);
    }
    mbar_init(bars + B_XF * 8, 1); mbar_init(bars + (B_XF + 1) * 8, 1);
  } else if (warp >= 6) {
    const uint32_t cnt = warp < 12 || warp == 15 ? 1 : 4, b0 = bars + (warp - 4) * 32;
    #pragma unroll
    for (int i = 0; i < 4; i++) mbar_init(b0 + i * 8, i == 3 && warp == 15 ? 4 : cnt);
    if (warp == 8 || warp == 9) {
      #pragma unroll
      for (int i = 0; i < 4; i++) mbar_expect_tx(b0 + i * 8, 4096);
    } else if ((warp & 13) == 13) {
      mbar_expect_tx(bars + (warp == 13 ? B_KVB : B_EX) * 8, warp == 13 ? 5120 : 8);
    }
  }
  asm volatile("fence.mbarrier_init.release.cluster;" ::: "memory");
  __syncwarp();
  asm volatile("barrier.cluster.arrive.relaxed.aligned;" ::: "memory");

  if ((warp >> 2) == 2) {
    asm volatile("setmaxnreg.inc.sync.aligned.u32 %0;" :: "n"(160));
    const int ht = tid - 256, w = warp - 8;
    const int kap = w & 1;
    {
      uint32_t c4[4], s4[4];
      #pragma unroll
      for (int i = 0; i < 4; i++) {
        float c0, s0, c1, s1;
        unit_root<7>((32 * (ht & 3) + 8 * i + 1) * (ht >> 2), c0, s0);
        unit_root<7>((32 * (ht & 3) + 8 * i + 5) * (ht >> 2), c1, s1);
        c4[i] = pack_bf16(c0 * 0.125f, c1 * 0.125f); s4[i] = pack_bf16(s0 * 0.125f, s1 * 0.125f);
      }
      const uint32_t aa = sb + A_OFF + w * 2048 + (ht & 3) * 256 + ((ht >> 2) & 7) * 16;
      sts128(aa, c4[0], c4[1], c4[2], c4[3]);
      sts128(aa + 128, s4[0], s4[1], s4[2], s4[3]);
      sts128(aa + 1024, s4[0] ^ 0x80008000u, s4[1] ^ 0x80008000u, s4[2] ^ 0x80008000u, s4[3] ^ 0x80008000u);
      sts128(aa + 1024 + 128, c4[0], c4[1], c4[2], c4[3]);
      float c0, s0, c1, s1;
      unit_root<4>((ht >> 3) * (2 * (ht & 7)), c0, s0);
      unit_root<4>((ht >> 3) * (2 * (ht & 7) + 1), c1, s1);
      const uint32_t fa = sb + F_OFF + (ht >> 6) * 512 + ((ht >> 2) & 1) * 256 + ((ht >> 3) & 7) * 16 + (ht & 3) * 4;
      const uint32_t cc = pack_bf16(c0, c1), ss = pack_bf16(s0, s1);
      sts32(fa, cc); sts32(fa + 128, ss ^ 0x80008000u); sts32(fa + 1024, ss); sts32(fa + 1024 + 128, cc);
    }
    cluster_wait();
    mbar_wait(bars + B_EX * 8, 0);
    const uint32_t id2 = job(); IDS(id2);
    if (id2 != ids) bar_sync(8, 160);
    const uint4 sw = *reinterpret_cast<const uint4*>(P.shift + (cp * 16 + kap * 8 + 2 * (lane & 3)) * 4);
    const float dv = __bfloat162float(P.ssmD[cp * 16 + rank * 8 + (ht & 7)]) * 0.125f;
    Tw tw;
    make_tw(tw, ht);
    D2 cd[9];
    {
      const uint64_t v = P.cd[min(lane, 17)];
      #pragma unroll
      for (int i = 0; i < 9; i++) { cd[i].a = __shfl_sync(0xffffffffu, v, 2 * i); cd[i].b = __shfl_sync(0xffffffffu, v, 2 * i + 1); }
    }
    const D2 &dF = cd[0], *dT = cd + 1, *dH = cd + 5;
    D2* dX = cd + 7;
#define CFENCE(n) sched_fence<n>((uint32_t)dF.a)
    if (ht < 8) sts32(sb + D_OFF + ht * 4, __float_as_uint(dv));
    const uint32_t w0 = __byte_perm(sw.x, sw.z, 0x5410), w1 = __byte_perm(sw.x, sw.z, 0x7632);
    const uint32_t w2 = __byte_perm(sw.y, sw.w, 0x5410), w3 = __byte_perm(sw.y, sw.w, 0x7632);
    const uint32_t psb = uni(mapa(sb, rank ^ 1));
    if (ht == 0) OSTAMP(20);
    {
      const int m = lane >> 3, n1 = (w >> 1) * 8 + (lane & 7);
      const int rk = 17 * m + n1 + 1, rh = 17 * (12 + m) + n1, rv = 16 * m + n1;
      const uint32_t ka = rk * 32 + ((kap ^ (rk >> 2)) & 1) * 16, ha = rh * 32 + ((kap ^ (rh >> 2)) & 1) * 16;
      const uint32_t va = rv * 32 + ((kap ^ (rv >> 2)) & 1) * 16;
      const uint32_t po = sb + T_OFF + (w >> 1) * 2176;
      #pragma unroll 1
      for (int rd = 0; rd < 4; rd++) {
        const uint32_t kb = sb + M_OFF + (rd & 1) * KB, vb = sb + M_OFF + 2 * KB + (rd & 1) * 8192;
        const uint32_t xo = X_OFF + ((rd & 1) * 2 + (w >> 1)) * 1024 + (2 * rank + (rd >> 1)) * 256;
        const uint32_t xa = (kap == rank ? sb + xo + (lane & 7) * XS : po + (lane & 7) * 272) + m * 16;
        mbar_wait(bars + (B_STG + (rd & 1) * 2) * 8, rd >> 1);
        uint32_t kk[20], vv[16];
        const uint32_t zero = P.one - 1;
        ldsm4(kk, kb + ha);
        ldsm4(kk + 4, kb + ka);
        #pragma unroll
        for (int i = 0; i < 16; i++) {
          if ((i & 3) == 0 && i < 12) ldsm4(kk + 8 + i, kb + (ka ^ ((~i & 4) * 4)) + (i + 4) * 544 + (kk[i + 4] & zero));
          uint32_t t = bmul2(kk[i + 1], w3);
          t = badd2(t, bmul2(kk[i + 2], w2));
          t = badd2(t, bmul2(kk[i + 3], w1));
          kk[i] = badd2(t, bmul2(kk[i + 4], w0));
          asm volatile("" : "+r"(kk[i]));
        }
        mbar_wait(bars + (B_STG + (rd & 1) * 2 + 1) * 8, rd >> 1);
        ldsm4(vv, vb + va);
        #pragma unroll
        for (int i = 0; i < 16; i += 4) {
          if (i < 12) ldsm4(vv + 4 + i, vb + va + (i + 4) * 512 + (i == 4 ? vv[0] & zero : 0));
          stsm4t(xa + (i >> 2) * 64, bmul2(kk[i], vv[i]), bmul2(kk[i + 1], vv[i + 1]), bmul2(kk[i + 2], vv[i + 2]), bmul2(kk[i + 3], vv[i + 3]));
        }
        if (rd < 2) {
          fence_async_smem();
          __syncwarp();
          mbar_arrive(bars + (B_SFREE + (rd & 1)) * 8);
        }
        __syncwarp();
        if (kap != rank) {
          #pragma unroll
          for (int i = 0; i < 4; i++) lds128(vv + 4 * i, po + (2 * i + (lane >> 4)) * 272 + (lane & 15) * 16);
          #pragma unroll
          for (int i = 0; i < 4; i++)
            st_async128(psb + xo + (2 * i + (lane >> 4)) * XS + (lane & 15) * 16, psb + BAR_OFF + B_X * 8, vv[4 * i], vv[4 * i + 1], vv[4 * i + 2], vv[4 * i + 3]);
          __syncwarp();
        }
      }
    }
    bar_sync(3, 128);
    if (w == 0) mbar_expect_tx(bars + B_X * 8, 16384);
    {
      constexpr int NC = 8;
      Tmp t; t.t0 = 0.f; t.t1 = 0.f;
      asm volatile("setp.ne.b32 p_one, %0, 0;" :: "r"(lds32(sb + F_OFF)));
      float ra[32], lo[32], hi[32];
      uint32_t fa[2][2][4], fb[2][2][4];
      const uint32_t ta = sb + T_OFF + w * 2048 + lane * 16;
      const uint32_t y0 = rank ? psb : sb, y1 = rank ? sb : psb;
      auto fin = [&](int ch) {
        if (ch > 0) mbar_wait(bars + (B_YR + ch - 1) * 8, 0);
        finish(t, ra, ch, ht, rank, y0, y1);
      };
      auto load_h = [&](int i) {
        mbar_expect_tx(bars + B_H * 8, 4096);
        tma2d(sb + H_OFF, &mH, 0, (cp * 16 + rank * 8 + i) * 128, bars + B_H * 8);
      };
      auto skip = [&](int i) {
        const float dn = __uint_as_float(lds32(sb + D_OFF + i * 4));
        return dn;
      };
      mbar_wait(bars + B_H * 8, 0);
      wg_fence();
      dft32_h(lo, dH);
      mbar_wait(bars + B_X * 8, 0);
      fence_async_smem();
      if (ht == 0) OSTAMP(21);
      wg_fence();
      dft32_x(hi, dX);
      float dn = skip(0);
      wg_wait<1>(); pinv<32>(lo);
      if (w == 0) load_h(1);
      pack_fwd(fa, lo); CFENCE(0); rot_fwd(fa, tw); CFENCE(1);
      wg_wait<0>(); pinv<32>(hi);
      pack_fwd(fb, hi); CFENCE(2); rot_fwd(fb, tw); CFENCE(3);
      wg_fence();
      dft16h(hi, fb[1], dF); dft16h(hi + 16, fa[1], dF); dft16h(lo, fb[0], dF); dft16h(lo + 16, fa[0], dF);
      wg_commit();
      wg_wait<0>(); pinv<32>(lo); pinv<32>(hi);
#define CSTAMP(n) do {} while (0)
      #pragma unroll 1
      for (int i = 0;; i++) {
        CSTAMP(0);
        add_skip(lo + 16, dn);
        prod<1, 0, FG>(t, fa[1], lo, hi);
        CFENCE(4);
        CSTAMP(1);
        fence_async_smem();
        bar_sync(3, 128);
        CSTAMP(2);
        float rg[32];
        wg_fence();
        ss64x4(rg, dT, i);
        CFENCE(5);
        CSTAMP(3);
        const uint32_t yr = bars + (i < 2 ? B_X : B_YR + i - 2) * 8;
        const uint32_t oky = mbar_try(yr, 0);
        dn = skip(i + 1);
        prod<1, FG, 8>(t, fa[1], lo, hi);
        pinv<32>(lo);
        if (!oky) mbar_wait(yr, 0);
        CSTAMP(4);
        wg_wait<0>(); pinv<32>(rg);
        if (i > 0) finish(t, rg, i - 1, ht, rank, y0, y1);
        if (i == NC - 1) break;
        CSTAMP(5);
        wg_fence();
        dft32_x<false>(hi, dX);
        dft16h(ra + 16, fa[1], dF);
        wg_commit();
        CFENCE(7);
        CSTAMP(6);
        const uint32_t okh = mbar_try(bars + B_H * 8, (i + 1) & 1);
        prod<0>(t, fa[0], lo, lo);
        if (!okh) mbar_wait(bars + B_H * 8, (i + 1) & 1);
        CSTAMP(7);
        wg_fence();
        dft32_h<false>(lo, dH);
        dft16h(ra, fa[0], dF);
        wg_commit();
        wg_wait<1>(); pinv<32>(hi);
        if (ht == 64) OSTAMP(22 + i);
        CSTAMP(8);
        pack_fwd(fb, hi); CFENCE(9); rot_fwd(fb, tw); CFENCE(10);
        CSTAMP(9);
        wg_wait<0>(); pinv<32>(lo); pinv<32>(ra);
        CSTAMP(10);
        if (w == 0 && i < NC - 2) load_h(i + 2);
        pack_fwd(fa, lo);
        CFENCE(11);
        wg_fence();
        dft16h(hi, fb[1], dF); dft16h(lo, fb[0], dF);
        wg_commit();
        CFENCE(12);
        rot_fwd(fa, tw);
        uint32_t u[2][2][4];
        CFENCE(13);
        pack_inv(u, ra);
        CFENCE(14);
        CSTAMP(11);
        wg_fence();
        dft16h(hi + 16, fa[1], dF); dft16h(lo + 16, fa[0], dF);
        wg_commit();
        CFENCE(15);
        CSTAMP(12);
        rot_inv(u, tw, ta);
        CSTAMP(13);
        CFENCE(16);
        wg_wait<0>(); pinv<32>(lo); pinv<32>(hi);
        CSTAMP(14);
      }
      wg_fence();
      dft16h(hi + 16, fa[1], dF);
      wg_commit();
      CFENCE(17);
      prod<0>(t, fa[0], lo, lo);
      CFENCE(18);
      wg_fence();
      dft16h(hi, fa[0], dF);
      wg_commit();
      if (ht == 64) OSTAMP(29);
      wg_wait<0>(); pinv<32>(hi);
      pack_inv(fb, hi); CFENCE(19); rot_inv(fb, tw, ta);
      fence_async_smem();
      bar_sync(3, 128);
      idft32(ra, dT);
      const int l3 = fresh_tid() & 31;
      uint32_t qa = sb + M_OFF + ((l3 >> 4) * 512 + w * 128 + (l3 & 8) + ((l3 >> 2) & 1) + (l3 & 2)) * 32 + (l3 & 1) * 16;
      uint32_t yb = sb + X_OFF + (l3 & 1) * (XS + 16) + w * 512
                    + (((l3 >> 1) & 1) == rank ? (l3 >> 2) * 16 : YX - XS + ((l3 >> 2) ^ 4) * 16);
      mbar_wait(bars + B_Q * 8, 0);
      wg_wait<0>(); pinv<32>(ra);
      fin(NC - 1);
      if (ht == 64) OSTAMP(30);
      uint32_t t0 = 0, dt = 0;
      #pragma unroll 1
      for (int sg = 0; sg < 4; sg++, qa += 1024, yb += 128) {
        uint32_t qv[4][4], yv[4][4];
        #pragma unroll
        for (int i = 0; i < 4; i++) lds128(qv[i], qa + (i >> 1) * 512 + (i & 1) * 128);
        #pragma unroll
        for (int m = 0; m < 4; m++) {
          if (m == 3 && sg == 0) mbar_wait(bars + (B_YR + NC - 1) * 8, 0);
          ldsm4t(yv[m], yb + 2 * m * XS);
        }
        #pragma unroll
        for (int i = 0; i < 4; i++)
          sts128(qa + (i >> 1) * 512 + (i & 1) * 128, bmul2(qv[i][0], yv[0][i]), bmul2(qv[i][1], yv[1][i]), bmul2(qv[i][2], yv[2][i]), bmul2(qv[i][3], yv[3][i]));
        if (sg == 3) mbar_arrive(bars + B_CD * 8);
        fence_async_smem();
        __syncwarp();
        if (sg == 0) {
          mbar_wait(bars + B_GO * 8, 0);
          t0 = uni((uint32_t)clock());
          dt = uni(min(max((int)(lds32(sb + D_OFF + 44) + OA_END - t0) >> 2, 4 * OA_MIN), 4 * OA_MAX));
          t0 += w * (dt >> 2);
        }
        pace(t0, dt);
        #pragma unroll
        for (int hf = 0; hf < 2; hf++) {
          const int r = w * 128 + sg * 32 + hf * 512;
          tma2d_store(&mOutA, cp * 16, rank * 1024 + r, sb + M_OFF + r * 32);
        }
      }
      bulk_commit(); bulk_wait_read();
      if (ht == 0) OSTAMP(31);
    }
  } else if (warp >= 12) {
    asm volatile("setmaxnreg.dec.sync.aligned.u32 %0;" :: "n"(32));
    const uint32_t t_pf = (uint32_t)clock();
    if (warp >= 14) {
      const uint32_t id2 = fresh(ids); IDS(id2);
      if (warp == 14) {
        asm volatile("prefetch.global.L2 [%0];" :: "l"(((lane & 1) ? P.v : P.k) + (rank * 2097152 + cp * 32 + (lane >> 1) * 131072)));
      } else {
        uint32_t t0 = t_pf + id2 * 2;
        #pragma unroll 1
        for (int i = 0; i < PF_N; i++) {
          const int u = P.pf[i];
          const PfType& f = P.pt[u >> 4];
          pace(t0, i == 0 ? PF_DT0 : (i < PF_N1 ? PF_DT1 : PF_DT2));
          asm volatile("prefetch.global.L2 [%0];" :: "l"(f.base + ((g & 3) * f.gl + (g >> 2) * f.gh + mb * f.sp + rank * f.sr + (u & 15) * f.su
                                                                   + (lane >> 2) * f.l4 + ((lane >> 1) & 1) * f.l2 + (lane & 1) * 128)));
        }
      }
    }
    cluster_wait();
    if (warp == 13) {
      unsigned* const asked = P.cnt + 80 * 32;
      uint32_t j = ids, taken = 0;
      if (lane + (ids & 1) == 0) taken = atomicExch(P.cnt + 64 * 32 + ids * 4, 1u);
      if (uni(taken)) {
        fence_gpu();
        unsigned n = 0;
        if (lane == 0) n = atomicAdd(asked, 1u);
        spin_until(asked, (uni(n) | 63) + 1);
        #pragma unroll 1
        for (j = 0; j < 126; j += 2) {
          if (lane == 0) n = atomicExch(P.cnt + 64 * 32 + j * 4, 1u);
          if (!uni(n)) break;
        }
        if (lane == 0) P.cnt[64 * 32 + j * 4] = 1;
        j |= 128;
      }
      asm volatile("{\n.reg .pred p;\nsetp.lt.u32 p, %3, 2;\n@p st.async.weak.shared::cluster.mbarrier::complete_tx::bytes.b32 [%0], %2, [%1];\n}"
        :: "r"(mapa(sb + D_OFF + 52 + (j & 1) * 4, lane & 1)), "r"(mapa(bars + B_EX * 8, lane & 1)), "r"(j), "r"(lane) : "memory");
      if (!(j & 129)) { fence_gpu(); red_add(asked); }
    }
    if (warp == 12) {
      uint32_t xs = 0, idk = fresh(ids);
      auto load_x = [&](int k) {
        IDS(idk);
        tma2d_mc(sb + xs * SLOT + rank * 16384, &mX, k, mb * 256 + rank * 128, bars + (B_XF + xs) * 8);
        mbar_expect_tx(bars + (B_XF + xs) * 8, SLOT);
        xs = xs == 2 ? 0 : xs + 1;
      };
      load_x(64); load_x(128);
      mbar_expect_tx(bars + B_Q * 8, 32768);
      int look = 5;
      #pragma unroll 1
      for (int it = 1; it < 8; it++) {
        #pragma unroll
        for (int j = 0; j < 4; j++) {
          bool again = false;
          if (j == 3 && it == look) again = wrong_job();
          mbar_wait(bars + (B_EMPTY + j) * 8, (it - 1) & 1);
          TSTAMP(1, 4 * it + j);
          tma3d(sb + W_OFF + j * 8192, &mW, (idk & 15) * 64, it * 128 + j * 32, 1, bars + (B_FULL + j) * 8);
          if (again) { it = look = -1; idk = job(); }
          if (j == 1 || (j == 3 && it < 7)) load_x(it * 128 + j * 32 + 32);
          mbar_expect_tx(bars + (B_FULL + j) * 8, 8192);
        }
      }
    }
    if (warp == 14) {
      uint32_t t0 = t_pf + STG_T0, idk = fresh(ids);
      #pragma unroll 1
      for (int pc = 0; pc < 16; pc++) {
        if (pc == 2) {
          mbar_wait(bars + B_EX * 8, 0);
          if (job() != idk) { mbar_wait(bars + B_STG * 8, 0); mbar_arrive(bars + B_STG * 8); bar_sync(8, 160); idk = job(); pc = 0; }
        }
        IDS(idk);
        const int rd = pc >> 2, u = pc & 3;
        const uint32_t gb = bars + (B_STG + (rd & 1) * 2 + (u >> 1)) * 8;
        if (pc == 8 || pc == 12) mbar_wait(bars + (B_SFREE + (rd & 1)) * 8, 0);
        if (!(u & 1)) mbar_expect_tx(gb, u ? 8192 : KB);
        pace(t0, STG_DT);
        TSTAMP(3, 16 + pc);
        tma3d(sb + M_OFF + (u < 2 ? (rd & 1) * KB + u * (KB / 2) : 2 * KB + (rd & 1) * 8192 + (u & 1) * 4096), u < 2 ? &mK : &mV,
              cp * 16, rank * 64 + rd * 16 - (u < 2), (u & 1) * 8, gb);
      }
      IDS(idk);
      mbar_expect_tx(bars + B_H * 8, 4096);
      tma2d(sb + H_OFF, &mH, 0, (cp * 16 + rank * 8) * 128, bars + B_H * 8);
    }
    mbar_wait(bars + B_EX * 8, 0);
    const uint32_t id2 = job(); IDS(id2);
    if (warp == 12) {
      #pragma unroll 1
      for (int it = 0; it < 4; it++) {
        #pragma unroll
        for (int j = 0; j < 4; j++) {
          const uint32_t fb = bars + (B_FULL2 + j) * 8;
          if (j || it) mbar_wait(bars + (it ? B_EMPTY2 + j : B_EMPTY + (j | 1)) * 8, (it - 1) & 1);
          TSTAMP(5, 4 * it + j);
          tma2d_mc(sb + j * SLOT + 16384 + rank * 8192, &mWq, n2 * 128 + rank * 64, it * 256 + j * 64, fb);
          tma2d(sb + j * SLOT, &mX, it * 256 + j * 64, m2 * 128, fb);
          mbar_expect_tx(fb, SLOT);
        }
      }
      mbar_wait(bars + B_MF * 8, 0);
      #pragma unroll 1
      for (int pc = 0; pc < 8; pc++) { tma2d(sb + M_OFF + pc * 4096, &mQ, cp * 16, rank * 1024 + pc * 128, bars + B_Q * 8); if (QP) { const uint32_t t0 = (uint32_t)clock(); while ((uint32_t)clock() - t0 < QP) {} } }
      auto load_wo = [&](int st, uint32_t ph) {
        const uint32_t j = st & 3, fb = bars + (B_FULL2 + j) * 8, k = fresh(g2_k(st, n2) * 64);
        mbar_wait(bars + (B_EMPTY2 + j) * 8, ph);
        TSTAMP(5, 16 + st);
        tma2d_mc(sb + j * SLOT + 16384 + rank * 8192, &mWo, n2 * 128 + rank * 64, k, fb);
        mbar_expect_tx(fb, 16384);
      };
      load_wo(4, 1);
      mbar_wait(bars + (B_EMPTY2 + 1) * 8, 1);
      asm volatile(ELECT "cp.async.bulk.tensor.5d.shared::cluster.global.mbarrier::complete_tx::bytes.multicast::cluster [%0], [%1, {%3, %4, %4, %4, %5}], [%2], %6;\n}"
        :: "r"(sb + SLOT + rank * 16384), "l"(&mWp), "r"(bars + (B_FULL2 + 1) * 8), "r"(n2 * 128 + rank * 64), "r"(0), "r"(n2 * 4), "h"((uint16_t)3) : "memory");
      mbar_expect_tx(bars + (B_FULL2 + 1) * 8, SLOT);
      load_wo(2, 1);
      load_wo(3, 1);
      mbar_arrive(bars + B_QE * 8);
      #pragma unroll 1
      for (int it = 1; it < 4; it++) {
        load_wo(4 * it + 1, (it - 1) & 1); load_wo(4 * it + 2, (it - 1) & 1); load_wo(4 * it + 3, (it - 1) & 1);
        if (it < 3) load_wo(4 * it + 4, (it - 1) & 1);
      }
    } else {
      if (warp == 13) {
      if ((sb & 0xffffff) != SB0) __trap();
      float4* zp = reinterpret_cast<float4*>(P.kv + hp * KV_PER_HP + mb * 264);
      const float4 z4 = make_float4(0.f, 0.f, 0.f, 0.f);
      zp[lane] = z4; zp[lane + 32] = z4;
      if (lane < 2) zp[lane + 64] = z4;
      if (lane == 0) P.cnt[hp * 32 + 8 + mb] = t_pf;
      {
        uint4* op = P.o + (m2 * 8 + n2) * 2048 + lane;
        uint32_t t0 = t_pf + RS_T0 + mb * (RS_DT / 8);
        #pragma unroll 1
        for (int i = 0; i < 8; i++) {
          while ((int)((uint32_t)clock() - t0) < 0) __nanosleep(100);
          t0 += RS_DT;
          #pragma unroll
          for (int j = 0; j < 8; j++) op[(i * 8 + j) * 32] = make_uint4(~0u, ~0u, ~0u, ~0u);
        }
      }
      fence_gpu();
      __syncwarp();
      unsigned gen = 0;
      if (lane == 0) gen = (atomicAdd(&P.cnt[hp * 32], 1u) >> 3) + 1;
      gen = uni(gen);
      sts32(sb + D_OFF + 40, gen);
      spin_until(&P.cnt[hp * 32], gen * 8);
      sts32(sb + D_OFF + 48, __ballot_sync(0xffffffffu, (TEST & 4) || __ldcg(&P.cnt[hp * 32 + 8 + (lane & 7)]) - t_pf + 4096 >= 8192));
      mbar_arrive(bars + B_Z * 8);
      }
      {
        float* kr = P.kv + hp * KV_PER_HP;
        mbar_wait(bars + B_Z * 8, 0);
        bar_sync(4, 352);
        #pragma unroll 1
        for (int i0 = max(warp * 6 - 80, 0); i0 < warp * 6 - 74; i0 += 2) {
          uint32_t p[2][4], q[2][4];
          const int i = (i0 + 2 * mb) & 15;
          const uint32_t pa = sb + M_OFF + (i & 3) * 2048 + (i >> 2) * 512 + (lane & 7) * 64 + (((lane >> 3) ^ (lane >> 1)) & 3) * 16;
          lds128(p[0], pa); lds128(q[0], pa + VT); lds128(p[1], pa + 2048); lds128(q[1], pa + VT + 2048);
          #pragma unroll
          for (int j = 0; j < 2; j++)
            asm volatile("red.relaxed.gpu.global.add.v4.f32 [%0], {%1,%2,%3,%4};" :: "l"(kr + (i + j) * 128 + lane * 4),
              "f"(__uint_as_float(p[j][0]) + __uint_as_float(q[j][0])), "f"(__uint_as_float(p[j][1]) + __uint_as_float(q[j][1])),
              "f"(__uint_as_float(p[j][2]) + __uint_as_float(q[j][2])), "f"(__uint_as_float(p[j][3]) + __uint_as_float(q[j][3])) : "memory");
        }
        if (warp == 13) {
          const uint32_t za = sb + M_OFF + 8192 + lane * 4;
          #pragma unroll
          for (int h = 0; h < 2; h++)
            asm volatile("red.relaxed.gpu.global.add.f32 [%0], %1;" :: "l"(kr + 2048 + h * 32 + lane),
              "f"(__uint_as_float(lds32(za + h * 128)) + __uint_as_float(lds32(za + h * 128 + VT))) : "memory");
        }
        bar_sync(5, 96);
        if (warp == 13) {
          mbar_arrive(mapa(bars, rank ^ 1) + B_KVL * 8);
          mbar_arrive(bars + B_MF * 8);
          OSTAMP(17);
          fence_gpu();
          red_add(&P.cnt[hp * 32 + 1]);
          OSTAMP(15);
        }
      }
      const unsigned gen = uni(lds32(sb + D_OFF + 40));
      {
        const int u0 = (15 - warp) * 3;
        const float* kg = P.kv + (2 * n2 + rank) * KV_PER_HP + u0 * 256;
        const uint32_t psb = uni(mapa(sb, rank ^ 1));
        auto put = [&](uint32_t o, uint32_t v0, uint32_t v1, uint32_t v2, uint32_t v3) {
          st_async128(psb + o, psb + BAR_OFF + B_KVB * 8, v0, v1, v2, v3);
          sts128(sb + o, v0, v1, v2, v3);
        };
        auto put8 = [&](int j, const float4* v) {
          put(KVB_OFF + (rank * 8 + u0 + j) * 640 + lane * 16, pack_bf16(v[0].x, v[0].y), pack_bf16(v[0].z, v[0].w), pack_bf16(v[1].x, v[1].y), pack_bf16(v[1].z, v[1].w));
        };
        mbar_wait(bars + B_KVL * 8, 0);
        spin_until(&P.cnt[(2 * n2 + rank) * 32 + 1], gen * 8);
        float4 v[3][2];
        #pragma unroll
        for (int j = 0; j < 2; j++) {
          const float4* kr = reinterpret_cast<const float4*>(kg + j * 256) + lane;
          v[j][0] = __ldcg(kr); v[j][1] = __ldcg(kr + 32);
        }
        if (warp == 13) {
          const float z0 = __ldcg(kg + 512 + lane), z1 = __ldcg(kg + 544 + lane);
          const uint32_t za = KVB_OFF + (rank * 8 + (lane >> 3)) * 640 + 512 + (lane & 7) * 16, a = pack_bf16(z0, z0), b = pack_bf16(z1, z1);
          put(za, a, a, a, a); put(za + 2560, b, b, b, b);
        } else {
          const float4* kr = reinterpret_cast<const float4*>(kg + 512) + lane;
          v[2][0] = __ldcg(kr); v[2][1] = __ldcg(kr + 32);
          put8(2, v[2]);
        }
        put8(0, v[0]); put8(1, v[1]);
        fence_async_smem();
        __syncwarp();
        mbar_arrive(bars + B_KVB * 8);
      }
      if (warp == 13) {
        bar_sync(6, 288);
        mbar_wait(bars + B_GO * 8, 0);
        fence_gpu();
        asm volatile(ELECT "st.relaxed.gpu.global.u32 [%0], %1;\n}" :: "l"(&P.cnt[(16 + m2) * 32 + n2]), "r"(gen) : "memory");
        OSTAMP(32);
      } else {
        const int wg = 15 - warp;
        const uint32_t ab = bars + B_FA * 8 + wg * 32, far = uni(lds32(sb + D_OFF + 48));
        const unsigned* fp = &P.cnt[(32 + m2 * 2 + wg) * 32 + lane];
        const char* og = reinterpret_cast<const char*>(P.o + m2 * 16384 + wg * 512);
        unsigned v = gen;
        auto poll = [&](int k) {
          const bool mine = (lane >> 2) == (k >> 1);
          #pragma unroll 1
          for (int n = 0; n < WAIT_BOUND; n++) {
            asm volatile("ld.relaxed.gpu.global.u32 %0, [%1];" : "=r"(v) : "l"(fp) : "memory");
            if (!__any_sync(0xffffffffu, mine && v != gen)) break;
          }
        };
        mbar_arrive(ab + 8);
        mbar_expect_tx(ab + 16, 8192); mbar_expect_tx(ab + 24, 8192);
        fence_async_global();
        {
          const int k = g2_k(2, n2);
          const char* src = reinterpret_cast<const char*>(__shfl_sync(0xffffffffu, reinterpret_cast<uint64_t>(og + k * 16384), 0));
          mbar_wait(bars + B_QE * 8, 0);
          if (!(TEST & 2)) poll(k);
          bulk_load(sb + 2 * SLOT + wg * 8192, src, 8192, ab + 16);
          bulk_load(sb + 3 * SLOT + wg * 8192, src + 16384, 8192, ab + 24);
        }
        uint32_t safe = (uint32_t)clock() + FAR_DT, miss = __ballot_sync(0xffffffffu, v != gen) | ((TEST & 2) ? ~0xfffu : 0);
        OSTAMP(18 + wg * 15);
        TSTAMP(9, wg * 16 + 8);
        #pragma unroll 1
        for (int st = 4; st < 16; st += 2) {
          const int k = g2_k(st, n2), j = st & 3;
          const char* src = og + k * 16384;
          const uint32_t eb = bars + (B_EMPTY2 + j) * 8, ph = ((st >> 2) - 1) & 1, dst = sb + j * SLOT + wg * 8192;
          if ((miss >> (2 * k)) & 15) {
            poll(k);
            miss = __ballot_sync(0xffffffffu, v != gen);
            safe = (uint32_t)clock() + FAR_DT;
          }
          if ((far >> (k >> 1)) & 1) while ((int)(uni((uint32_t)clock()) - safe) < 0) {}
          mbar_wait(eb, j ? ph : ph ^ 1);
          bulk_load(dst, src, 8192, ab + j * 8);
          mbar_expect_tx(ab + j * 8, 8192);
          if (st < 10) TSTAMP(9, wg * 16 + 5 + st);
          if (st == 4 && wg) { sts32(sb + D_OFF + 44, (uint32_t)clock()); mbar_arrive(bars + B_GO * 8); }
          mbar_wait(eb + 8, ph);
          bulk_load(dst + SLOT, src + 16384, 8192, ab + j * 8 + 8);
          mbar_expect_tx(ab + j * 8 + 8, 8192);
          if (st < 10) TSTAMP(9, wg * 16 + 6 + st);
        }
        if (wg + rank + lane == 0) P.cnt[64 * 32 + id2 * 4] = 0;
      }
    }
  } else {
    asm volatile("setmaxnreg.inc.sync.aligned.u32 %0;" :: "n"(160));
    const int wg = warp >> 2;
    Team c;
    c.bars = bars; c.rel = mapa(bars, tid & 1); c.wofs = wg * 8192; c.lead = fresh((tid & 127) < 2);
    uint32_t key = P.one;
    auto gemm2 = [&](float* a, auto O_, auto SK_, auto last) {
      constexpr int O = O_.value, SK = SK_.value;
      static_assert(SK >= 1 && SK <= 3 + O, "tail");
      uint32_t ph = 1;
      const uint32_t ab = bars + B_FA * 8 + wg * 32;
      #pragma unroll 1
      for (int it = 1; it < 4; it++, ph ^= 1) {
        if (SK == 4 && it == 3) break;
        c.wofs += P.one - 1;
        ring_step<false, O>(c, B_FULL2, ph ^ O, B_EMPTY2 + 3, c.lead, [&](auto f) { g2_issue<O, 0, (MID >> (1 + O)) & 1>(a, c, [&]() { f(); if (O && (tid & 127) == 0 && 4 * it + 0 < 10) TSTAMP(9, wg * 16 + 4 * it + 0 - 2); }); }, ab, ph ^ 1);
        if (!O && (tid & 127) == 0) OSTAMP(55 + wg * 4 + it);
        if (O && (tid & 127) == 0) OSTAMP(40 + wg * 4 + it);
        if (SK == 3 && it == 3) break;
        ring_step<false, O>(c, B_FULL2 + 1, ph, B_EMPTY2, (!O || it < 3 ? c.lead : 0), [&](auto f) { g2_issue<O, 1, (MID >> (1 + O)) & 1>(a, c, [&]() { f(); if (O && (tid & 127) == 0 && 4 * it + 1 < 10) TSTAMP(9, wg * 16 + 4 * it + 1 - 2); }); }, ab + 8, ph);
        if (SK == 2 && it == 3) break;
        ring_step<false, O>(c, B_FULL2 + 2, ph, B_EMPTY2 + 1, (!O || it < 3 ? c.lead : 0), [&](auto f) { g2_issue<O, 2, (MID >> (1 + O)) & 1>(a, c, [&]() { f(); if (O && (tid & 127) == 0 && 4 * it + 2 < 10) TSTAMP(9, wg * 16 + 4 * it + 2 - 2); }); }, ab + 16, ph);
        if (SK == 1 && it == 3) break;
        ring_step<false, O>(c, B_FULL2 + 3, ph, B_EMPTY2 + 2, c.lead, [&](auto f) { g2_issue<O, 3, (MID >> (1 + O)) & 1>(a, c, [&]() { f(); if (O && (tid & 127) == 0 && 4 * it + 3 < 10) TSTAMP(9, wg * 16 + 4 * it + 3 - 2); }); }, ab + 24, ph);
      }
      if (!O) {
        auto rel = [&](int jj, bool on) { arrive_at(c.rel + (B_EMPTY2 + jj) * 8, on ? c.lead : 0); };
        if (wg) { wg_wait<0>(); rel(3 - SK, true); mbar_wait(bars + B_SK * 8, 1); }
        auto st = [&](auto J_) {
          constexpr int J = J_.value;
          mbar_wait(bars + (B_FULL2 + J) * 8, 1);
          g2_half<0, J, 0>(a, c);
          wg_wait<1>(); rel(J - 1, J > 4 - SK || !wg);
          g2_half<0, J, 1>(a, c);
          if (J < 3) wg_wait<1>();
        };
        if (SK >= 3) st(IC<1>());
        if (SK >= 2) st(IC<2>());
        st(IC<3>());
        arrive_at(bars + B_SK * 8, fresh_tid() == 0);
        last();
        wg_wait<0>(); rel(3, true);
      } else
      skew_tail<SK>(c, O ^ 1,
        [&]() {
          auto full = [&](int jj) { mbar_wait(bars + (B_FULL2 + jj) * 8, 1); mbar_wait(ab + jj * 8, 1); };
          if (SK >= 4) {
            mbar_wait(bars + B_FULL2 * 8, 0); mbar_wait(ab, 0); g2_issue<O, 0>(a, c);
            wg_wait<1>(); arrive_at(c.rel + (B_EMPTY2 + 3) * 8, wg ? 0 : c.lead);
          }
          if (SK >= 3) { full(1); g2_issue<O, 1>(a, c); }
          if (SK >= 2) { full(2); g2_issue<O, 2>(a, c); }
          full(3); g2_issue<O, 3>(a, c);
        },
        [&](int i) { if (SK == 4 && i < 0) arrive_at(c.rel + (B_EMPTY2 + 3) * 8, wg ? c.lead : 0); });
      pinv<64>(a);
    };
    float aq[64];
    {
      float aK[64], aV[64];
      if (wg == 0) { kv_issue<0>(aK, aV, 0, 0); wg_wait<0>(); }
      cluster_wait();
      if (wg == 1) mbar_wait(bars + B_F0 * 8, 0);
      static_assert(SK1 >= 1 && SK1 <= 3, "tail");
      uint32_t ph = 0, xs = 2, xp = 0;
      auto next_x = [&]() { if (xs == 1) xp ^= 1; xs = xs == 2 ? 0 : xs + 1; };
      uint32_t rel = 0;
      int look = 5;
      uint32_t xo = xs * SLOT + wg * 16384;
      #pragma unroll 1
      for (int it = 0; it < 8; it++, ph ^= 1) {
        ring_step<false, true>(c, B_FULL, ph, B_EMPTY + 3, rel, [&](auto f) { kv_issue<0, MID & 1>(aK, aV, xo, it, f); if (tid == 0 && it == 0) OSTAMP(1); }, bars + (B_XF + xs) * 8, xp);
        if (SK1 == 3 && it == 7) break;
        next_x();
        ring_step<false>(c, B_FULL + 1, ph, B_EMPTY, c.lead, [&](auto f) { kv_issue<1, MID & 1>(aK, aV, xo, 1, f); });
        if (SK1 == 2 && it == 7) break;
        xo = xs * SLOT + wg * 16384;
        ring_step<false, true>(c, B_FULL + 2, ph, B_EMPTY + 1, c.lead, [&](auto f) { kv_issue<2, MID & 1>(aK, aV, xo, 1, f); }, bars + (B_XF + xs) * 8, xp);
        if (SK1 == 1 && it == 7) break;
        next_x();
        ring_step<false>(c, B_FULL + 3, ph, B_EMPTY + 2, c.lead, [&](auto f) { kv_issue<3, MID & 1>(aK, aV, xo, 1, f); });
        rel = c.lead;
        xo = xs * SLOT + wg * 16384;
        if (it == look && wrong_job()) { mbar_wait(bars + B_EX * 8, 0); it = look = -1; }
      }
      skew_tail<SK1>(c, 0,
        [&]() {
          auto wait = [&](uint32_t a) { mbar_wait(a, 1); };
          if (SK1 >= 3) { wait(bars + (B_FULL + 1) * 8); kv_issue<1>(aK, aV, SLOT + wg * 16384, 1); }
          if (SK1 >= 2) { wait(bars + (B_FULL + 2) * 8); wait(bars + (B_XF + 2) * 8); kv_issue<2>(aK, aV, 2 * SLOT + wg * 16384, 1); }
          wait(bars + (B_FULL + 3) * 8); kv_issue<3>(aK, aV, 2 * SLOT + wg * 16384, 1);
        },
        [&](int i) { arrive_at(c.rel + (B_EMPTY + ((32 - SK1 + i) & 3)) * 8, c.lead); });
      pinv<64>(aV); pinv<64>(aK);
      if (tid == 128) OSTAMP(3);
      const uint32_t vb = sb + M_OFF + wg * VT;
      float kv[36];
      uint32_t kf[4][8];
      const uint64_t dv = dofs(cdesc(M_OFF, 1152, 128, 0), wg * VT);
      const int t = fresh_tid();
      const uint32_t va = vb + ((t >> 4) & 1) * 1152 + ((t >> 5) & 3) * 256 + (t & 15) * 16;
      mbar_wait(bars + B_X * 8, 0);
      #pragma unroll
      for (int i = 0; i < 8; i++) {
        const float* a = aV + 8 * i;
        stsm4(va + i * 2304, pack_bf16(a[0], a[1]), pack_bf16(a[2], a[3]), pack_bf16(a[4], a[5]), pack_bf16(a[6], a[7]));
      }
      phi_a(aK + 48, kf[3]);
      mbar_wait(bars + B_FULL2 * 8, 0);
      if ((tid & 127) == 0) OSTAMP(50 + wg);
      g2_issue<0, 0, false, true>(aq, c);
      sched_fence(key++);
      sts128(vb + ((t & 127) >> 3) * 1152 + 1024 + (t & 7) * 16, 0x3f803f80u, 0x3f803f80u, 0x3f803f80u, 0x3f803f80u);
      phi_a(aK + 32, kf[2]); phi_b(aK + 48, kf[3]);
      sched_fence(key++);
      ring_step<true>(c, B_FULL2 + 1, 0, B_EMPTY2, c.lead, [&]() { g2_issue<0, 1>(aq, c); });
      sched_fence(key++);
      phi_a(aK + 16, kf[1]); phi_b(aK + 32, kf[2]);
      sched_fence(key++);
      ring_step<true>(c, B_FULL2 + 2, 0, B_EMPTY2 + 1, c.lead, [&]() { g2_issue<0, 2>(aq, c); });
      sched_fence(key++);
      phi_a(aK, kf[0]); phi_b(aK + 16, kf[1]);
      sched_fence(key++);
      fence_async_smem(); bar_sync(1 + wg, 128);
      phi_b(aK, kf[0]);
      sched_fence(key++);
      wg_fence();
      #pragma unroll
      for (int ks = 0; ks < 8; ks++) {
        if (ks == 0) rs72z<0>(kv, kf[0], dv); else rs72a<0>(kv, kf[ks >> 1] + 4 * (ks & 1), dofs(dv, ks * 2304));
      }
      wg_commit();
      wg_wait<1>();
      arrive_at(c.rel + (B_EMPTY2 + 2) * 8, c.lead);
      mbar_wait(bars + (B_FULL2 + 3) * 8, 0);
      g2_issue<0, 3>(aq, c);
      wg_wait<1>();
      pinv<36>(kv);
      const int a = fresh_tid() & 127;
      const bool hi = a >= 64;
      #pragma unroll
      for (int u = 0; u < 4; u++) {
        const int o = (u & 1) * 8 + (u & 2);
        sts128(vb + (a ^ ((a >> 3) & 3)) * 16 + u * 2048, __float_as_uint(hi ? kv[16 + o] : kv[o]), __float_as_uint(hi ? kv[17 + o] : kv[o + 1]),
               __float_as_uint(hi ? kv[20 + o] : kv[o + 4]), __float_as_uint(hi ? kv[21 + o] : kv[o + 5]));
      }
      if ((a & 3) < 2) sts32(vb + 8192 + ((a >> 5) * 16 + ((a & 31) >> 2) + (a & 1) * 8) * 4, __float_as_uint((a & 1) ? kv[34] : kv[32]));
      bar_arrive(4, 352);
    }
    if (tid == 0) OSTAMP(4);
    if (tid == 128) OSTAMP(5);
    float acc[64];
    {
      uint32_t kvok;
      gemm2(aq, IC<0>(), IC<SK2>(), [&]() {
        kvok = mbar_try(bars + B_KVB * 8, 0);
        if (kvok) fence_async_smem();
      });
      if (tid == 0) OSTAMP(6);
      if (tid == 128) OSTAMP(7);
      constexpr uint64_t dk = cdesc(KVB_OFF, 640, 128, 0);
      const uint32_t id2 = job(); IDS(id2);
      float nu[4][20];
      uint32_t pq[4][8], o[4][2][4];
      const int t2 = fresh_tid();
      const uint32_t oo = (t2 & 96) * 32 + (t2 & 28) * 16 + ((t2 ^ (t2 >> 3)) & 3) * 16;
      uint4* og = P.o + ((m2 * 8 + n2) * 4 + wg) * 512 + (oo >> 4);
      auto o_put = [&](int h, int e) {
        asm volatile("st.global.v4.b32 [%0], {%1,%2,%3,%4};" :: "l"(og + (h >> 1) * 1024 + (h & 1) * 256 + e * 32),
          "r"(o[h][e][0]), "r"(o[h][e][1]), "r"(o[h][e][2]), "r"(o[h][e][3]) : "memory");
      };
      auto o_out = [&](int h) {
        pinv<20>(nu[h]);
        #pragma unroll
        for (int e = 0; e < 2; e++) {
          const float* n = nu[h] + 2 * e;
          const float iv = rcp_fast(n[16] + 1e-6f);
          #pragma unroll
          for (int i = 0; i < 4; i++) o[h][e][i] = pack_bf16(n[4 * i] * iv, n[4 * i + 1] * iv);
          o_put(h, e);
        }
      };
      auto o_mma = [&](int h) {
        wg_fence();
        rs40z<1>(nu[h], pq[h], dk + h * (2560 >> 4));
        rs40a<1>(nu[h], pq[h] + 4, dk + h * (2560 >> 4) + (1280 >> 4));
        wg_commit();
      };
      auto sent = [&](uint32_t v) {
        asm volatile(ELECT "st.relaxed.gpu.global.u32 [%0], %1;\n}" :: "l"(&P.cnt[(32 + m2 * 2 + wg) * 32 + n2 * 4 + (warp & 3)]), "r"(v) : "memory");
      };
      phi_s(aq, pq[0]); phi_e(aq); phi_s(aq + 16, pq[1]);
      if (!kvok) { mbar_wait(bars + B_KVB * 8, 0); fence_async_smem(); }
      const uint32_t gen = lds32(sb + D_OFF + 40), far = lds32(sb + D_OFF + 48);
      #pragma unroll
      for (int u = 0; u < 4; u++) {
        if (u < 3) phi_e(aq + 16 * u + 16);
        phi_b(aq + 16 * u, pq[u]);
        o_mma(u);
        if (u < 2) phi_s(aq + 16 * u + 32, pq[u + 2]);
        if (u > 0) { wg_wait<1>(); o_out(u - 1); }
        sched_fence(key++);
      }
      wg_wait<0>(); o_out(3);
      sent(gen);
      bar_arrive(6, 288);
      arrive_at(bars + B_OD * 8, t2 == 128);
      if ((t2 & 127) == 0) OSTAMP(8 + wg * 2);
      {
        sched_fence(key++);
        #pragma unroll
        for (int i = 0; i < 32; i++) asm volatile("lop3.b32 %0, %1, %2, 0, 0xf0 | 0xcc;" : "=r"(o[i >> 3][(i >> 2) & 1][i & 3]) : "r"(o[i >> 3][(i >> 2) & 1][i & 3]), "r"(P.one - 1));
      }
      if (wg == 0) mbar_wait(bars + B_OD * 8, 0);
      mbar_wait(bars + (B_FULL2 + 1) * 8, 0);
      wg_fence();
      #pragma unroll
      for (int i = 0; i < 8; i++) {
        const uint32_t f[4] = {o[i >> 1][0][i & 1], o[i >> 1][1][i & 1], o[i >> 1][0][2 + (i & 1)], o[i >> 1][1][2 + (i & 1)]};
        constexpr uint64_t dw = cdesc(SLOT, 16384, 2048, 1);
        if (i == 0) rs128z<1>(acc, f, dw); else rs128a<1>(acc, f, dw + (((i >> 1) * 4096 + (i & 1) * 1024) >> 4));
      }
      wg_commit();
      if ((t2 & 127) == 0) OSTAMP(37 + wg);
      if ((t2 & 127) == 0) TSTAMP(9, wg * 16 + 15);
      const uint32_t ab = bars + B_FA * 8 + wg * 32;
      const int k2 = g2_k(2, n2);
      const bool doubt = (uni(far) >> (k2 >> 1)) & 1;
      auto look = [&](int j) {
        if (doubt) {
          const uint32_t a = sb + (2 + j) * SLOT + wg * 8192 + (t2 & 96) * 32;
          if (__any_sync(0xffffffffu, lds32(a + (t2 & 16) * 256 + (t2 & 15) * 64 + (t2 & 30) * 2) == ~0u)) {
            const uint4* src = P.o + (m2 * 16 + k2 + j) * 1024 + wg * 512 + (t2 & 96) * 2 + (t2 & 31);
            if ((t2 & 31) == 0) OSTAMP(34);
            #pragma unroll 1
            for (int i = 0; i < 4; i++) {
              uint32_t v[4];
              int n = 0;
              do asm volatile("ld.relaxed.gpu.global.v4.u32 {%0,%1,%2,%3}, [%4];" : "=r"(v[0]), "=r"(v[1]), "=r"(v[2]), "=r"(v[3]) : "l"(src + (i & 1) * 32 + (i >> 1) * 256) : "memory");
              while (__any_sync(0xffffffffu, v[0] == ~0u) && ++n < 64);
              sts128(a + (t2 & 31) * 16 + (i & 1) * 512 + (i >> 1) * 4096, v[0], v[1], v[2], v[3]);
            }
            fence_async_smem();
            __syncwarp();
          }
        }
      };
      #pragma unroll 1
      for (int j = 0; j < 2; j += P.one)
        ring_step<true, true>(c, B_FULL2 + 2 + j, 0, B_EMPTY2 + 1 + j, c.lead, [&]() {
          look(j);
          if ((t2 & 127) == 0 && j == 0) OSTAMP(11 + wg * 24);
          if ((t2 & 127) == 0) TSTAMP(9, wg * 16 + j);
          const uint64_t da = dofs(cdesc(2 * SLOT, 16, 512, 2), c.wofs + j * SLOT), db = dofs(cdesc(2 * SLOT + 16384, 8192, 1024, 1), j * SLOT);
          wg_fence();
          #pragma unroll
          for (int i = 0; i < 4; i++) ss128a<0, 1>(acc, dofs(da, (i & 1) * 32 + (i >> 1) * 4096), dofs(db, i * 2048));
          wg_commit();
        }, ab + 16 + j * 8, 0);
    }
    gemm2(acc, IC<1>(), IC<SK3>(), []() {});
    if (tid == 0) OSTAMP(13);
    if (tid == 128) OSTAMP(14);
    {
      const uint32_t id2 = job(); IDS(id2);
      const int t2 = fresh_tid();
      const int row = ((t2 >> 5) & 3) * 16 + (t2 & 15);
      const int cq = (t2 >> 4) & 1, sw = t2 & 7;
      const uint32_t stg = sb + (EHI ? T_OFF : 0) + wg * 8192;
      constexpr uint32_t HS = EHI ? 16384 : SLOT;
      if (EHI) mbar_wait(bars + B_CD * 8, 0);
      #pragma unroll 1
      for (int pass = 0;; pass++) {
      const bool bad = acc[0] != acc[0] || acc[2] != acc[2];
      #pragma unroll
      for (int hf = 0; hf < 2; hf++) {
        #pragma unroll
        for (int jj = 0; jj < 4; jj++) {
          const int o = hf * 32 + jj * 8;
          stsm4(stg + hf * HS + row * 128 + (((2 * jj + cq) ^ sw) << 4),
                pack_bf16(acc[o], acc[o + 1]), pack_bf16(acc[o + 2], acc[o + 3]),
                pack_bf16(acc[o + 4], acc[o + 5]), pack_bf16(acc[o + 6], acc[o + 7]));
        }
        fence_async_smem();
        __syncwarp();
        tma2d_store(&mOut, 1024 + n2 * 128 + hf * 64, m2 * 128 + warp * 16, sb + (EHI ? T_OFF : 0) + hf * HS + warp * 2048);
      }
      bulk_commit();
      uint32_t redo;
      asm volatile("{\n.reg .pred p, q;\nsetp.ne.b32 p, %1, 0;\nbar.red.or.pred q, %2, 128, p;\nselp.u32 %0, 1, 0, q;\n}" : "=r"(redo) : "r"((uint32_t)bad), "r"(1 + wg) : "memory");
      if (!uni(redo) || pass) break;
      if ((t2 & 127) == 0) OSTAMP(48 + wg);
      asm volatile("cp.async.bulk.wait_group 0;" ::: "memory");
      spin_until(&P.cnt[(16 + m2) * 32 + (t2 & 7)], lds32(sb + D_OFF + 40));
      fence_async_global();
      const uint32_t ab = bars + B_FA * 8 + wg * 32;
      #pragma unroll 1
      for (int k = 0; k < 16; k += P.one) {
        bar_sync(1 + wg, 128);
        if ((warp & 3) == 0) {
          mbar_expect_tx(ab, 24576);
          bulk_load(sb + c.wofs, P.o + (m2 * 16 + k) * 1024 + wg * 512, 8192, ab);
          tma2d(sb + SLOT + c.wofs, &mWo, n2 * 128, k * 64, ab);
          tma2d(sb + 2 * SLOT + c.wofs, &mWo, n2 * 128 + 64, k * 64, ab);
        }
        mbar_wait(ab, ~k & 1);
        const uint64_t da = dofs(cdesc(0, 16, 512, 2), c.wofs), db = dofs(cdesc(SLOT, SLOT, 1024, 1), c.wofs);
        wg_fence();
        ss128p<0, 1>(acc, da, db, k);
        ss128a<0, 1>(acc, dofs(da, 32), dofs(db, 2048));
        ss128a<0, 1>(acc, dofs(da, 4096), dofs(db, 4096));
        ss128a<0, 1>(acc, dofs(da, 4128), dofs(db, 6144));
        wg_commit();
        wg_wait<0>(); pinv<64>(acc);
      }
      }
      bulk_wait_read();
    }
  }
}

typedef CUresult (*EncodeFn)(CUtensorMap*, CUtensorMapDataType, cuuint32_t, void*, const cuuint64_t*, const cuuint64_t*,
                             const cuuint32_t*, const cuuint32_t*, CUtensorMapInterleave, CUtensorMapSwizzle,
                             CUtensorMapL2promotion, CUtensorMapFloatOOBfill);

void encode(EncodeFn fn, CUtensorMap* m, const void* ptr, int rank, const cuuint64_t* dims, const cuuint64_t* strides,
            const cuuint32_t* box, CUtensorMapSwizzle sw, CUtensorMapL2promotion pr) {
  const cuuint32_t es[5] = {1, 1, 1, 1, 1};
  fn(m, CU_TENSOR_MAP_DATA_TYPE_BFLOAT16, rank, const_cast<void*>(ptr), dims, strides, box, es,
     CU_TENSOR_MAP_INTERLEAVE_NONE, sw, pr, CU_TENSOR_MAP_FLOAT_OOB_FILL_NONE);
}

}

extern "C" void kernel_launch(void* const* d_in, const int* in_sizes, int n_in, void* d_out, int out_size) {
  (void)in_sizes; (void)n_in; (void)out_size;
  static EncodeFn fn = nullptr;
  static void *po, *pkv, *pcnt;
  if (!fn) {
    void* p = nullptr; cudaDriverEntryPointQueryResult qr;
    cudaGetDriverEntryPoint("cuTensorMapEncodeTiled", &p, cudaEnableDefault, &qr);
    fn = (EncodeFn)p;
    cudaGetSymbolAddress(&po, g_O); cudaGetSymbolAddress(&pkv, g_kv); cudaGetSymbolAddress(&pcnt, g_cnt);
    cudaFuncSetAttribute(fused_kernel, cudaFuncAttributeMaxDynamicSharedMemorySize, SMEM_BYTES);
  }
  const CUtensorMapL2promotion P128 = CU_TENSOR_MAP_L2_PROMOTION_L2_128B, P0 = CU_TENSOR_MAP_L2_PROMOTION_NONE;
  CUtensorMap mX, mW, mWq, mWo, mK, mV, mH, mQ, mOut, mOutA, mWp;
  { cuuint64_t d[2] = {1024, 2048}, s[1] = {2048}; cuuint32_t bx[2] = {64, 128}, bq[2] = {16, 128};
    encode(fn, &mX, d_in[6], 2, d, s, bx, CU_TENSOR_MAP_SWIZZLE_128B, P128);
    encode(fn, &mQ, d_in[0], 2, d, s, bq, CU_TENSOR_MAP_SWIZZLE_NONE, P128); }
  { cuuint64_t d[3] = {1024, 1024, 3}, s[2] = {6144, 2048}; cuuint32_t bx[3] = {64, 32, 2};
    encode(fn, &mW, d_in[7], 3, d, s, bx, CU_TENSOR_MAP_SWIZZLE_128B, P128); }
  { cuuint64_t d[2] = {1024, 1024}, s[1] = {6144}, so[1] = {2048}; cuuint32_t bx[2] = {64, 64};
    encode(fn, &mWq, d_in[7], 2, d, s, bx, CU_TENSOR_MAP_SWIZZLE_128B, P128);
    encode(fn, &mWo, d_in[8], 2, d, so, bx, CU_TENSOR_MAP_SWIZZLE_128B, P128); }
  { cuuint64_t d[5] = {1024, 2, 4, 4, 32}, s[4] = {2048, 16384, 4096, 65536}; cuuint32_t bx[5] = {64, 2, 4, 4, 4};
    encode(fn, &mWp, d_in[8], 5, d, s, bx, CU_TENSOR_MAP_SWIZZLE_128B, P128); }
  { cuuint64_t d[3] = {1024, 128, 16}, s[2] = {32768, 2048}; cuuint32_t bk[3] = {16, 17, 8}, bv[3] = {16, 16, 8};
    encode(fn, &mK, d_in[1], 3, d, s, bk, CU_TENSOR_MAP_SWIZZLE_32B, P128);
    encode(fn, &mV, d_in[2], 3, d, s, bv, CU_TENSOR_MAP_SWIZZLE_32B, P128); }
  { cuuint64_t d[2] = {16, 131072}, s[1] = {32}; cuuint32_t bx[2] = {16, 128};
    encode(fn, &mH, d_in[4], 2, d, s, bx, CU_TENSOR_MAP_SWIZZLE_32B, CU_TENSOR_MAP_L2_PROMOTION_L2_256B); }
  { cuuint64_t d[2] = {2048, 2048}, s[1] = {4096}; cuuint32_t bx[2] = {64, 16}, ba[2] = {16, 32};
    encode(fn, &mOut, d_out, 2, d, s, bx, CU_TENSOR_MAP_SWIZZLE_128B, P0);
    encode(fn, &mOutA, d_out, 2, d, s, ba, CU_TENSOR_MAP_SWIZZLE_NONE, P0); }
  Params P;
  P.shift = (const __nv_bfloat16*)d_in[3]; P.ssmD = (const __nv_bfloat16*)d_in[5];
  P.x = (const __nv_bfloat16*)d_in[6]; P.w = (const __nv_bfloat16*)d_in[7]; P.out = (__nv_bfloat16*)d_out; P.one = 1;
  P.o = (uint4*)po; P.kv = (float*)pkv; P.cnt = (unsigned*)pcnt;
  P.k = (const char*)d_in[1]; P.v = (const char*)d_in[2];
  P.pt[0] = {(const char*)d_in[6], 16 * 32768, 64 * 32768, 65536, 32768, 256, 4096, 2048};
  P.pt[1] = {(const char*)d_in[7] + 2048, 256, 1024, 16 * 6144, 8 * 6144, 128 * 6144, 6144, 2048};
  P.pt[2] = {(const char*)d_in[7], 512, 128 * 6144, 16 * 6144, 8 * 6144, 256 * 6144, 6144, 256};
  P.pt[3] = {(const char*)d_in[8], 512, 128 * 2048, 16 * 2048, 8 * 2048, 256 * 2048, 2048, 256};
  P.pt[4] = {(const char*)d_in[0], 256, 1024, 32768, 2097152, 262144, 4096, 2048};
  P.pt[5] = {(const char*)d_in[4], 16 * 32768, 64 * 32768, 65536, 32768, 4096, 512, 256};
  const uint8_t pf[32] = {PF_LIST};
  for (int i = 0; i < 32; i++) P.pf[i] = pf[i];
  const uint64_t cd[18] = {CONV_DESC};
  for (int i = 0; i < 18; i++) P.cd[i] = cd[i];
  fused_kernel<<<NCTA, NTHREADS, SMEM_BYTES, cudaStreamPerThread>>>(P, mX, mW, mWq, mWo, mK, mV, mH, mQ, mOut, mOutA, mWp);
}
```

```cpp
#include <cuda_runtime.h>
#include <cuda_bf16.h>
#include <cuda.h>
#include <stdint.h>

#define PARAM(name, value) constexpr int name = value
#define TUNE
namespace dflt {
PARAM(SK1, 2); PARAM(SK2, 3); PARAM(SK3, 3);
PARAM(MID, 3);
PARAM(STG_T0, 700); PARAM(STG_DT, 540);
PARAM(RS_T0, 12000); PARAM(RS_DT, 600);
PARAM(FAR_DT, 400);
PARAM(OA_END, 7400); PARAM(OA_MIN, 200); PARAM(OA_MAX, 450);
PARAM(PF_DT0, 400); PARAM(PF_DT1, 1100); PARAM(PF_DT2, 540); PARAM(PF_N1, 9);
PARAM(TEST, 0);
PARAM(P8, 1); PARAM(EHI, 1); PARAM(FG, 2); PARAM(CI, 1); PARAM(CW, 2);
}
#define PF_LIST 0x01, 0x11, 0x02, 0x12, 0x03, 0x13, 0x04, 0x14, 0x05, 0x15, 0x51, 0x06, 0x16, 0x20, 0x07, 0x17, 0x21, 0x22, 0x23, \
                0x40, 0x41, 0x42, 0x43, 0x44, 0x45, 0x46, 0x47, 0x30, 0x31, 0x32, 0x33
#define PF_N 31
#define WAIT_BOUND 262144

namespace {
using namespace dflt;
TUNE

constexpr int S_LEN = 2048;
constexpr int DM    = 1024;
constexpr int NCTA  = 128;
constexpr int NTHREADS = 512;
constexpr int SLOT  = 32768;
constexpr int W_OFF = 3 * SLOT;
constexpr int M_OFF = 4 * SLOT;
constexpr int VT    = 16 * 1152;
constexpr int T_OFF = M_OFF + 43008;
constexpr int XS    = 4096 + 16;
constexpr int YX    = 2048 + 16;
constexpr int X_OFF = T_OFF + 8192 + 2176;
constexpr int H_OFF = X_OFF + 8 * XS;
constexpr int A_OFF = H_OFF + 4096;
constexpr int F_OFF = A_OFF + 8192;
constexpr int BAR_OFF = F_OFF + 2048;
constexpr int D_OFF = BAR_OFF + 384;
constexpr int SMEM_BYTES = D_OFF + 64 + 256;
constexpr int KB = 8704;
constexpr int KVB_OFF = M_OFF + 32768;
static_assert(H_OFF % 256 == 0 && X_OFF % 128 == 0 && SMEM_BYTES <= 232448, "layout");
constexpr int B_XF = 0, B_F0 = 3, B_FULL = 4, B_FA = 4, B_FULL2 = 25, B_KVL = 24, B_STG = 8, B_X = 12, B_Z = 13, B_H = 14, B_Q = 15, B_YR = 16,
              B_SK = 29, B_GO = 30, B_QE = 31,
              B_EMPTY = 32, B_KVB = 36, B_EMPTY2 = 37, B_SFREE = 41, B_CD = 43, B_MF = 44, B_OD = 45, B_EX = 46;
constexpr int KV_PER_HP = 2 * 1056;

__device__ __align__(1024) uint4 g_O[S_LEN * DM / 8];
__device__ __align__(128) float g_kv[16 * KV_PER_HP];
__device__ __align__(128) unsigned g_cnt[81 * 32];

#define OSTAMP(i) do {} while (0)
#define TSTAMP(k, i) do {} while (0)

__device__ __forceinline__ uint32_t wanted_job() {
  uint32_t t;
  asm volatile("mov.u32 %0, %%smid;" : "=r"(t));
  if (TEST & 1) t = t * 3 % 100;
  t >>= 1;
  const uint32_t q = ((t - 32) * 37) >> 8;
  uint32_t r;
  asm("{\n.reg .pred p, q;\nsetp.lt.u32 p, %3, 32;\nsetp.lt.u32 q, %3, 62;\nselp.u32 %0, %1, %2, q;\nselp.u32 %0, %3, %0, p;\n}" : "=&r"(r) : "r"(t + 1 + q), "r"((t - 58) * 8), "r"(t));
  return (r & 7) | ((((r & 7 ? 0x76154032 : 0x76543012) >> ((r >> 1) & 28)) & 7) << 3);
}

#define ELECT "{\n.reg .pred e;\nelect.sync _|e, 0xffffffff;\n@e "
__device__ __forceinline__ uint32_t uni(uint32_t v) { return __shfl_sync(0xffffffffu, v, 0); }
__device__ __forceinline__ uint32_t fresh(uint32_t v) { asm volatile("" : "+r"(v)); return v; }
__device__ __forceinline__ uint32_t smem_u32(const void* p) { return (uint32_t)__cvta_generic_to_shared(p); }
__device__ __forceinline__ void mbar_init(uint32_t b, uint32_t c) { asm volatile(ELECT "mbarrier.init.shared::cta.b64 [%0], %1;\n}" :: "r"(b), "r"(c) : "memory"); }
__device__ __forceinline__ void mbar_expect_tx(uint32_t b, uint32_t bytes) { asm volatile(ELECT "mbarrier.arrive.expect_tx.shared::cta.b64 _, [%0], %1;\n}" :: "r"(b), "r"(bytes) : "memory"); }
__device__ __forceinline__ void mbar_arrive(uint32_t b) { asm volatile(ELECT "mbarrier.arrive.shared::cluster.b64 _, [%0];\n}" :: "r"(b) : "memory"); }
__device__ __forceinline__ void mbar_wait(uint32_t b, uint32_t ph) {
  asm volatile("{\n.reg .pred p;\nWAIT_LOOP:\nmbarrier.try_wait.parity.shared::cta.b64 p, [%0], %1;\n@!p bra.uni WAIT_LOOP;\n}" :: "r"(b), "r"(ph) : "memory");
}
__device__ __forceinline__ void tma2d(uint32_t dst, const CUtensorMap* m, int c0, int c1, uint32_t bar) {
  asm volatile(ELECT "cp.async.bulk.tensor.2d.shared::cluster.global.mbarrier::complete_tx::bytes [%0], [%1, {%3, %4}], [%2];\n}"
    :: "r"(dst), "l"(m), "r"(bar), "r"(c0), "r"(c1) : "memory"); }
__device__ __forceinline__ void tma2d_mc(uint32_t dst, const CUtensorMap* m, int c0, int c1, uint32_t bar) {
  asm volatile(ELECT "cp.async.bulk.tensor.2d.shared::cluster.global.mbarrier::complete_tx::bytes.multicast::cluster [%0], [%1, {%3, %4}], [%2], %5;\n}"
    :: "r"(dst), "l"(m), "r"(bar), "r"(c0), "r"(c1), "h"((uint16_t)3) : "memory"); }
__device__ __forceinline__ void tma3d(uint32_t dst, const CUtensorMap* m, int c0, int c1, int c2, uint32_t bar) {
  asm volatile(ELECT "cp.async.bulk.tensor.3d.shared::cluster.global.mbarrier::complete_tx::bytes [%0], [%1, {%3, %4, %5}], [%2];\n}"
    :: "r"(dst), "l"(m), "r"(bar), "r"(c0), "r"(c1), "r"(c2) : "memory"); }
__device__ __forceinline__ void tma2d_store(const CUtensorMap* m, int c0, int c1, uint32_t src) {
  asm volatile(ELECT "cp.async.bulk.tensor.2d.global.shared::cta.bulk_group [%0, {%2, %3}], [%1];\n}"
    :: "l"(m), "r"(src), "r"(c0), "r"(c1) : "memory"); }
__device__ __forceinline__ void bulk_load(uint32_t dst, const void* src, uint32_t bytes, uint32_t bar) {
  asm volatile(ELECT "cp.async.bulk.shared::cluster.global.mbarrier::complete_tx::bytes [%0], [%1], %2, [%3];\n}"
    :: "r"(dst), "l"(src), "r"(bytes), "r"(bar) : "memory"); }
__device__ __forceinline__ void bulk_commit() { asm volatile("cp.async.bulk.commit_group;" ::: "memory"); }
__device__ __forceinline__ void bulk_wait_read() { asm volatile("cp.async.bulk.wait_group.read 0;" ::: "memory"); }
__device__ __forceinline__ void fence_async_smem() { asm volatile("fence.proxy.async.shared::cta;" ::: "memory"); }
__device__ __forceinline__ void bar_sync(int id, int n) { asm volatile("bar.sync %0, %1;" :: "r"(id), "r"(n) : "memory"); }
__device__ __forceinline__ void bar_arrive(int id, int n) { asm volatile("bar.arrive %0, %1;" :: "r"(id), "r"(n) : "memory"); }
__device__ __forceinline__ void wg_fence() { asm volatile("wgmma.fence.sync.aligned;" ::: "memory"); }
__device__ __forceinline__ void wg_commit() { asm volatile("wgmma.commit_group.sync.aligned;" ::: "memory"); }
template <int N> __device__ __forceinline__ void wg_wait() { asm volatile("wgmma.wait_group.sync.aligned %0;" :: "n"(N) : "memory"); }
constexpr uint32_t SB0 = 1024;
__host__ __device__ constexpr uint64_t cdesc(uint32_t off, uint32_t lbo, uint32_t sbo, uint32_t swz) {
  return (uint64_t)((SB0 + off) >> 4) | ((uint64_t)(lbo >> 4) << 16) | ((uint64_t)(sbo >> 4) << 32) | ((uint64_t)swz << 62); }
__device__ __forceinline__ uint64_t dofs(uint64_t d, uint32_t bytes) { return (d & 0xffffffff00000000ull) | (uint32_t)((uint32_t)d + (bytes >> 4)); }
__device__ __forceinline__ uint32_t mbar_try(uint32_t b, uint32_t ph) {
  uint32_t ok;
  asm volatile("{\n.reg .pred p;\nmbarrier.test_wait.parity.shared::cta.b64 p, [%1], %2;\nselp.u32 %0, 1, 0, p;\n}" : "=r"(ok) : "r"(b), "r"(ph) : "memory");
  return ok; }
__device__ __forceinline__ void arrive_at(uint32_t a, uint32_t on) {
  asm volatile("{\n.reg .pred p;\nsetp.ne.b32 p, %1, 0;\n@p mbarrier.arrive.shared::cluster.b64 _, [%0];\n}" :: "r"(a), "r"(on) : "memory"); }
__device__ __forceinline__ void ldsm4(uint32_t* r, uint32_t a) {
  asm volatile("ldmatrix.sync.aligned.m8n8.x4.shared.b16 {%0,%1,%2,%3}, [%4];" : "=r"(r[0]), "=r"(r[1]), "=r"(r[2]), "=r"(r[3]) : "r"(a) : "memory"); }
__device__ __forceinline__ void ldsm4t(uint32_t* r, uint32_t a) {
  asm volatile("ldmatrix.sync.aligned.m8n8.x4.trans.shared.b16 {%0,%1,%2,%3}, [%4];" : "=r"(r[0]), "=r"(r[1]), "=r"(r[2]), "=r"(r[3]) : "r"(a) : "memory"); }
__device__ __forceinline__ void stsm4(uint32_t a, uint32_t r0, uint32_t r1, uint32_t r2, uint32_t r3) {
  asm volatile("stmatrix.sync.aligned.m8n8.x4.shared.b16 [%0], {%1,%2,%3,%4};" :: "r"(a), "r"(r0), "r"(r1), "r"(r2), "r"(r3) : "memory"); }
__device__ __forceinline__ void stsm4t(uint32_t a, uint32_t r0, uint32_t r1, uint32_t r2, uint32_t r3) {
  asm volatile("stmatrix.sync.aligned.m8n8.x4.trans.shared.b16 [%0], {%1,%2,%3,%4};" :: "r"(a), "r"(r0), "r"(r1), "r"(r2), "r"(r3) : "memory"); }
__device__ __forceinline__ uint32_t lds32(uint32_t a) { uint32_t v; asm volatile("ld.shared.b32 %0, [%1];" : "=r"(v) : "r"(a) : "memory"); return v; }
__device__ __forceinline__ void lds128(uint32_t* v, uint32_t a) { asm volatile("ld.shared.v4.b32 {%0,%1,%2,%3}, [%4];" : "=r"(v[0]), "=r"(v[1]), "=r"(v[2]), "=r"(v[3]) : "r"(a) : "memory"); }
__device__ __forceinline__ void sts32(uint32_t a, uint32_t v) { asm volatile("st.shared.b32 [%0], %1;" :: "r"(a), "r"(v) : "memory"); }
__device__ __forceinline__ void sts128(uint32_t a, uint32_t v0, uint32_t v1, uint32_t v2, uint32_t v3) {
  asm volatile("st.shared.v4.b32 [%0], {%1,%2,%3,%4};" :: "r"(a), "r"(v0), "r"(v1), "r"(v2), "r"(v3) : "memory"); }
__device__ __forceinline__ uint32_t pack_bf16(float lo, float hi) { uint32_t r; asm("cvt.rn.bf16x2.f32 %0, %1, %2;" : "=r"(r) : "f"(hi), "f"(lo)); return r; }
template <int ID = 0> __device__ __forceinline__ void sched_fence(uint32_t key) {
  asm volatile("{\n.reg .pred p;\nsetp.eq.u32 p, %0, %1;\nSF_LOOP:\n@p pmevent 1;\n@p bra.uni SF_LOOP;\n}" :: "r"(key), "n"(ID) : "memory");
}
template <int N> __device__ __forceinline__ void pinv(float* v) {
  #pragma unroll
  for (int i = 0; i < N; i++) asm volatile("" : "+f"(v[i]) :: "memory"); }
__device__ __forceinline__ uint32_t bmul2(uint32_t a, uint32_t b) { uint32_t r; asm("mul.rn.bf16x2 %0, %1, %2;" : "=r"(r) : "r"(a), "r"(b)); return r; }
__device__ __forceinline__ uint32_t badd2(uint32_t a, uint32_t b) { uint32_t r; asm("add.rn.bf16x2 %0, %1, %2;" : "=r"(r) : "r"(a), "r"(b)); return r; }
__device__ __forceinline__ void spin_until(const unsigned* p, unsigned target) {
  int n = 0;
  unsigned v;
  do { asm volatile("ld.relaxed.gpu.global.u32 %0, [%1];" : "=r"(v) : "l"(p) : "memory"); } while ((int)(v - target) < 0 && ++n < WAIT_BOUND);
  asm volatile("fence.acquire.gpu;" ::: "memory");
}
__device__ __forceinline__ void cluster_wait() { asm volatile("barrier.cluster.wait.aligned;" ::: "memory"); }
__device__ __forceinline__ void fence_gpu() { asm volatile("fence.release.gpu;" ::: "memory"); }
__device__ __forceinline__ void fence_async_global() { asm volatile("fence.proxy.async.global;" ::: "memory"); }
__device__ __forceinline__ void red_add(unsigned* p) { asm volatile(ELECT "red.relaxed.gpu.global.add.u32 [%0], 1;\n}" :: "l"(p) : "memory"); }
__device__ __forceinline__ float rcp_fast(float x) { float r; asm("rcp.approx.ftz.f32 %0, %1;" : "=f"(r) : "f"(x)); return r; }
__device__ __forceinline__ uint32_t mapa(uint32_t a, uint32_t rank) { uint32_t r; asm("mapa.shared::cluster.u32 %0, %1, %2;" : "=r"(r) : "r"(a), "r"(rank)); return r; }
__device__ __forceinline__ void st_async128(uint32_t a, uint32_t bar, uint32_t v0, uint32_t v1, uint32_t v2, uint32_t v3) {
  asm volatile("st.async.weak.shared::cluster.mbarrier::complete_tx::bytes.v4.b32 [%0], {%2,%3,%4,%5}, [%1];"
    :: "r"(a), "r"(bar), "r"(v0), "r"(v1), "r"(v2), "r"(v3) : "memory"); }
__device__ __forceinline__ int fresh_tid() { int t; asm volatile("mov.u32 %0, %%tid.x;" : "=r"(t)); return t; }
__device__ __forceinline__ void pace(uint32_t& t, uint32_t dt) {
  uint32_t c;
  while ((int)((c = uni((uint32_t)clock())) - t) < 0) __nanosleep(40);
  t = ((int)(c - t) > (int)dt ? c : t) + dt;
}
template <int LOG> __device__ __forceinline__ void unit_root(int a, float& c, float& s) {
  const float x = (float)((a << (32 - LOG)) >> (32 - LOG)) * (6.283185307179586f / (1 << LOG));
  c = __cosf(x); s = __sinf(x); }

struct D2 { uint64_t a, b; };
template <int TA, int TB> __device__ __forceinline__ void ss128p(float* d, uint64_t da, uint64_t db, int sd) {
  asm volatile("{\n.reg .pred p;\nsetp.ne.b32 p, %68, 0;\n"
    "wgmma.mma_async.sync.aligned.m64n128k16.f32.bf16.bf16 "
    "{%0, %1, %2, %3, %4, %5, %6, %7, %8, %9, %10, %11, %12, %13, %14, %15, "
    "%16, %17, %18, %19, %20, %21, %22, %23, %24, %25, %26, %27, %28, %29, %30, %31, "
    "%32, %33, %34, %35, %36, %37, %38, %39, %40, %41, %42, %43, %44, %45, %46, %47, "
    "%48, %49, %50, %51, %52, %53, %54, %55, %56, %57, %58, %59, %60, %61, %62, %63}, %64, %65, p, 1, 1, %66, %67;\n}\n"
    : "+f"(d[0]), "+f"(d[1]), "+f"(d[2]), "+f"(d[3]), "+f"(d[4]), "+f"(d[5]), "+f"(d[6]), "+f"(d[7]),
      "+f"(d[8]), "+f"(d[9]), "+f"(d[10]), "+f"(d[11]), "+f"(d[12]), "+f"(d[13]), "+f"(d[14]), "+f"(d[15]),
      "+f"(d[16]), "+f"(d[17]), "+f"(d[18]), "+f"(d[19]), "+f"(d[20]), "+f"(d[21]), "+f"(d[22]), "+f"(d[23]),
      "+f"(d[24]), "+f"(d[25]), "+f"(d[26]), "+f"(d[27]), "+f"(d[28]), "+f"(d[29]), "+f"(d[30]), "+f"(d[31]),
      "+f"(d[32]), "+f"(d[33]), "+f"(d[34]), "+f"(d[35]), "+f"(d[36]), "+f"(d[37]), "+f"(d[38]), "+f"(d[39]),
      "+f"(d[40]), "+f"(d[41]), "+f"(d[42]), "+f"(d[43]), "+f"(d[44]), "+f"(d[45]), "+f"(d[46]), "+f"(d[47]),
      "+f"(d[48]), "+f"(d[49]), "+f"(d[50]), "+f"(d[51]), "+f"(d[52]), "+f"(d[53]), "+f"(d[54]), "+f"(d[55]),
      "+f"(d[56]), "+f"(d[57]), "+f"(d[58]), "+f"(d[59]), "+f"(d[60]), "+f"(d[61]), "+f"(d[62]), "+f"(d[63])
    : "l"(da), "l"(db), "n"(TA), "n"(TB), "r"(sd));
}
template <int TA, int TB> __device__ __forceinline__ void ss128a(float* d, uint64_t da, uint64_t db) {
  asm volatile("{\n.reg .pred p;\nsetp.eq.b32 p, 0, 0;\n"
    "wgmma.mma_async.sync.aligned.m64n128k16.f32.bf16.bf16 "
    "{%0, %1, %2, %3, %4, %5, %6, %7, %8, %9, %10, %11, %12, %13, %14, %15, "
    "%16, %17, %18, %19, %20, %21, %22, %23, %24, %25, %26, %27, %28, %29, %30, %31, "
    "%32, %33, %34, %35, %36, %37, %38, %39, %40, %41, %42, %43, %44, %45, %46, %47, "
    "%48, %49, %50, %51, %52, %53, %54, %55, %56, %57, %58, %59, %60, %61, %62, %63}, %64, %65, p, 1, 1, %66, %67;\n}\n"
    : "+f"(d[0]), "+f"(d[1]), "+f"(d[2]), "+f"(d[3]), "+f"(d[4]), "+f"(d[5]), "+f"(d[6]), "+f"(d[7]),
      "+f"(d[8]), "+f"(d[9]), "+f"(d[10]), "+f"(d[11]), "+f"(d[12]), "+f"(d[13]), "+f"(d[14]), "+f"(d[15]),
      "+f"(d[16]), "+f"(d[17]), "+f"(d[18]), "+f"(d[19]), "+f"(d[20]), "+f"(d[21]), "+f"(d[22]), "+f"(d[23]),
      "+f"(d[24]), "+f"(d[25]), "+f"(d[26]), "+f"(d[27]), "+f"(d[28]), "+f"(d[29]), "+f"(d[30]), "+f"(d[31]),
      "+f"(d[32]), "+f"(d[33]), "+f"(d[34]), "+f"(d[35]), "+f"(d[36]), "+f"(d[37]), "+f"(d[38]), "+f"(d[39]),
      "+f"(d[40]), "+f"(d[41]), "+f"(d[42]), "+f"(d[43]), "+f"(d[44]), "+f"(d[45]), "+f"(d[46]), "+f"(d[47]),
      "+f"(d[48]), "+f"(d[49]), "+f"(d[50]), "+f"(d[51]), "+f"(d[52]), "+f"(d[53]), "+f"(d[54]), "+f"(d[55]),
      "+f"(d[56]), "+f"(d[57]), "+f"(d[58]), "+f"(d[59]), "+f"(d[60]), "+f"(d[61]), "+f"(d[62]), "+f"(d[63])
    : "l"(da), "l"(db), "n"(TA), "n"(TB));
}
template <int TA, int TB> __device__ __forceinline__ void ss128z(float* d, uint64_t da, uint64_t db) {
  asm volatile("{\n.reg .pred p;\nsetp.ne.b32 p, 0, 0;\n"
    "wgmma.mma_async.sync.aligned.m64n128k16.f32.bf16.bf16 "
    "{%0, %1, %2, %3, %4, %5, %6, %7, %8, %9, %10, %11, %12, %13, %14, %15, "
    "%16, %17, %18, %19, %20, %21, %22, %23, %24, %25, %26, %27, %28, %29, %30, %31, "
    "%32, %33, %34, %35, %36, %37, %38, %39, %40, %41, %42, %43, %44, %45, %46, %47, "
    "%48, %49, %50, %51, %52, %53, %54, %55, %56, %57, %58, %59, %60, %61, %62, %63}, %64, %65, p, 1, 1, %66, %67;\n}\n"
    : "=f"(d[0]), "=f"(d[1]), "=f"(d[2]), "=f"(d[3]), "=f"(d[4]), "=f"(d[5]), "=f"(d[6]), "=f"(d[7]),
      "=f"(d[8]), "=f"(d[9]), "=f"(d[10]), "=f"(d[11]), "=f"(d[12]), "=f"(d[13]), "=f"(d[14]), "=f"(d[15]),
      "=f"(d[16]), "=f"(d[17]), "=f"(d[18]), "=f"(d[19]), "=f"(d[20]), "=f"(d[21]), "=f"(d[22]), "=f"(d[23]),
      "=f"(d[24]), "=f"(d[25]), "=f"(d[26]), "=f"(d[27]), "=f"(d[28]), "=f"(d[29]), "=f"(d[30]), "=f"(d[31]),
      "=f"(d[32]), "=f"(d[33]), "=f"(d[34]), "=f"(d[35]), "=f"(d[36]), "=f"(d[37]), "=f"(d[38]), "=f"(d[39]),
      "=f"(d[40]), "=f"(d[41]), "=f"(d[42]), "=f"(d[43]), "=f"(d[44]), "=f"(d[45]), "=f"(d[46]), "=f"(d[47]),
      "=f"(d[48]), "=f"(d[49]), "=f"(d[50]), "=f"(d[51]), "=f"(d[52]), "=f"(d[53]), "=f"(d[54]), "=f"(d[55]),
      "=f"(d[56]), "=f"(d[57]), "=f"(d[58]), "=f"(d[59]), "=f"(d[60]), "=f"(d[61]), "=f"(d[62]), "=f"(d[63])
    : "l"(da), "l"(db), "n"(TA), "n"(TB));
}
template <int TA, int TB> __device__ __forceinline__ void ss64a(float* d, uint64_t da, uint64_t db) {
  asm volatile("{\n.reg .pred p;\nsetp.eq.b32 p, 0, 0;\n"
    "wgmma.mma_async.sync.aligned.m64n64k16.f32.bf16.bf16 "
    "{%0, %1, %2, %3, %4, %5, %6, %7, %8, %9, %10, %11, %12, %13, %14, %15, "
    "%16, %17, %18, %19, %20, %21, %22, %23, %24, %25, %26, %27, %28, %29, %30, %31}, %32, %33, p, 1, 1, %34, %35;\n}\n"
    : "+f"(d[0]), "+f"(d[1]), "+f"(d[2]), "+f"(d[3]), "+f"(d[4]), "+f"(d[5]), "+f"(d[6]), "+f"(d[7]),
      "+f"(d[8]), "+f"(d[9]), "+f"(d[10]), "+f"(d[11]), "+f"(d[12]), "+f"(d[13]), "+f"(d[14]), "+f"(d[15]),
      "+f"(d[16]), "+f"(d[17]), "+f"(d[18]), "+f"(d[19]), "+f"(d[20]), "+f"(d[21]), "+f"(d[22]), "+f"(d[23]),
      "+f"(d[24]), "+f"(d[25]), "+f"(d[26]), "+f"(d[27]), "+f"(d[28]), "+f"(d[29]), "+f"(d[30]), "+f"(d[31])
    : "l"(da), "l"(db), "n"(TA), "n"(TB));
}
template <int TA, int TB> __device__ __forceinline__ void ss64z(float* d, uint64_t da, uint64_t db) {
  asm volatile("{\n.reg .pred p;\nsetp.ne.b32 p, 0, 0;\n"
    "wgmma.mma_async.sync.aligned.m64n64k16.f32.bf16.bf16 "
    "{%0, %1, %2, %3, %4, %5, %6, %7, %8, %9, %10, %11, %12, %13, %14, %15, "
    "%16, %17, %18, %19, %20, %21, %22, %23, %24, %25, %26, %27, %28, %29, %30, %31}, %32, %33, p, 1, 1, %34, %35;\n}\n"
    : "=f"(d[0]), "=f"(d[1]), "=f"(d[2]), "=f"(d[3]), "=f"(d[4]), "=f"(d[5]), "=f"(d[6]), "=f"(d[7]),
      "=f"(d[8]), "=f"(d[9]), "=f"(d[10]), "=f"(d[11]), "=f"(d[12]), "=f"(d[13]), "=f"(d[14]), "=f"(d[15]),
      "=f"(d[16]), "=f"(d[17]), "=f"(d[18]), "=f"(d[19]), "=f"(d[20]), "=f"(d[21]), "=f"(d[22]), "=f"(d[23]),
      "=f"(d[24]), "=f"(d[25]), "=f"(d[26]), "=f"(d[27]), "=f"(d[28]), "=f"(d[29]), "=f"(d[30]), "=f"(d[31])
    : "l"(da), "l"(db), "n"(TA), "n"(TB));
}
__device__ __forceinline__ void ss64x4(float* d, const D2* c, int on) {
  asm volatile("{\n.reg .pred p, z, c;\nsetp.eq.b32 p, 0, 0;\nsetp.ne.b32 z, 0, 0;\nsetp.eq.b32 c, %40, 0;\n"
    "wgmma.mma_async.sync.aligned.m64n64k16.f32.bf16.bf16 "
    "{%0, %1, %2, %3, %4, %5, %6, %7, %8, %9, %10, %11, %12, %13, %14, %15, "
    "%16, %17, %18, %19, %20, %21, %22, %23, %24, %25, %26, %27, %28, %29, %30, %31}, %32, %33, z, 1, 1, 0, 1;\n"
    "wgmma.commit_group.sync.aligned;\n@c bra.uni X4_DONE;\n"
    "wgmma.mma_async.sync.aligned.m64n64k16.f32.bf16.bf16 "
    "{%0, %1, %2, %3, %4, %5, %6, %7, %8, %9, %10, %11, %12, %13, %14, %15, "
    "%16, %17, %18, %19, %20, %21, %22, %23, %24, %25, %26, %27, %28, %29, %30, %31}, %34, %35, p, 1, 1, 0, 1;\n"
    "wgmma.mma_async.sync.aligned.m64n64k16.f32.bf16.bf16 "
    "{%0, %1, %2, %3, %4, %5, %6, %7, %8, %9, %10, %11, %12, %13, %14, %15, "
    "%16, %17, %18, %19, %20, %21, %22, %23, %24, %25, %26, %27, %28, %29, %30, %31}, %36, %37, p, 1, 1, 0, 1;\n"
    "wgmma.mma_async.sync.aligned.m64n64k16.f32.bf16.bf16 "
    "{%0, %1, %2, %3, %4, %5, %6, %7, %8, %9, %10, %11, %12, %13, %14, %15, "
    "%16, %17, %18, %19, %20, %21, %22, %23, %24, %25, %26, %27, %28, %29, %30, %31}, %38, %39, p, 1, 1, 0, 1;\n"
    "wgmma.commit_group.sync.aligned;\nX4_DONE:\n}\n"
    : "=f"(d[0]), "=f"(d[1]), "=f"(d[2]), "=f"(d[3]), "=f"(d[4]), "=f"(d[5]), "=f"(d[6]), "=f"(d[7]),
      "=f"(d[8]), "=f"(d[9]), "=f"(d[10]), "=f"(d[11]), "=f"(d[12]), "=f"(d[13]), "=f"(d[14]), "=f"(d[15]),
      "=f"(d[16]), "=f"(d[17]), "=f"(d[18]), "=f"(d[19]), "=f"(d[20]), "=f"(d[21]), "=f"(d[22]), "=f"(d[23]),
      "=f"(d[24]), "=f"(d[25]), "=f"(d[26]), "=f"(d[27]), "=f"(d[28]), "=f"(d[29]), "=f"(d[30]), "=f"(d[31])
    : "l"(c[0].a), "l"(c[0].b), "l"(c[1].a), "l"(c[1].b), "l"(c[2].a), "l"(c[2].b), "l"(c[3].a), "l"(c[3].b), "r"(on));
}
template <int TB> __device__ __forceinline__ void rs32a(float* d, const uint32_t* a, uint64_t db) {
  asm volatile("{\n.reg .pred p;\nsetp.eq.b32 p, 0, 0;\n"
    "wgmma.mma_async.sync.aligned.m64n32k16.f32.bf16.bf16 "
    "{%0, %1, %2, %3, %4, %5, %6, %7, %8, %9, %10, %11, %12, %13, %14, %15}, {%16, %17, %18, %19}, %20, p, 1, 1, %21;\n}\n"
    : "+f"(d[0]), "+f"(d[1]), "+f"(d[2]), "+f"(d[3]), "+f"(d[4]), "+f"(d[5]), "+f"(d[6]), "+f"(d[7]),
      "+f"(d[8]), "+f"(d[9]), "+f"(d[10]), "+f"(d[11]), "+f"(d[12]), "+f"(d[13]), "+f"(d[14]), "+f"(d[15])
    : "r"(a[0]), "r"(a[1]), "r"(a[2]), "r"(a[3]), "l"(db), "n"(TB));
}
template <int TB> __device__ __forceinline__ void rs32z(float* d, const uint32_t* a, uint64_t db) {
  asm volatile("{\n.reg .pred p;\nsetp.ne.b32 p, 0, 0;\n"
    "wgmma.mma_async.sync.aligned.m64n32k16.f32.bf16.bf16 "
    "{%0, %1, %2, %3, %4, %5, %6, %7, %8, %9, %10, %11, %12, %13, %14, %15}, {%16, %17, %18, %19}, %20, p, 1, 1, %21;\n}\n"
    : "=&f"(d[0]), "=&f"(d[1]), "=&f"(d[2]), "=&f"(d[3]), "=&f"(d[4]), "=&f"(d[5]), "=&f"(d[6]), "=&f"(d[7]),
      "=&f"(d[8]), "=&f"(d[9]), "=&f"(d[10]), "=&f"(d[11]), "=&f"(d[12]), "=&f"(d[13]), "=&f"(d[14]), "=&f"(d[15])
    : "r"(a[0]), "r"(a[1]), "r"(a[2]), "r"(a[3]), "l"(db), "n"(TB));
}
template <int TB> __device__ __forceinline__ void rs40a(float* d, const uint32_t* a, uint64_t db) {
  asm volatile("{\n.reg .pred p;\nsetp.eq.b32 p, 0, 0;\n"
    "wgmma.mma_async.sync.aligned.m64n40k16.f32.bf16.bf16 "
    "{%0, %1, %2, %3, %4, %5, %6, %7, %8, %9, %10, %11, %12, %13, %14, %15, "
    "%16, %17, %18, %19}, {%20, %21, %22, %23}, %24, p, 1, 1, %25;\n}\n"
    : "+f"(d[0]), "+f"(d[1]), "+f"(d[2]), "+f"(d[3]), "+f"(d[4]), "+f"(d[5]), "+f"(d[6]), "+f"(d[7]),
      "+f"(d[8]), "+f"(d[9]), "+f"(d[10]), "+f"(d[11]), "+f"(d[12]), "+f"(d[13]), "+f"(d[14]), "+f"(d[15]),
      "+f"(d[16]), "+f"(d[17]), "+f"(d[18]), "+f"(d[19])
    : "r"(a[0]), "r"(a[1]), "r"(a[2]), "r"(a[3]), "l"(db), "n"(TB));
}
template <int TB> __device__ __forceinline__ void rs40z(float* d, const uint32_t* a, uint64_t db) {
  asm volatile("{\n.reg .pred p;\nsetp.ne.b32 p, 0, 0;\n"
    "wgmma.mma_async.sync.aligned.m64n40k16.f32.bf16.bf16 "
    "{%0, %1, %2, %3, %4, %5, %6, %7, %8, %9, %10, %11, %12, %13, %14, %15, "
    "%16, %17, %18, %19}, {%20, %21, %22, %23}, %24, p, 1, 1, %25;\n}\n"
    : "=&f"(d[0]), "=&f"(d[1]), "=&f"(d[2]), "=&f"(d[3]), "=&f"(d[4]), "=&f"(d[5]), "=&f"(d[6]), "=&f"(d[7]),
      "=&f"(d[8]), "=&f"(d[9]), "=&f"(d[10]), "=&f"(d[11]), "=&f"(d[12]), "=&f"(d[13]), "=&f"(d[14]), "=&f"(d[15]),
      "=&f"(d[16]), "=&f"(d[17]), "=&f"(d[18]), "=&f"(d[19])
    : "r"(a[0]), "r"(a[1]), "r"(a[2]), "r"(a[3]), "l"(db), "n"(TB));
}
template <int TB> __device__ __forceinline__ void rs72a(float* d, const uint32_t* a, uint64_t db) {
  asm volatile("{\n.reg .pred p;\nsetp.eq.b32 p, 0, 0;\n"
    "wgmma.mma_async.sync.aligned.m64n72k16.f32.bf16.bf16 "
    "{%0, %1, %2, %3, %4, %5, %6, %7, %8, %9, %10, %11, %12, %13, %14, %15, "
    "%16, %17, %18, %19, %20, %21, %22, %23, %24, %25, %26, %27, %28, %29, %30, %31, "
    "%32, %33, %34, %35}, {%36, %37, %38, %39}, %40, p, 1, 1, %41;\n}\n"
    : "+f"(d[0]), "+f"(d[1]), "+f"(d[2]), "+f"(d[3]), "+f"(d[4]), "+f"(d[5]), "+f"(d[6]), "+f"(d[7]),
      "+f"(d[8]), "+f"(d[9]), "+f"(d[10]), "+f"(d[11]), "+f"(d[12]), "+f"(d[13]), "+f"(d[14]), "+f"(d[15]),
      "+f"(d[16]), "+f"(d[17]), "+f"(d[18]), "+f"(d[19]), "+f"(d[20]), "+f"(d[21]), "+f"(d[22]), "+f"(d[23]),
      "+f"(d[24]), "+f"(d[25]), "+f"(d[26]), "+f"(d[27]), "+f"(d[28]), "+f"(d[29]), "+f"(d[30]), "+f"(d[31]),
      "+f"(d[32]), "+f"(d[33]), "+f"(d[34]), "+f"(d[35])
    : "r"(a[0]), "r"(a[1]), "r"(a[2]), "r"(a[3]), "l"(db), "n"(TB));
}
template <int TB> __device__ __forceinline__ void rs72z(float* d, const uint32_t* a, uint64_t db) {
  asm volatile("{\n.reg .pred p;\nsetp.ne.b32 p, 0, 0;\n"
    "wgmma.mma_async.sync.aligned.m64n72k16.f32.bf16.bf16 "
    "{%0, %1, %2, %3, %4, %5, %6, %7, %8, %9, %10, %11, %12, %13, %14, %15, "
    "%16, %17, %18, %19, %20, %21, %22, %23, %24, %25, %26, %27, %28, %29, %30, %31, "
    "%32, %33, %34, %35}, {%36, %37, %38, %39}, %40, p, 1, 1, %41;\n}\n"
    : "=&f"(d[0]), "=&f"(d[1]), "=&f"(d[2]), "=&f"(d[3]), "=&f"(d[4]), "=&f"(d[5]), "=&f"(d[6]), "=&f"(d[7]),
      "=&f"(d[8]), "=&f"(d[9]), "=&f"(d[10]), "=&f"(d[11]), "=&f"(d[12]), "=&f"(d[13]), "=&f"(d[14]), "=&f"(d[15]),
      "=&f"(d[16]), "=&f"(d[17]), "=&f"(d[18]), "=&f"(d[19]), "=&f"(d[20]), "=&f"(d[21]), "=&f"(d[22]), "=&f"(d[23]),
      "=&f"(d[24]), "=&f"(d[25]), "=&f"(d[26]), "=&f"(d[27]), "=&f"(d[28]), "=&f"(d[29]), "=&f"(d[30]), "=&f"(d[31]),
      "=&f"(d[32]), "=&f"(d[33]), "=&f"(d[34]), "=&f"(d[35])
    : "r"(a[0]), "r"(a[1]), "r"(a[2]), "r"(a[3]), "l"(db), "n"(TB));
}
template <int TB> __device__ __forceinline__ void rs128a(float* d, const uint32_t* a, uint64_t db) {
  asm volatile("{\n.reg .pred p;\nsetp.eq.b32 p, 0, 0;\n"
    "wgmma.mma_async.sync.aligned.m64n128k16.f32.bf16.bf16 "
    "{%0, %1, %2, %3, %4, %5, %6, %7, %8, %9, %10, %11, %12, %13, %14, %15, "
    "%16, %17, %18, %19, %20, %21, %22, %23, %24, %25, %26, %27, %28, %29, %30, %31, "
    "%32, %33, %34, %35, %36, %37, %38, %39, %40, %41, %42, %43, %44, %45, %46, %47, "
    "%48, %49, %50, %51, %52, %53, %54, %55, %56, %57, %58, %59, %60, %61, %62, %63}, {%64, %65, %66, %67}, %68, p, 1, 1, %69;\n}\n"
    : "+f"(d[0]), "+f"(d[1]), "+f"(d[2]), "+f"(d[3]), "+f"(d[4]), "+f"(d[5]), "+f"(d[6]), "+f"(d[7]),
      "+f"(d[8]), "+f"(d[9]), "+f"(d[10]), "+f"(d[11]), "+f"(d[12]), "+f"(d[13]), "+f"(d[14]), "+f"(d[15]),
      "+f"(d[16]), "+f"(d[17]), "+f"(d[18]), "+f"(d[19]), "+f"(d[20]), "+f"(d[21]), "+f"(d[22]), "+f"(d[23]),
      "+f"(d[24]), "+f"(d[25]), "+f"(d[26]), "+f"(d[27]), "+f"(d[28]), "+f"(d[29]), "+f"(d[30]), "+f"(d[31]),
      "+f"(d[32]), "+f"(d[33]), "+f"(d[34]), "+f"(d[35]), "+f"(d[36]), "+f"(d[37]), "+f"(d[38]), "+f"(d[39]),
      "+f"(d[40]), "+f"(d[41]), "+f"(d[42]), "+f"(d[43]), "+f"(d[44]), "+f"(d[45]), "+f"(d[46]), "+f"(d[47]),
      "+f"(d[48]), "+f"(d[49]), "+f"(d[50]), "+f"(d[51]), "+f"(d[52]), "+f"(d[53]), "+f"(d[54]), "+f"(d[55]),
      "+f"(d[56]), "+f"(d[57]), "+f"(d[58]), "+f"(d[59]), "+f"(d[60]), "+f"(d[61]), "+f"(d[62]), "+f"(d[63])
    : "r"(a[0]), "r"(a[1]), "r"(a[2]), "r"(a[3]), "l"(db), "n"(TB));
}
template <int TB> __device__ __forceinline__ void rs128z(float* d, const uint32_t* a, uint64_t db) {
  asm volatile("{\n.reg .pred p;\nsetp.ne.b32 p, 0, 0;\n"
    "wgmma.mma_async.sync.aligned.m64n128k16.f32.bf16.bf16 "
    "{%0, %1, %2, %3, %4, %5, %6, %7, %8, %9, %10, %11, %12, %13, %14, %15, "
    "%16, %17, %18, %19, %20, %21, %22, %23, %24, %25, %26, %27, %28, %29, %30, %31, "
    "%32, %33, %34, %35, %36, %37, %38, %39, %40, %41, %42, %43, %44, %45, %46, %47, "
    "%48, %49, %50, %51, %52, %53, %54, %55, %56, %57, %58, %59, %60, %61, %62, %63}, {%64, %65, %66, %67}, %68, p, 1, 1, %69;\n}\n"
    : "=&f"(d[0]), "=&f"(d[1]), "=&f"(d[2]), "=&f"(d[3]), "=&f"(d[4]), "=&f"(d[5]), "=&f"(d[6]), "=&f"(d[7]),
      "=&f"(d[8]), "=&f"(d[9]), "=&f"(d[10]), "=&f"(d[11]), "=&f"(d[12]), "=&f"(d[13]), "=&f"(d[14]), "=&f"(d[15]),
      "=&f"(d[16]), "=&f"(d[17]), "=&f"(d[18]), "=&f"(d[19]), "=&f"(d[20]), "=&f"(d[21]), "=&f"(d[22]), "=&f"(d[23]),
      "=&f"(d[24]), "=&f"(d[25]), "=&f"(d[26]), "=&f"(d[27]), "=&f"(d[28]), "=&f"(d[29]), "=&f"(d[30]), "=&f"(d[31]),
      "=&f"(d[32]), "=&f"(d[33]), "=&f"(d[34]), "=&f"(d[35]), "=&f"(d[36]), "=&f"(d[37]), "=&f"(d[38]), "=&f"(d[39]),
      "=&f"(d[40]), "=&f"(d[41]), "=&f"(d[42]), "=&f"(d[43]), "=&f"(d[44]), "=&f"(d[45]), "=&f"(d[46]), "=&f"(d[47]),
      "=&f"(d[48]), "=&f"(d[49]), "=&f"(d[50]), "=&f"(d[51]), "=&f"(d[52]), "=&f"(d[53]), "=&f"(d[54]), "=&f"(d[55]),
      "=&f"(d[56]), "=&f"(d[57]), "=&f"(d[58]), "=&f"(d[59]), "=&f"(d[60]), "=&f"(d[61]), "=&f"(d[62]), "=&f"(d[63])
    : "r"(a[0]), "r"(a[1]), "r"(a[2]), "r"(a[3]), "l"(db), "n"(TB));
}

template <int V> struct IC { static constexpr int value = V; };
struct PfType { const char* base; uint32_t gl, gh, sp, sr, su, l4, l2; };
struct Params {
  const __nv_bfloat16 *x, *w;
  unsigned* cnt;
  uint32_t one;
  const __nv_bfloat16 *shift, *ssmD;
  __nv_bfloat16* out;
  uint4* o; float* kv;
  const char *k, *v;
  PfType pt[6];
  uint8_t pf[32];
  uint64_t cd[18];
};

struct Tmp { float t0, t1; };
__device__ __forceinline__ void mul2(Tmp& t, float a0, float b0, float a1, float b1) {
  asm volatile("@p_one mul.rn.f32 %0, %2, %3;\n@p_one mul.rn.f32 %1, %4, %5;" : "+f"(t.t0), "+f"(t.t1) : "f"(a0), "f"(b0), "f"(a1), "f"(b1)); }
__device__ __forceinline__ void add2(Tmp& t, float a0, float b0, float a1, float b1) {
  asm volatile("@p_one add.rn.f32 %0, %2, %3;\n@p_one add.rn.f32 %1, %4, %5;" : "+f"(t.t0), "+f"(t.t1) : "f"(a0), "f"(b0), "f"(a1), "f"(b1)); }
__device__ __forceinline__ void fma2(Tmp& t, float a0, float b0, float a1, float b1) { t.t0 = fmaf(a0, b0, t.t0); t.t1 = fmaf(a1, b1, t.t1); }
struct Tw { uint32_t c[2], s[2], ns[2]; };
__device__ __forceinline__ void rot(uint32_t& u, uint32_t& v, const Tw& w, int k) {
  asm("{\n.reg .b32 a, b;\nmul.rn.bf16x2 a, %0, %2;\nmul.rn.bf16x2 b, %0, %3;\nfma.rn.bf16x2 %0, %1, %4, a;\nfma.rn.bf16x2 %1, %1, %2, b;\n}"
    : "+r"(u), "+r"(v) : "r"(w.c[k]), "r"(w.s[k]), "r"(w.ns[k]));
}
__device__ __forceinline__ void pack_fwd(uint32_t (&f)[2][2][4], const float* a) {
  #pragma unroll
  for (int j = 0; j < 16; j++) f[j >> 3][(j >> 1) & 1][2 * (j & 1) + ((j >> 2) & 1)] = fresh(pack_bf16(a[2 * j], a[2 * j + 1]));
}
__device__ __forceinline__ void rot_fwd(uint32_t (&f)[2][2][4], const Tw& w) {
  #pragma unroll
  for (int j = 0; j < 8; j++) rot(f[j >> 2][j & 1][(j >> 1) & 1], f[j >> 2][j & 1][2 + ((j >> 1) & 1)], w, j & 1);
}
__device__ __forceinline__ void add_skip(float* h, float d) {
  asm volatile("add.rn.f32 %0, %0, %4;\nadd.rn.f32 %1, %1, %4;\nadd.rn.f32 %2, %2, %4;\nadd.rn.f32 %3, %3, %4;" : "+f"(h[0]), "+f"(h[1]), "+f"(h[4]), "+f"(h[5]) : "f"(d)); }
__device__ __forceinline__ void dft16h(float* d, const uint32_t (&f)[2][4], const D2& dF) { rs32z<0>(d, f[0], dF.a); rs32a<0>(d, f[1], dF.b); }
#define SP(h, p, im, k) (((p) >> 1 ? hi : lo) + 16 * (h) + 8 * (im) + 4 * (k) + 2 * ((p) & 1))
template <int PH, int G0 = 0, int G1 = 8> __device__ __forceinline__ void prod(Tmp& t, uint32_t (&f)[2][4], const float* lo, const float* hi) {
  #pragma unroll
  for (int g = G0; g < G1; g++) {
    const int p = 2 * PH + 1 - (g >> 2), k = (g >> 1) & 1, im = g & 1;
    #pragma unroll
    for (int q = 0; q <= p; q++) {
      const float *hr = SP(1, q, 0, k), *hi_ = SP(1, q, 1, k), *xa = SP(0, p - q, im, k), *xb = SP(0, p - q, 1 - im, k);
      if (q == 0) mul2(t, hr[0], xa[0], hr[1], xa[1]); else fma2(t, hr[0], xa[0], hr[1], xa[1]);
      if (im) fma2(t, hi_[0], xb[0], hi_[1], xb[1]); else fma2(t, -hi_[0], xb[0], -hi_[1], xb[1]);
    }
    f[k][2 * (1 - im) + (p & 1)] = pack_bf16(t.t0, t.t1);
  }
}

constexpr uint64_t dA = cdesc(A_OFF, 2048, 128, 0), dAi = cdesc(A_OFF, 128, 1024, 0), dF0 = cdesc(F_OFF, 128, 512, 0),
                   dT0 = cdesc(T_OFF, 1024, 128, 0), dH0 = cdesc(H_OFF, 1024, 256, 3), dX0 = cdesc(X_OFF, 1024, 128, 0);
#define CONV_DESC dF0, dF0 + 16, dAi, dT0, dAi + 16, dT0 + 128, dAi + 32, dT0 + 256, dAi + 48, dT0 + 384, dA, dH0, dA + 256, dH0 + 32, dA, dX0, dA + 256, dX0 + 128
__device__ __forceinline__ void make_tw(Tw& tw, int ht) {
  #pragma unroll
  for (int i = 0; i < 2; i++) {
    float c0, s0, c1, s1;
    unit_root<11>((4 * (ht >> 2) + 1) * (i * 8 + 2 * (ht & 3)), c0, s0);
    unit_root<11>((4 * (ht >> 2) + 1) * (i * 8 + 2 * (ht & 3) + 1), c1, s1);
    tw.c[i] = pack_bf16(c0, c1); tw.s[i] = pack_bf16(s0, s1); tw.ns[i] = fresh(tw.s[i] ^ 0x80008000u);
  }
}
template <bool COMMIT = true> __device__ __forceinline__ void dft32_h(float* r, const D2* d) {
  ss64z<1, 1>(r, d[0].a, d[0].b); ss64a<1, 1>(r, d[1].a, d[1].b);
  if (COMMIT) wg_commit();
}
template <bool COMMIT = true> __device__ __forceinline__ void dft32_x(float* r, D2* d) {
  ss64z<1, 0>(r, d[0].a, d[0].b); ss64a<1, 0>(r, d[1].a, d[1].b);
  if (COMMIT) wg_commit();
  d[0].b = dofs(d[0].b, XS); d[1].b = dofs(d[1].b, XS);
}
__device__ __forceinline__ void pack_inv(uint32_t (&u)[2][2][4], const float* r) {
  #pragma unroll
  for (int j = 0; j < 16; j++) u[j >> 3][(j >> 2) & 1][2 * (j & 1) + ((j >> 1) & 1)] = fresh(pack_bf16(r[2 * j], r[2 * j + 1]));
}
__device__ __forceinline__ void rot_inv(uint32_t (&u)[2][2][4], const Tw& tw, uint32_t ta) {
  #pragma unroll
  for (int m = 0; m < 2; m++) {
    #pragma unroll
    for (int j = 0; j < 4; j++) rot(u[m][0][j], u[m][1][j], tw, j & 1);
    stsm4(ta + m * 512, u[m][1][0], u[m][1][1], u[m][1][2], u[m][1][3]);
    stsm4(ta + 1024 + m * 512, u[m][0][0], u[m][0][1], u[m][0][2], u[m][0][3]);
  }
}
__device__ __forceinline__ void idft32(float* r, const D2* d) {
  wg_fence();
  ss64z<0, 1>(r, d[0].a, d[0].b);
  #pragma unroll
  for (int j = 1; j < 4; j++) ss64a<0, 1>(r, d[j].a, d[j].b);
  wg_commit();
}
__device__ __forceinline__ void finish(Tmp& t, const float* r, int ch, int ht, int rank, uint32_t y0, uint32_t y1) {
  const uint32_t ya = X_OFF + ch * XS + (ch & 1) * 16, yb = BAR_OFF + (B_YR + ch) * 8;
  uint32_t y[8];
  #pragma unroll
  for (int j = 0; j < 8; j++) {
    if (j >= 2) add2(t, r[4 * j], r[4 * j - 6], r[4 * j + 1], r[4 * j - 5]);
    y[j] = j < 2 ? pack_bf16(r[4 * j], r[4 * j + 1]) : pack_bf16(t.t0, t.t1);
  }
  st_async128(y0 + ya + (ht ^ (rank * 4)) * 16 + rank * (YX - XS), y0 + yb, y[0], y[1], y[2], y[3]);
  st_async128(y1 + ya + (ht ^ (rank * 4) ^ 4) * 16 + (rank ^ 1) * (YX - XS), y1 + yb, y[4], y[5], y[6], y[7]);
}

struct Team { uint32_t bars, rel, wofs, lead; };
struct Nop { __device__ __forceinline__ void operator()() const {} };
template <bool M, class F> __device__ __forceinline__ void mid_wait(F f) { if (M) wg_commit(); f(); if (M) { wg_wait<0>(); wg_fence(); } }
template <int J, bool M = false, class F = Nop> __device__ __forceinline__ void kv_issue(float* aK, float* aV, uint32_t xo, int sd, F f = F()) {
  constexpr uint64_t dw = cdesc(W_OFF + J * 8192, 8192, 1024, 1);
  const uint64_t dx = dofs(cdesc((J & 1) * 64, 16, 1024, 1), xo);
  wg_fence();
  ss128p<1, 0>(aV, dw + (4096 >> 4), dx, sd);
  ss128p<1, 0>(aK, dw, dx, sd);
  mid_wait<M>(f);
  ss128a<1, 0>(aV, dw + (6144 >> 4), dofs(dx, 32));
  ss128a<1, 0>(aK, dw + (2048 >> 4), dofs(dx, 32));
  wg_commit();
}
template <int O, int J, int H> __device__ __forceinline__ void g2_half(float* acc, const Team& c) {
  constexpr uint64_t db = cdesc(J * SLOT + 16384 + H * 4096, 8192, 1024, 1);
  const uint64_t da = dofs(O ? cdesc(J * SLOT + H * 4096, 16, 512, 2) : cdesc(J * SLOT + H * 64, 16, 1024, 1), c.wofs);
  wg_fence();
  ss128a<0, 1>(acc, da, db);
  ss128a<0, 1>(acc, dofs(da, 32), db + (2048 >> 4));
  wg_commit();
}
template <int O, int J, bool M = false, bool FIRST = false, class F = Nop> __device__ __forceinline__ void g2_issue(float* acc, const Team& c, F f = F()) {
  constexpr uint64_t db = cdesc(J * SLOT + 16384, 8192, 1024, 1);
  const uint64_t da = dofs(O ? cdesc(J * SLOT, 16, 512, 2) : cdesc(J * SLOT, 16, 1024, 1), c.wofs);
  wg_fence();
  if (FIRST) ss128z<0, 1>(acc, da, db); else ss128a<0, 1>(acc, da, db);
  ss128a<0, 1>(acc, dofs(da, 32), db + (2048 >> 4));
  mid_wait<M>(f);
  ss128a<0, 1>(acc, dofs(da, O ? 4096 : 64), db + (4096 >> 4));
  ss128a<0, 1>(acc, dofs(da, O ? 4128 : 96), db + (6144 >> 4));
  wg_commit();
}
template <bool DEEP, bool AB = false, class F>
__device__ __forceinline__ void ring_step(const Team& c, int fb, uint32_t ph, int eb, uint32_t rel, F issue, uint32_t ab = 0, uint32_t aph = 0) {
  uint32_t ok = mbar_try(c.bars + fb * 8, ph);
  if (AB) ok &= mbar_try(ab, aph);
  if (!ok) {
    wg_wait<0>();
    arrive_at(c.rel + eb * 8, rel);
    rel = 0;
    mbar_wait(c.bars + fb * 8, ph);
    if (AB) mbar_wait(ab, aph);
  }
  if constexpr (!DEEP) {
    wg_wait<0>();
    issue([&]() { arrive_at(c.rel + eb * 8, rel); });
  } else {
    issue();
    wg_wait<1>(); arrive_at(c.rel + eb * 8, rel);
  }
}
template <int N, int I = 0, class R> __device__ __forceinline__ void tail_release(R rel) {
  if constexpr (I <= N) { wg_wait<N - I>(); rel(I - 1); tail_release<N, I + 1>(rel); }
}
template <int N, class F, class R> __device__ __forceinline__ void skew_tail(const Team& c, int ph, F issue, R rel) {
  if (c.wofs) { wg_wait<0>(); rel(-1); mbar_wait(c.bars + B_SK * 8, ph); }
  issue();
  arrive_at(c.bars + B_SK * 8, fresh_tid() == 0);
  tail_release<N>([&](int i) { if (i >= 0 || !c.wofs) rel(i); });
}
__device__ __forceinline__ void phi_a(float* a, uint32_t* f) {
  #pragma unroll
  for (int i = 0; i < 8; i++) {
    asm("cvt.rn.relu.bf16x2.f32 %0, %1, %2;" : "=r"(f[i]) : "f"(a[2 * i + 1]), "f"(a[2 * i]));
    asm("ex2.approx.ftz.f32 %0, %1;" : "=f"(a[2 * i]) : "f"(a[2 * i] * 1.4426950408889634f));
    asm("ex2.approx.ftz.f32 %0, %1;" : "=f"(a[2 * i + 1]) : "f"(a[2 * i + 1] * 1.4426950408889634f));
  }
  pinv<16>(a);
}
__device__ __forceinline__ void phi1_a(float* a) {
  #pragma unroll
  for (int i = 0; i < 16; i++)
    asm("{\n.reg .pred p;\n.reg .f32 u;\nfma.rn.f32 u, %0, 0f3FB8AA3B, 0fBFB8AA3B;\nsetp.le.f32 p, %0, 0f3F800000;\n@p ex2.approx.ftz.f32 %0, u;\n}" : "+f"(a[i]));
  pinv<16>(a);
}
__device__ __forceinline__ void phi1_b(const float* a, uint32_t* f) {
  #pragma unroll
  for (int i = 0; i < 8; i++) f[i] = badd2(pack_bf16(a[2 * i], a[2 * i + 1]), 0x35863586u);
}
__device__ __forceinline__ void phi_s(float* a, uint32_t* f) {
  #pragma unroll
  for (int i = 0; i < 8; i++) {
    asm("cvt.rn.relu.bf16x2.f32 %0, %1, %2;" : "=r"(f[i]) : "f"(a[2 * i + 1]), "f"(a[2 * i]));
    a[2 * i] *= 1.4426950408889634f; a[2 * i + 1] *= 1.4426950408889634f;
  }
  pinv<16>(a);
}
__device__ __forceinline__ void phi_e(float* a) {
  #pragma unroll
  for (int i = 0; i < 16; i++) asm("ex2.approx.ftz.f32 %0, %0;" : "+f"(a[i]));
  pinv<16>(a);
}
__device__ __forceinline__ void phi_b(const float* e, uint32_t* f) {
  #pragma unroll
  for (int i = 0; i < 8; i++) f[i] = badd2(f[i], pack_bf16(__saturatef(e[2 * i] + 1e-6f), __saturatef(e[2 * i + 1] + 1e-6f)));
}
__device__ __forceinline__ int g2_k(int st, int n2) {
  const int j = (st >> 1) - 1;
  return 2 * (j == 0 ? n2 == 0 : (j == max(n2, 1) ? 7 : j)) + (st & 1);
}

__global__ void __cluster_dims__(2, 1, 1) __launch_bounds__(NTHREADS, 1)
fused_kernel(const __grid_constant__ Params P, const __grid_constant__ CUtensorMap mX, const __grid_constant__ CUtensorMap mW,
             const __grid_constant__ CUtensorMap mWq, const __grid_constant__ CUtensorMap mWo,
             const __grid_constant__ CUtensorMap mK, const __grid_constant__ CUtensorMap mV, const __grid_constant__ CUtensorMap mH,
             const __grid_constant__ CUtensorMap mQ, const __grid_constant__ CUtensorMap mOut, const __grid_constant__ CUtensorMap mOutA,
             const __grid_constant__ CUtensorMap mWp) {
  extern __shared__ __align__(1024) uint8_t smem[];
  asm volatile(".reg .pred p_one;");
  const int tid = threadIdx.x, lane = tid & 31;
  const int warp = __shfl_sync(0xffffffffu, tid >> 5, 0);
  if (warp == 0) {
    asm volatile(ELECT "prefetch.tensormap [%0];\n}" :: "l"(&mW) : "memory");
    asm volatile(ELECT "prefetch.tensormap [%0];\n}" :: "l"(&mX) : "memory");
  }
  {
    const uint32_t t = threadIdx.x, bb = blockIdx.x;
    asm volatile("{\n.reg .pred p, q;\nsetp.eq.u32 p, %2, 2;\nsetp.eq.u32 q, %3, 8;\n@p prefetch.global.L2 [%0];\n@q prefetch.global.L2 [%1];\n}"
      :: "l"(reinterpret_cast<const char*>(P.x) + ((bb * 16 + t - 32) * 2048)),
         "l"(reinterpret_cast<const char*>(P.w) + ((bb >> 2) * 2048 + bb * 1024 + t * 128 - 6144)), "r"(t >> 4), "r"(t >> 3));
  }
  const uint32_t sb = uni(smem_u32(smem));
  const uint32_t bars = sb + BAR_OFF;
  const uint32_t ids = uni(wanted_job() * 2 + (blockIdx.x & 1));
#define IDS(w) const int rank = (w) & 1, hp = (w) & 15, g = hp >> 1, mb = (w) >> 4, m2 = hp, n2 = mb, cp = g * 8 + mb; \
               (void)rank; (void)m2; (void)n2; (void)cp
  auto job = [&]() { return (uni(lds32(sb + D_OFF + 52)) & 126) | (ids & 1); };
  auto wrong_job = [&]() {
    mbar_wait(bars + B_EX * 8, 0);
    return uni(lds32(sb + D_OFF + 52) ^ lds32(sb + D_OFF + 56)) != 1;
  };

  if (warp == 0) {
    IDS(ids);
    mbar_init(bars + (B_XF + 2) * 8, 1); mbar_init(bars + B_F0 * 8, 1); mbar_init(bars + B_FULL * 8, 1);
    mbar_expect_tx(bars + B_FULL * 8, 8192);
    tma3d(sb + W_OFF, &mW, hp * 64, 0, 1, bars + B_FULL * 8);
    mbar_expect_tx(bars + (B_XF + 2) * 8, 16384);
    tma2d(sb + 2 * SLOT, &mX, 0, mb * 256, bars + (B_XF + 2) * 8);
    mbar_expect_tx(bars + B_F0 * 8, 16384);
    tma2d(sb + 2 * SLOT + 16384, &mX, 0, mb * 256 + 128, bars + B_F0 * 8);
    #pragma unroll
    for (int i = 1; i < 4; i++) mbar_init(bars + (B_FULL + i) * 8, 1);
    #pragma unroll
    for (int i = 1; i < 4; i++) {
      mbar_expect_tx(bars + (B_FULL + i) * 8, 8192);
      tma3d(sb + W_OFF + i * 8192, &mW, hp * 64, i * 32, 1, bars + (B_FULL + i) * 8);
    }
    mbar_init(bars + B_XF * 8, 1); mbar_init(bars + (B_XF + 1) * 8, 1);
  } else if (warp >= 6) {
    const uint32_t cnt = warp < 12 || warp == 15 ? 1 : 4, b0 = bars + (warp - 4) * 32;
    #pragma unroll
    for (int i = 0; i < 4; i++) mbar_init(b0 + i * 8, i == 3 && warp == 15 ? 4 : cnt);
    if (warp == 8 || warp == 9) {
      #pragma unroll
      for (int i = 0; i < 4; i++) mbar_expect_tx(b0 + i * 8, 4096);
    } else if ((warp & 13) == 13) {
      mbar_expect_tx(bars + (warp == 13 ? B_KVB : B_EX) * 8, warp == 13 ? 5120 : 8);
    }
  }
  asm volatile("fence.mbarrier_init.release.cluster;" ::: "memory");
  __syncwarp();
  asm volatile("barrier.cluster.arrive.relaxed.aligned;" ::: "memory");

  if ((warp >> 2) == 2) {
    asm volatile("setmaxnreg.inc.sync.aligned.u32 %0;" :: "n"(160));
    const int ht = tid - 256, w = warp - 8;
    const int kap = w & 1;
    {
      uint32_t c4[4], s4[4];
      #pragma unroll
      for (int i = 0; i < 4; i++) {
        float c0, s0, c1, s1;
        unit_root<7>((32 * (ht & 3) + 8 * i + 1) * (ht >> 2), c0, s0);
        unit_root<7>((32 * (ht & 3) + 8 * i + 5) * (ht >> 2), c1, s1);
        c4[i] = pack_bf16(c0 * 0.125f, c1 * 0.125f); s4[i] = pack_bf16(s0 * 0.125f, s1 * 0.125f);
      }
      const uint32_t aa = sb + A_OFF + w * 2048 + (ht & 3) * 256 + ((ht >> 2) & 7) * 16;
      sts128(aa, c4[0], c4[1], c4[2], c4[3]);
      sts128(aa + 128, s4[0], s4[1], s4[2], s4[3]);
      sts128(aa + 1024, s4[0] ^ 0x80008000u, s4[1] ^ 0x80008000u, s4[2] ^ 0x80008000u, s4[3] ^ 0x80008000u);
      sts128(aa + 1024 + 128, c4[0], c4[1], c4[2], c4[3]);
      float c0, s0, c1, s1;
      unit_root<4>((ht >> 3) * (2 * (ht & 7)), c0, s0);
      unit_root<4>((ht >> 3) * (2 * (ht & 7) + 1), c1, s1);
      const uint32_t fa = sb + F_OFF + (ht >> 6) * 512 + ((ht >> 2) & 1) * 256 + ((ht >> 3) & 7) * 16 + (ht & 3) * 4;
      const uint32_t cc = pack_bf16(c0, c1), ss = pack_bf16(s0, s1);
      sts32(fa, cc); sts32(fa + 128, ss ^ 0x80008000u); sts32(fa + 1024, ss); sts32(fa + 1024 + 128, cc);
    }
    cluster_wait();
    mbar_wait(bars + B_EX * 8, 0);
    const uint32_t id2 = job(); IDS(id2);
    if (id2 != ids) bar_sync(8, 160);
    const uint4 sw = *reinterpret_cast<const uint4*>(P.shift + (cp * 16 + kap * 8 + 2 * (lane & 3)) * 4);
    const float dv = __bfloat162float(P.ssmD[cp * 16 + rank * 8 + (ht & 7)]) * 0.125f;
    Tw tw;
    make_tw(tw, ht);
    D2 cd[9];
    {
      const uint64_t v = P.cd[min(lane, 17)];
      #pragma unroll
      for (int i = 0; i < 9; i++) { cd[i].a = __shfl_sync(0xffffffffu, v, 2 * i); cd[i].b = __shfl_sync(0xffffffffu, v, 2 * i + 1); }
    }
    const D2 &dF = cd[0], *dT = cd + 1, *dH = cd + 5;
    D2* dX = cd + 7;
#define CFENCE(n) sched_fence<n>((uint32_t)dF.a)
    if (ht < 8) sts32(sb + D_OFF + ht * 4, __float_as_uint(dv));
    const uint32_t w0 = __byte_perm(sw.x, sw.z, 0x5410), w1 = __byte_perm(sw.x, sw.z, 0x7632);
    const uint32_t w2 = __byte_perm(sw.y, sw.w, 0x5410), w3 = __byte_perm(sw.y, sw.w, 0x7632);
    const uint32_t psb = uni(mapa(sb, rank ^ 1));
    if (ht == 0) OSTAMP(20);
    {
      const int m = lane >> 3, n1 = (w >> 1) * 8 + (lane & 7);
      const int rk = 17 * m + n1 + 1, rh = 17 * (12 + m) + n1, rv = 16 * m + n1;
      const uint32_t ka = rk * 32 + ((kap ^ (rk >> 2)) & 1) * 16, ha = rh * 32 + ((kap ^ (rh >> 2)) & 1) * 16;
      const uint32_t va = rv * 32 + ((kap ^ (rv >> 2)) & 1) * 16;
      const uint32_t po = sb + T_OFF + (w >> 1) * 2176;
      #pragma unroll 1
      for (int rd = 0; rd < 4; rd++) {
        const uint32_t kb = sb + M_OFF + (rd & 1) * KB, vb = sb + M_OFF + 2 * KB + (rd & 1) * 8192;
        const uint32_t xo = X_OFF + ((rd & 1) * 2 + (w >> 1)) * 1024 + (2 * rank + (rd >> 1)) * 256;
        const uint32_t xa = (kap == rank ? sb + xo + (lane & 7) * XS : po + (lane & 7) * 272) + m * 16;
        mbar_wait(bars + (B_STG + (rd & 1) * 2) * 8, rd >> 1);
        uint32_t kk[20], vv[16];
        const uint32_t zero = P.one - 1;
        ldsm4(kk, kb + ha);
        ldsm4(kk + 4, kb + ka);
        #pragma unroll
        for (int i = 0; i < 16; i++) {
          if ((i & 3) == 0 && i < 12) ldsm4(kk + 8 + i, kb + (ka ^ ((~i & 4) * 4)) + (i + 4) * 544 + (kk[i + 4] & zero));
          uint32_t t = bmul2(kk[i + 1], w3);
          t = badd2(t, bmul2(kk[i + 2], w2));
          t = badd2(t, bmul2(kk[i + 3], w1));
          kk[i] = badd2(t, bmul2(kk[i + 4], w0));
          asm volatile("" : "+r"(kk[i]));
        }
        mbar_wait(bars + (B_STG + (rd & 1) * 2 + 1) * 8, rd >> 1);
        ldsm4(vv, vb + va);
        #pragma unroll
        for (int i = 0; i < 16; i += 4) {
          if (i < 12) ldsm4(vv + 4 + i, vb + va + (i + 4) * 512 + (i == 4 ? vv[0] & zero : 0));
          stsm4t(xa + (i >> 2) * 64, bmul2(kk[i], vv[i]), bmul2(kk[i + 1], vv[i + 1]), bmul2(kk[i + 2], vv[i + 2]), bmul2(kk[i + 3], vv[i + 3]));
        }
        if (rd < 2) {
          fence_async_smem();
          __syncwarp();
          mbar_arrive(bars + (B_SFREE + (rd & 1)) * 8);
        }
        __syncwarp();
        if (kap != rank) {
          #pragma unroll
          for (int i = 0; i < 4; i++) lds128(vv + 4 * i, po + (2 * i + (lane >> 4)) * 272 + (lane & 15) * 16);
          #pragma unroll
          for (int i = 0; i < 4; i++)
            st_async128(psb + xo + (2 * i + (lane >> 4)) * XS + (lane & 15) * 16, psb + BAR_OFF + B_X * 8, vv[4 * i], vv[4 * i + 1], vv[4 * i + 2], vv[4 * i + 3]);
          __syncwarp();
        }
      }
    }
    bar_sync(3, 128);
    if (w == 0) mbar_expect_tx(bars + B_X * 8, 16384);
    {
      constexpr int NC = 8;
      Tmp t; t.t0 = 0.f; t.t1 = 0.f;
      asm volatile("setp.ne.b32 p_one, %0, 0;" :: "r"(lds32(sb + F_OFF)));
      float ra[32], lo[32], hi[32];
      uint32_t fa[2][2][4], fb[2][2][4];
      const uint32_t ta = sb + T_OFF + w * 2048 + lane * 16;
      const uint32_t y0 = rank ? psb : sb, y1 = rank ? sb : psb;
      auto fin = [&](int ch) {
        if (ch > 0) mbar_wait(bars + (B_YR + ch - 1) * 8, 0);
        finish(t, ra, ch, ht, rank, y0, y1);
      };
      auto load_h = [&](int i) {
        mbar_expect_tx(bars + B_H * 8, 4096);
        tma2d(sb + H_OFF, &mH, 0, (cp * 16 + rank * 8 + i) * 128, bars + B_H * 8);
      };
      auto skip = [&](int i) {
        const float dn = __uint_as_float(lds32(sb + D_OFF + i * 4));
        return dn;
      };
      mbar_wait(bars + B_H * 8, 0);
      wg_fence();
      dft32_h(lo, dH);
      mbar_wait(bars + B_X * 8, 0);
      fence_async_smem();
      if (ht == 0) OSTAMP(21);
      wg_fence();
      dft32_x(hi, dX);
      float dn = skip(0);
      wg_wait<1>(); pinv<32>(lo);
      if (w == 0) load_h(1);
      pack_fwd(fa, lo); CFENCE(0); rot_fwd(fa, tw); CFENCE(1);
      wg_wait<0>(); pinv<32>(hi);
      pack_fwd(fb, hi); CFENCE(2); rot_fwd(fb, tw); CFENCE(3);
      wg_fence();
      dft16h(hi, fb[1], dF); dft16h(hi + 16, fa[1], dF); dft16h(lo, fb[0], dF); dft16h(lo + 16, fa[0], dF);
      wg_commit();
      wg_wait<0>(); pinv<32>(lo); pinv<32>(hi);
#define CSTAMP(n) do {} while (0)
      #pragma unroll 1
      for (int i = 0;; i++) {
        CSTAMP(0);
        add_skip(lo + 16, dn);
        prod<1, 0, FG>(t, fa[1], lo, hi);
        CFENCE(4);
        CSTAMP(1);
        fence_async_smem();
        bar_sync(3, 128);
        CSTAMP(2);
        float rg[32];
        wg_fence();
        ss64x4(rg, dT, i);
        CFENCE(5);
        CSTAMP(3);
        const uint32_t yr = bars + (i < 2 ? B_X : B_YR + i - 2) * 8;
        const uint32_t oky = mbar_try(yr, 0);
        dn = skip(i + 1);
        prod<1, FG, 8>(t, fa[1], lo, hi);
        pinv<32>(lo);
        if (!oky) mbar_wait(yr, 0);
        CSTAMP(4);
        wg_wait<0>(); pinv<32>(rg);
        if (i > 0) finish(t, rg, i - 1, ht, rank, y0, y1);
        if (i == NC - 1) break;
        CSTAMP(5);
        wg_fence();
        dft32_x<false>(hi, dX);
        dft16h(ra + 16, fa[1], dF);
        wg_commit();
        CFENCE(7);
        CSTAMP(6);
        const uint32_t okh = mbar_try(bars + B_H * 8, (i + 1) & 1);
        prod<0>(t, fa[0], lo, lo);
        if (!okh) mbar_wait(bars + B_H * 8, (i + 1) & 1);
        CSTAMP(7);
        wg_fence();
        dft32_h<false>(lo, dH);
        dft16h(ra, fa[0], dF);
        wg_commit();
        wg_wait<1>(); pinv<32>(hi);
        if (ht == 64) OSTAMP(22 + i);
        CSTAMP(8);
        pack_fwd(fb, hi); CFENCE(9); rot_fwd(fb, tw); CFENCE(10);
        CSTAMP(9);
        wg_wait<0>(); pinv<32>(lo); pinv<32>(ra);
        CSTAMP(10);
        if (w == 0 && i < NC - 2) load_h(i + 2);
        pack_fwd(fa, lo);
        CFENCE(11);
        wg_fence();
        dft16h(hi, fb[1], dF); dft16h(lo, fb[0], dF);
        wg_commit();
        CFENCE(12);
        rot_fwd(fa, tw);
        uint32_t u[2][2][4];
        CFENCE(13);
        pack_inv(u, ra);
        CFENCE(14);
        CSTAMP(11);
        wg_fence();
        dft16h(hi + 16, fa[1], dF); dft16h(lo + 16, fa[0], dF);
        wg_commit();
        CFENCE(15);
        CSTAMP(12);
        rot_inv(u, tw, ta);
        CSTAMP(13);
        CFENCE(16);
        wg_wait<0>(); pinv<32>(lo); pinv<32>(hi);
        CSTAMP(14);
      }
      wg_fence();
      dft16h(hi + 16, fa[1], dF);
      wg_commit();
      CFENCE(17);
      prod<0>(t, fa[0], lo, lo);
      CFENCE(18);
      wg_fence();
      dft16h(hi, fa[0], dF);
      wg_commit();
      if (ht == 64) OSTAMP(29);
      wg_wait<0>(); pinv<32>(hi);
      pack_inv(fb, hi); CFENCE(19); rot_inv(fb, tw, ta);
      fence_async_smem();
      bar_sync(3, 128);
      idft32(ra, dT);
      const int l3 = fresh_tid() & 31;
      uint32_t qa = sb + M_OFF + ((l3 >> 4) * 512 + w * 128 + (l3 & 8) + ((l3 >> 2) & 1) + (l3 & 2)) * 32 + (l3 & 1) * 16;
      uint32_t yb = sb + X_OFF + (l3 & 1) * (XS + 16) + w * 512
                    + (((l3 >> 1) & 1) == rank ? (l3 >> 2) * 16 : YX - XS + ((l3 >> 2) ^ 4) * 16);
      mbar_wait(bars + B_Q * 8, 0);
      wg_wait<0>(); pinv<32>(ra);
      fin(NC - 1);
      if (ht == 64) OSTAMP(30);
      uint32_t t0 = 0, dt = 0;
      #pragma unroll 1
      for (int sg = 0; sg < 4; sg++, qa += 1024, yb += 128) {
        uint32_t qv[4][4], yv[4][4];
        #pragma unroll
        for (int i = 0; i < 4; i++) lds128(qv[i], qa + (i >> 1) * 512 + (i & 1) * 128);
        #pragma unroll
        for (int m = 0; m < 4; m++) {
          if (m == 3 && sg == 0) mbar_wait(bars + (B_YR + NC - 1) * 8, 0);
          ldsm4t(yv[m], yb + 2 * m * XS);
        }
        #pragma unroll
        for (int i = 0; i < 4; i++)
          sts128(qa + (i >> 1) * 512 + (i & 1) * 128, bmul2(qv[i][0], yv[0][i]), bmul2(qv[i][1], yv[1][i]), bmul2(qv[i][2], yv[2][i]), bmul2(qv[i][3], yv[3][i]));
        if (sg == 3) mbar_arrive(bars + B_CD * 8);
        fence_async_smem();
        __syncwarp();
        if (sg == 0) {
          mbar_wait(bars + B_GO * 8, 0);
          t0 = uni((uint32_t)clock());
          dt = uni(min(max((int)(lds32(sb + D_OFF + 44) + OA_END - t0) >> 2, 4 * OA_MIN), 4 * OA_MAX));
          t0 += w * (dt >> 2);
        }
        pace(t0, dt);
        #pragma unroll
        for (int hf = 0; hf < 2; hf++) {
          const int r = w * 128 + sg * 32 + hf * 512;
          tma2d_store(&mOutA, cp * 16, rank * 1024 + r, sb + M_OFF + r * 32);
        }
      }
      bulk_commit(); bulk_wait_read();
      if (ht == 0) OSTAMP(31);
    }
  } else if (warp >= 12) {
    asm volatile("setmaxnreg.dec.sync.aligned.u32 %0;" :: "n"(32));
    const uint32_t t_pf = (uint32_t)clock();
    if (warp >= 14) {
      const uint32_t id2 = fresh(ids); IDS(id2);
      if (warp == 14) {
        asm volatile("prefetch.global.L2 [%0];" :: "l"(((lane & 1) ? P.v : P.k) + (rank * 2097152 + cp * 32 + (lane >> 1) * 131072)));
      } else {
        uint32_t t0 = t_pf + id2 * 2;
        #pragma unroll 1
        for (int i = 0; i < PF_N; i++) {
          const int u = P.pf[i];
          const PfType& f = P.pt[u >> 4];
          pace(t0, i == 0 ? PF_DT0 : (i < PF_N1 ? PF_DT1 : PF_DT2));
          asm volatile("prefetch.global.L2 [%0];" :: "l"(f.base + ((g & 3) * f.gl + (g >> 2) * f.gh + mb * f.sp + rank * f.sr + (u & 15) * f.su
                                                                   + (lane >> 2) * f.l4 + ((lane >> 1) & 1) * f.l2 + (lane & 1) * 128)));
        }
      }
    }
    cluster_wait();
    if (warp == 13) {
      unsigned* const asked = P.cnt + 80 * 32;
      uint32_t j = ids, taken = 0;
      if (lane + (ids & 1) == 0) taken = atomicExch(P.cnt + 64 * 32 + ids * 4, 1u);
      if (uni(taken)) {
        fence_gpu();
        unsigned n = 0;
        if (lane == 0) n = atomicAdd(asked, 1u);
        spin_until(asked, (uni(n) | 63) + 1);
        #pragma unroll 1
        for (j = 0; j < 126; j += 2) {
          if (lane == 0) n = atomicExch(P.cnt + 64 * 32 + j * 4, 1u);
          if (!uni(n)) break;
        }
        if (lane == 0) P.cnt[64 * 32 + j * 4] = 1;
        j |= 128;
      }
      asm volatile("{\n.reg .pred p;\nsetp.lt.u32 p, %3, 2;\n@p st.async.weak.shared::cluster.mbarrier::complete_tx::bytes.b32 [%0], %2, [%1];\n}"
        :: "r"(mapa(sb + D_OFF + 52 + (j & 1) * 4, lane & 1)), "r"(mapa(bars + B_EX * 8, lane & 1)), "r"(j), "r"(lane) : "memory");
      if (!(j & 129)) { fence_gpu(); red_add(asked); }
    }
    if (warp == 12) {
      uint32_t xs = 0, idk = fresh(ids);
      auto load_x = [&](int k) {
        IDS(idk);
        tma2d_mc(sb + xs * SLOT + rank * 16384, &mX, k, mb * 256 + rank * 128, bars + (B_XF + xs) * 8);
        mbar_expect_tx(bars + (B_XF + xs) * 8, SLOT);
        xs = xs == 2 ? 0 : xs + 1;
      };
      load_x(64); load_x(128);
      mbar_expect_tx(bars + B_Q * 8, 32768);
      int look = 5;
      #pragma unroll 1
      for (int it = 1; it < 8; it++) {
        #pragma unroll
        for (int j = 0; j < 4; j++) {
          bool again = false;
          if (j == 3 && it == look) again = wrong_job();
          mbar_wait(bars + (B_EMPTY + j) * 8, (it - 1) & 1);
          TSTAMP(1, 4 * it + j);
          tma3d(sb + W_OFF + j * 8192, &mW, (idk & 15) * 64, it * 128 + j * 32, 1, bars + (B_FULL + j) * 8);
          if (again) { it = look = -1; idk = job(); }
          if (j == 1 || (j == 3 && it < 7)) load_x(it * 128 + j * 32 + 32);
          mbar_expect_tx(bars + (B_FULL + j) * 8, 8192);
        }
      }
    }
    if (warp == 14) {
      uint32_t t0 = t_pf + STG_T0, idk = fresh(ids);
      #pragma unroll 1
      for (int pc = 0; pc < 16; pc++) {
        if (pc == 2) {
          mbar_wait(bars + B_EX * 8, 0);
          if (job() != idk) { mbar_wait(bars + B_STG * 8, 0); mbar_arrive(bars + B_STG * 8); bar_sync(8, 160); idk = job(); pc = 0; }
        }
        IDS(idk);
        const int rd = pc >> 2, u = pc & 3;
        const uint32_t gb = bars + (B_STG + (rd & 1) * 2 + (u >> 1)) * 8;
        if (pc == 8 || pc == 12) mbar_wait(bars + (B_SFREE + (rd & 1)) * 8, 0);
        if (!(u & 1)) mbar_expect_tx(gb, u ? 8192 : KB);
        pace(t0, STG_DT);
        TSTAMP(3, 16 + pc);
        tma3d(sb + M_OFF + (u < 2 ? (rd & 1) * KB + u * (KB / 2) : 2 * KB + (rd & 1) * 8192 + (u & 1) * 4096), u < 2 ? &mK : &mV,
              cp * 16, rank * 64 + rd * 16 - (u < 2), (u & 1) * 8, gb);
      }
      IDS(idk);
      mbar_expect_tx(bars + B_H * 8, 4096);
      tma2d(sb + H_OFF, &mH, 0, (cp * 16 + rank * 8) * 128, bars + B_H * 8);
    }
    mbar_wait(bars + B_EX * 8, 0);
    const uint32_t id2 = job(); IDS(id2);
    if (warp == 12) {
      #pragma unroll 1
      for (int it = 0; it < 4; it++) {
        #pragma unroll
        for (int j = 0; j < 4; j++) {
          const uint32_t fb = bars + (B_FULL2 + j) * 8;
          if (j || it) mbar_wait(bars + (it ? B_EMPTY2 + j : B_EMPTY + (j | 1)) * 8, (it - 1) & 1);
          TSTAMP(5, 4 * it + j);
          tma2d_mc(sb + j * SLOT + 16384 + rank * 8192, &mWq, n2 * 128 + rank * 64, it * 256 + j * 64, fb);
          tma2d(sb + j * SLOT, &mX, it * 256 + j * 64, m2 * 128, fb);
          mbar_expect_tx(fb, SLOT);
        }
      }
      mbar_wait(bars + B_MF * 8, 0);
      #pragma unroll 1
      for (int pc = 0; pc < 8; pc++) { tma2d(sb + M_OFF + pc * 4096, &mQ, cp * 16, rank * 1024 + pc * 128, bars + B_Q * 8); }
      auto load_wo = [&](int st, uint32_t ph) {
        const uint32_t j = st & 3, fb = bars + (B_FULL2 + j) * 8, k = fresh(g2_k(st, n2) * 64);
        mbar_wait(bars + (B_EMPTY2 + j) * 8, ph);
        TSTAMP(5, 16 + st);
        tma2d_mc(sb + j * SLOT + 16384 + rank * 8192, &mWo, n2 * 128 + rank * 64, k, fb);
        mbar_expect_tx(fb, 16384);
      };
      load_wo(4, 1);
      mbar_wait(bars + (B_EMPTY2 + 1) * 8, 1);
      asm volatile(ELECT "cp.async.bulk.tensor.5d.shared::cluster.global.mbarrier::complete_tx::bytes.multicast::cluster [%0], [%1, {%3, %4, %4, %4, %5}], [%2], %6;\n}"
        :: "r"(sb + SLOT + rank * 16384), "l"(&mWp), "r"(bars + (B_FULL2 + 1) * 8), "r"(n2 * 128 + rank * 64), "r"(0), "r"(n2 * 4), "h"((uint16_t)3) : "memory");
      mbar_expect_tx(bars + (B_FULL2 + 1) * 8, SLOT);
      load_wo(2, 1);
      load_wo(3, 1);
      mbar_arrive(bars + B_QE * 8);
      #pragma unroll 1
      for (int it = 1; it < 4; it++) {
        load_wo(4 * it + 1, (it - 1) & 1); load_wo(4 * it + 2, (it - 1) & 1); load_wo(4 * it + 3, (it - 1) & 1);
        if (it < 3) load_wo(4 * it + 4, (it - 1) & 1);
      }
    } else {
      if (warp == 13) {
      if ((sb & 0xffffff) != SB0) __trap();
      float4* zp = reinterpret_cast<float4*>(P.kv + hp * KV_PER_HP + mb * 264);
      const float4 z4 = make_float4(0.f, 0.f, 0.f, 0.f);
      zp[lane] = z4; zp[lane + 32] = z4;
      if (lane < 2) zp[lane + 64] = z4;
      if (lane == 0) P.cnt[hp * 32 + 8 + mb] = t_pf;
      {
        uint4* op = P.o + (m2 * 8 + n2) * 2048 + lane;
        uint32_t t0 = t_pf + RS_T0 + mb * (RS_DT / 8);
        #pragma unroll 1
        for (int i = 0; i < 8; i++) {
          while ((int)((uint32_t)clock() - t0) < 0) __nanosleep(100);
          t0 += RS_DT;
          #pragma unroll
          for (int j = 0; j < 8; j++) op[(i * 8 + j) * 32] = make_uint4(~0u, ~0u, ~0u, ~0u);
        }
      }
      fence_gpu();
      __syncwarp();
      unsigned gen = 0;
      if (lane == 0) gen = (atomicAdd(&P.cnt[hp * 32], 1u) >> 3) + 1;
      gen = uni(gen);
      sts32(sb + D_OFF + 40, gen);
      spin_until(&P.cnt[hp * 32], gen * 8);
      sts32(sb + D_OFF + 48, __ballot_sync(0xffffffffu, (TEST & 4) || __ldcg(&P.cnt[hp * 32 + 8 + (lane & 7)]) - t_pf + 4096 >= 8192));
      mbar_arrive(bars + B_Z * 8);
      }
      {
        float* kr = P.kv + hp * KV_PER_HP;
        mbar_wait(bars + B_Z * 8, 0);
        bar_sync(4, 352);
        #pragma unroll 1
        for (int i0 = max(warp * 6 - 80, 0); i0 < warp * 6 - 74; i0 += 2) {
          uint32_t p[2][4], q[2][4];
          const int i = (i0 + 2 * mb) & 15;
          const uint32_t pa = sb + M_OFF + (i & 3) * 2048 + (i >> 2) * 512 + (lane & 7) * 64 + (((lane >> 3) ^ (lane >> 1)) & 3) * 16;
          lds128(p[0], pa); lds128(q[0], pa + VT); lds128(p[1], pa + 2048); lds128(q[1], pa + VT + 2048);
          #pragma unroll
          for (int j = 0; j < 2; j++)
            asm volatile("red.relaxed.gpu.global.add.v4.f32 [%0], {%1,%2,%3,%4};" :: "l"(kr + (i + j) * 128 + lane * 4),
              "f"(__uint_as_float(p[j][0]) + __uint_as_float(q[j][0])), "f"(__uint_as_float(p[j][1]) + __uint_as_float(q[j][1])),
              "f"(__uint_as_float(p[j][2]) + __uint_as_float(q[j][2])), "f"(__uint_as_float(p[j][3]) + __uint_as_float(q[j][3])) : "memory");
        }
        if (warp == 13) {
          const uint32_t za = sb + M_OFF + 8192 + lane * 4;
          #pragma unroll
          for (int h = 0; h < 2; h++)
            asm volatile("red.relaxed.gpu.global.add.f32 [%0], %1;" :: "l"(kr + 2048 + h * 32 + lane),
              "f"(__uint_as_float(lds32(za + h * 128)) + __uint_as_float(lds32(za + h * 128 + VT))) : "memory");
        }
        bar_sync(5, 96);
        if (warp == 13) {
          mbar_arrive(mapa(bars, rank ^ 1) + B_KVL * 8);
          mbar_arrive(bars + B_MF * 8);
          OSTAMP(17);
          fence_gpu();
          red_add(&P.cnt[hp * 32 + 1]);
          OSTAMP(15);
        }
      }
      const unsigned gen = uni(lds32(sb + D_OFF + 40));
      {
        const int u0 = (15 - warp) * 3;
        const float* kg = P.kv + (2 * n2 + rank) * KV_PER_HP + u0 * 256;
        const uint32_t psb = uni(mapa(sb, rank ^ 1));
        auto put = [&](uint32_t o, uint32_t v0, uint32_t v1, uint32_t v2, uint32_t v3) {
          st_async128(psb + o, psb + BAR_OFF + B_KVB * 8, v0, v1, v2, v3);
          sts128(sb + o, v0, v1, v2, v3);
        };
        auto put8 = [&](int j, const float4* v) {
          put(KVB_OFF + (rank * 8 + u0 + j) * 640 + lane * 16, pack_bf16(v[0].x, v[0].y), pack_bf16(v[0].z, v[0].w), pack_bf16(v[1].x, v[1].y), pack_bf16(v[1].z, v[1].w));
        };
        mbar_wait(bars + B_KVL * 8, 0);
        spin_until(&P.cnt[(2 * n2 + rank) * 32 + 1], gen * 8);
        float4 v[3][2];
        #pragma unroll
        for (int j = 0; j < 2; j++) {
          const float4* kr = reinterpret_cast<const float4*>(kg + j * 256) + lane;
          v[j][0] = __ldcg(kr); v[j][1] = __ldcg(kr + 32);
        }
        if (warp == 13) {
          const float z0 = __ldcg(kg + 512 + lane), z1 = __ldcg(kg + 544 + lane);
          const uint32_t za = KVB_OFF + (rank * 8 + (lane >> 3)) * 640 + 512 + (lane & 7) * 16, a = pack_bf16(z0, z0), b = pack_bf16(z1, z1);
          put(za, a, a, a, a); put(za + 2560, b, b, b, b);
        } else {
          const float4* kr = reinterpret_cast<const float4*>(kg + 512) + lane;
          v[2][0] = __ldcg(kr); v[2][1] = __ldcg(kr + 32);
          put8(2, v[2]);
        }
        put8(0, v[0]); put8(1, v[1]);
        fence_async_smem();
        __syncwarp();
        mbar_arrive(bars + B_KVB * 8);
      }
      if (warp == 13) {
        bar_sync(6, 288);
        mbar_wait(bars + B_GO * 8, 0);
        fence_gpu();
        asm volatile(ELECT "st.relaxed.gpu.global.u32 [%0], %1;\n}" :: "l"(&P.cnt[(16 + m2) * 32 + n2]), "r"(gen) : "memory");
        OSTAMP(32);
      } else {
        const int wg = 15 - warp;
        const uint32_t ab = bars + B_FA * 8 + wg * 32, far = uni(lds32(sb + D_OFF + 48));
        const unsigned* fp = &P.cnt[(32 + m2 * 2 + wg) * 32 + lane];
        const char* og = reinterpret_cast<const char*>(P.o + m2 * 16384 + wg * 512);
        unsigned v = gen;
        auto poll = [&](int k) {
          const bool mine = (lane >> 2) == (k >> 1);
          #pragma unroll 1
          for (int n = 0; n < WAIT_BOUND; n++) {
            asm volatile("ld.relaxed.gpu.global.u32 %0, [%1];" : "=r"(v) : "l"(fp) : "memory");
            if (!__any_sync(0xffffffffu, mine && v != gen)) break;
          }
        };
        mbar_arrive(ab + 8);
        mbar_expect_tx(ab + 16, 8192); mbar_expect_tx(ab + 24, 8192);
        fence_async_global();
        {
          const int k = g2_k(2, n2);
          const char* src = reinterpret_cast<const char*>(__shfl_sync(0xffffffffu, reinterpret_cast<uint64_t>(og + k * 16384), 0));
          mbar_wait(bars + B_QE * 8, 0);
          if (!(TEST & 2)) poll(k);
          bulk_load(sb + 2 * SLOT + wg * 8192, src, 8192, ab + 16);
          bulk_load(sb + 3 * SLOT + wg * 8192, src + 16384, 8192, ab + 24);
        }
        uint32_t safe = (uint32_t)clock() + FAR_DT, miss = __ballot_sync(0xffffffffu, v != gen) | ((TEST & 2) ? ~0xfffu : 0);
        OSTAMP(18 + wg * 15);
        TSTAMP(9, wg * 16 + 8);
        #pragma unroll 1
        for (int st = 4; st < 16; st += 2) {
          const int k = g2_k(st, n2), j = st & 3;
          const char* src = og + k * 16384;
          const uint32_t eb = bars + (B_EMPTY2 + j) * 8, ph = ((st >> 2) - 1) & 1, dst = sb + j * SLOT + wg * 8192;
          if ((miss >> (2 * k)) & 15) {
            poll(k);
            miss = __ballot_sync(0xffffffffu, v != gen);
            safe = (uint32_t)clock() + FAR_DT;
          }
          if ((far >> (k >> 1)) & 1) while ((int)(uni((uint32_t)clock()) - safe) < 0) {}
          mbar_wait(eb, j ? ph : ph ^ 1);
          bulk_load(dst, src, 8192, ab + j * 8);
          mbar_expect_tx(ab + j * 8, 8192);
          if (st < 10) TSTAMP(9, wg * 16 + 5 + st);
          if (st == 4 && wg) { sts32(sb + D_OFF + 44, (uint32_t)clock()); mbar_arrive(bars + B_GO * 8); }
          mbar_wait(eb + 8, ph);
          bulk_load(dst + SLOT, src + 16384, 8192, ab + j * 8 + 8);
          mbar_expect_tx(ab + j * 8 + 8, 8192);
          if (st < 10) TSTAMP(9, wg * 16 + 6 + st);
        }
        if (wg + rank + lane == 0) P.cnt[64 * 32 + id2 * 4] = 0;
      }
    }
  } else {
    asm volatile("setmaxnreg.inc.sync.aligned.u32 %0;" :: "n"(160));
    const int wg = warp >> 2;
    Team c;
    c.bars = bars; c.rel = mapa(bars, tid & 1); c.wofs = wg * 8192; c.lead = fresh((tid & 127) < 2);
    uint32_t key = P.one;
    auto gemm2 = [&](float* a, auto O_, auto SK_, auto last) {
      constexpr int O = O_.value, SK = SK_.value;
      static_assert(SK >= 1 && SK <= 3 + O, "tail");
      uint32_t ph = 1;
      const uint32_t ab = bars + B_FA * 8 + wg * 32;
      #pragma unroll 1
      for (int it = 1; it < 4; it++, ph ^= 1) {
        if (SK == 4 && it == 3) break;
        c.wofs += P.one - 1;
        ring_step<false, O>(c, B_FULL2, ph ^ O, B_EMPTY2 + 3, c.lead, [&](auto f) { g2_issue<O, 0, (MID >> (1 + O)) & 1>(a, c, [&]() { f(); if (O && (tid & 127) == 0 && 4 * it + 0 < 10) TSTAMP(9, wg * 16 + 4 * it + 0 - 2); }); }, ab, ph ^ 1);
        if (!O && (tid & 127) == 0) OSTAMP(55 + wg * 4 + it);
        if (O && (tid & 127) == 0) OSTAMP(40 + wg * 4 + it);
        if (SK == 3 && it == 3) break;
        ring_step<false, O>(c, B_FULL2 + 1, ph, B_EMPTY2, (!O || it < 3 ? c.lead : 0), [&](auto f) { g2_issue<O, 1, (MID >> (1 + O)) & 1>(a, c, [&]() { f(); if (O && (tid & 127) == 0 && 4 * it + 1 < 10) TSTAMP(9, wg * 16 + 4 * it + 1 - 2); }); }, ab + 8, ph);
        if (SK == 2 && it == 3) break;
        ring_step<false, O>(c, B_FULL2 + 2, ph, B_EMPTY2 + 1, (!O || it < 3 ? c.lead : 0), [&](auto f) { g2_issue<O, 2, (MID >> (1 + O)) & 1>(a, c, [&]() { f(); if (O && (tid & 127) == 0 && 4 * it + 2 < 10) TSTAMP(9, wg * 16 + 4 * it + 2 - 2); }); }, ab + 16, ph);
        if (SK == 1 && it == 3) break;
        ring_step<false, O>(c, B_FULL2 + 3, ph, B_EMPTY2 + 2, c.lead, [&](auto f) { g2_issue<O, 3, (MID >> (1 + O)) & 1>(a, c, [&]() { f(); if (O && (tid & 127) == 0 && 4 * it + 3 < 10) TSTAMP(9, wg * 16 + 4 * it + 3 - 2); }); }, ab + 24, ph);
      }
      if (!O) {
        auto rel = [&](int jj, bool on) { arrive_at(c.rel + (B_EMPTY2 + jj) * 8, on ? c.lead : 0); };
        if (wg) { wg_wait<0>(); rel(3 - SK, true); mbar_wait(bars + B_SK * 8, 1); }
        auto st = [&](auto J_) {
          constexpr int J = J_.value;
          mbar_wait(bars + (B_FULL2 + J) * 8, 1);
          g2_half<0, J, 0>(a, c);
          wg_wait<1>(); rel(J - 1, J > 4 - SK || !wg);
          g2_half<0, J, 1>(a, c);
          if (J < 3) wg_wait<1>();
        };
        if (SK >= 3) st(IC<1>());
        if (SK >= 2) st(IC<2>());
        st(IC<3>());
        arrive_at(bars + B_SK * 8, fresh_tid() == 0);
        last();
        wg_wait<0>(); rel(3, true);
      } else
      skew_tail<SK>(c, O ^ 1,
        [&]() {
          auto full = [&](int jj) { mbar_wait(bars + (B_FULL2 + jj) * 8, 1); mbar_wait(ab + jj * 8, 1); };
          if (SK >= 4) {
            mbar_wait(bars + B_FULL2 * 8, 0); mbar_wait(ab, 0); g2_issue<O, 0>(a, c);
            wg_wait<1>(); arrive_at(c.rel + (B_EMPTY2 + 3) * 8, wg ? 0 : c.lead);
          }
          if (SK >= 3) { full(1); g2_issue<O, 1>(a, c); }
          if (SK >= 2) { full(2); g2_issue<O, 2>(a, c); }
          full(3); g2_issue<O, 3>(a, c);
        },
        [&](int i) { if (SK == 4 && i < 0) arrive_at(c.rel + (B_EMPTY2 + 3) * 8, wg ? c.lead : 0); });
      pinv<64>(a);
    };
    float aq[64];
    {
      float aK[64], aV[64];
      if (wg == 0) { kv_issue<0>(aK, aV, 0, 0); wg_wait<0>(); }
      auto start = [&]() {
        if (!P8) return;
        #pragma unroll
        for (int i = 0; i < 64; i++) { asm volatile("mov.b32 %0, 0f3F800000;" : "=f"(aK[i])); asm volatile("mov.b32 %0, 0;" : "=f"(aV[i])); }
      };
      start();
      cluster_wait();
      if (wg == 1) mbar_wait(bars + B_F0 * 8, 0);
      static_assert(SK1 >= 1 && SK1 <= 3, "tail");
      uint32_t ph = 0, xs = 2, xp = 0;
      auto next_x = [&]() { if (xs == 1) xp ^= 1; xs = xs == 2 ? 0 : xs + 1; };
      uint32_t rel = 0;
      int look = 5;
      uint32_t xo = xs * SLOT + wg * 16384;
      #pragma unroll 1
      for (int it = 0; it < 8; it++, ph ^= 1) {
        ring_step<false, true>(c, B_FULL, ph, B_EMPTY + 3, rel, [&](auto f) { kv_issue<0, MID & 1>(aK, aV, xo, P8 ? 1 : it, f); if (tid == 0 && it == 0) OSTAMP(1); }, bars + (B_XF + xs) * 8, xp);
        if (SK1 == 3 && it == 7) break;
        next_x();
        ring_step<false>(c, B_FULL + 1, ph, B_EMPTY, c.lead, [&](auto f) { kv_issue<1, MID & 1>(aK, aV, xo, 1, f); });
        if (SK1 == 2 && it == 7) break;
        xo = xs * SLOT + wg * 16384;
        ring_step<false, true>(c, B_FULL + 2, ph, B_EMPTY + 1, c.lead, [&](auto f) { kv_issue<2, MID & 1>(aK, aV, xo, 1, f); }, bars + (B_XF + xs) * 8, xp);
        if (SK1 == 1 && it == 7) break;
        next_x();
        ring_step<false>(c, B_FULL + 3, ph, B_EMPTY + 2, c.lead, [&](auto f) { kv_issue<3, MID & 1>(aK, aV, xo, 1, f); });
        rel = c.lead;
        xo = xs * SLOT + wg * 16384;
        if (it == look && wrong_job()) { wg_wait<0>(); start(); it = look = -1; }
      }
      skew_tail<SK1>(c, 0,
        [&]() {
          auto wait = [&](uint32_t a) { mbar_wait(a, 1); };
          if (SK1 >= 3) { wait(bars + (B_FULL + 1) * 8); kv_issue<1>(aK, aV, SLOT + wg * 16384, 1); }
          if (SK1 >= 2) { wait(bars + (B_FULL + 2) * 8); wait(bars + (B_XF + 2) * 8); kv_issue<2>(aK, aV, 2 * SLOT + wg * 16384, 1); }
          wait(bars + (B_FULL + 3) * 8); kv_issue<3>(aK, aV, 2 * SLOT + wg * 16384, 1);
        },
        [&](int i) { arrive_at(c.rel + (B_EMPTY + ((32 - SK1 + i) & 3)) * 8, c.lead); });
      pinv<64>(aV); pinv<64>(aK);
      if (tid == 128) OSTAMP(3);
      const uint32_t vb = sb + M_OFF + wg * VT;
      float kv[36];
      uint32_t kf[4][8];
      const uint64_t dv = dofs(cdesc(M_OFF, 1152, 128, 0), wg * VT);
      const int t = fresh_tid();
      const uint32_t va = vb + ((t >> 4) & 1) * 1152 + ((t >> 5) & 3) * 256 + (t & 15) * 16;
      mbar_wait(bars + B_X * 8, 0);
      #pragma unroll
      for (int i = 0; i < 8; i++) {
        const float* a = aV + 8 * i;
        stsm4(va + i * 2304, pack_bf16(a[0], a[1]), pack_bf16(a[2], a[3]), pack_bf16(a[4], a[5]), pack_bf16(a[6], a[7]));
      }
      if (P8) phi1_a(aK + 48); else phi_a(aK + 48, kf[3]);
      mbar_wait(bars + B_FULL2 * 8, 0);
      if ((tid & 127) == 0) OSTAMP(50 + wg);
      g2_issue<0, 0, false, true>(aq, c);
      sched_fence(key++);
      sts128(vb + ((t & 127) >> 3) * 1152 + 1024 + (t & 7) * 16, 0x3f803f80u, 0x3f803f80u, 0x3f803f80u, 0x3f803f80u);
      if (P8) phi1_a(aK + 32); else phi_a(aK + 32, kf[2]); if (P8) phi1_b(aK + 48, kf[3]); else phi_b(aK + 48, kf[3]);
      sched_fence(key++);
      ring_step<true>(c, B_FULL2 + 1, 0, B_EMPTY2, c.lead, [&]() { g2_issue<0, 1>(aq, c); });
      sched_fence(key++);
      if (P8) phi1_a(aK + 16); else phi_a(aK + 16, kf[1]); if (P8) phi1_b(aK + 32, kf[2]); else phi_b(aK + 32, kf[2]);
      sched_fence(key++);
      ring_step<true>(c, B_FULL2 + 2, 0, B_EMPTY2 + 1, c.lead, [&]() { g2_issue<0, 2>(aq, c); });
      sched_fence(key++);
      if (P8) phi1_a(aK); else phi_a(aK, kf[0]); if (P8) phi1_b(aK + 16, kf[1]); else phi_b(aK + 16, kf[1]);
      sched_fence(key++);
      fence_async_smem(); bar_sync(1 + wg, 128);
      if (P8) phi1_b(aK, kf[0]); else phi_b(aK, kf[0]);
      sched_fence(key++);
      wg_fence();
      #pragma unroll
      for (int ks = 0; ks < 8; ks++) {
        if (ks == 0) rs72z<0>(kv, kf[0], dv); else rs72a<0>(kv, kf[ks >> 1] + 4 * (ks & 1), dofs(dv, ks * 2304));
      }
      wg_commit();
      wg_wait<1>();
      arrive_at(c.rel + (B_EMPTY2 + 2) * 8, c.lead);
      mbar_wait(bars + (B_FULL2 + 3) * 8, 0);
      g2_issue<0, 3>(aq, c);
      wg_wait<1>();
      pinv<36>(kv);
      const int a = fresh_tid() & 127;
      const bool hi = a >= 64;
      #pragma unroll
      for (int u = 0; u < 4; u++) {
        const int o = (u & 1) * 8 + (u & 2);
        sts128(vb + (a ^ ((a >> 3) & 3)) * 16 + u * 2048, __float_as_uint(hi ? kv[16 + o] : kv[o]), __float_as_uint(hi ? kv[17 + o] : kv[o + 1]),
               __float_as_uint(hi ? kv[20 + o] : kv[o + 4]), __float_as_uint(hi ? kv[21 + o] : kv[o + 5]));
      }
      if ((a & 3) < 2) sts32(vb + 8192 + ((a >> 5) * 16 + ((a & 31) >> 2) + (a & 1) * 8) * 4, __float_as_uint((a & 1) ? kv[34] : kv[32]));
      bar_arrive(4, 352);
    }
    if (tid == 0) OSTAMP(4);
    if (tid == 128) OSTAMP(5);
    float acc[64];
    {
      uint32_t kvok;
      gemm2(aq, IC<0>(), IC<SK2>(), [&]() {
        kvok = mbar_try(bars + B_KVB * 8, 0);
        if (kvok) fence_async_smem();
      });
      if (tid == 0) OSTAMP(6);
      if (tid == 128) OSTAMP(7);
      constexpr uint64_t dk = cdesc(KVB_OFF, 640, 128, 0);
      const uint32_t id2 = job(); IDS(id2);
      float nu[4][20];
      uint32_t pq[4][8], o[4][2][4];
      const int t2 = fresh_tid();
      const uint32_t oo = (t2 & 96) * 32 + (t2 & 28) * 16 + ((t2 ^ (t2 >> 3)) & 3) * 16;
      uint4* og = P.o + ((m2 * 8 + n2) * 4 + wg) * 512 + (oo >> 4);
      auto o_put = [&](int h, int e) {
        asm volatile("st.global.v4.b32 [%0], {%1,%2,%3,%4};" :: "l"(og + (h >> 1) * 1024 + (h & 1) * 256 + e * 32),
          "r"(o[h][e][0]), "r"(o[h][e][1]), "r"(o[h][e][2]), "r"(o[h][e][3]) : "memory");
      };
      auto o_out = [&](int h) {
        pinv<20>(nu[h]);
        #pragma unroll
        for (int e = 0; e < 2; e++) {
          const float* n = nu[h] + 2 * e;
          const float iv = rcp_fast(n[16] + 1e-6f);
          #pragma unroll
          for (int i = 0; i < 4; i++) o[h][e][i] = pack_bf16(n[4 * i] * iv, n[4 * i + 1] * iv);
          o_put(h, e);
        }
      };
      auto o_mma = [&](int h) {
        wg_fence();
        rs40z<1>(nu[h], pq[h], dk + h * (2560 >> 4));
        rs40a<1>(nu[h], pq[h] + 4, dk + h * (2560 >> 4) + (1280 >> 4));
        wg_commit();
      };
      auto sent = [&](uint32_t v) {
        asm volatile(ELECT "st.relaxed.gpu.global.u32 [%0], %1;\n}" :: "l"(&P.cnt[(32 + m2 * 2 + wg) * 32 + n2 * 4 + (warp & 3)]), "r"(v) : "memory");
      };
      phi_s(aq, pq[0]); phi_e(aq); phi_s(aq + 16, pq[1]);
      if (!kvok) { mbar_wait(bars + B_KVB * 8, 0); fence_async_smem(); }
      const uint32_t gen = lds32(sb + D_OFF + 40), far = lds32(sb + D_OFF + 48);
      #pragma unroll
      for (int u = 0; u < 4; u++) {
        if (u < 3) phi_e(aq + 16 * u + 16);
        phi_b(aq + 16 * u, pq[u]);
        o_mma(u);
        if (u < 2) phi_s(aq + 16 * u + 32, pq[u + 2]);
        if (u > 0) { wg_wait<1>(); o_out(u - 1); }
        sched_fence(key++);
      }
      wg_wait<0>(); o_out(3);
      sent(gen);
      bar_arrive(6, 288);
      arrive_at(bars + B_OD * 8, t2 == 128);
      if ((t2 & 127) == 0) OSTAMP(8 + wg * 2);
      {
        sched_fence(key++);
        #pragma unroll
        for (int i = 0; i < 32; i++) asm volatile("lop3.b32 %0, %1, %2, 0, 0xf0 | 0xcc;" : "=r"(o[i >> 3][(i >> 2) & 1][i & 3]) : "r"(o[i >> 3][(i >> 2) & 1][i & 3]), "r"(P.one - 1));
      }
      if (wg == 0) mbar_wait(bars + B_OD * 8, 0);
      mbar_wait(bars + (B_FULL2 + 1) * 8, 0);
      wg_fence();
      #pragma unroll
      for (int i = 0; i < 8; i++) {
        const uint32_t f[4] = {o[i >> 1][0][i & 1], o[i >> 1][1][i & 1], o[i >> 1][0][2 + (i & 1)], o[i >> 1][1][2 + (i & 1)]};
        constexpr uint64_t dw = cdesc(SLOT, 16384, 2048, 1);
        if (i == 0) rs128z<1>(acc, f, dw); else rs128a<1>(acc, f, dw + (((i >> 1) * 4096 + (i & 1) * 1024) >> 4));
      }
      wg_commit();
      if ((t2 & 127) == 0) OSTAMP(37 + wg);
      if ((t2 & 127) == 0) TSTAMP(9, wg * 16 + 15);
      const uint32_t ab = bars + B_FA * 8 + wg * 32;
      const int k2 = g2_k(2, n2);
      const bool doubt = (uni(far) >> (k2 >> 1)) & 1;
      auto look = [&](int j) {
        if (doubt) {
          const uint32_t a = sb + (2 + j) * SLOT + wg * 8192 + (t2 & 96) * 32;
          if (__any_sync(0xffffffffu, lds32(a + (t2 & 16) * 256 + (t2 & 15) * 64 + (t2 & 30) * 2) == ~0u)) {
            const uint4* src = P.o + (m2 * 16 + k2 + j) * 1024 + wg * 512 + (t2 & 96) * 2 + (t2 & 31);
            if ((t2 & 31) == 0) OSTAMP(34);
            #pragma unroll 1
            for (int i = 0; i < 4; i++) {
              uint32_t v[4];
              int n = 0;
              do asm volatile("ld.relaxed.gpu.global.v4.u32 {%0,%1,%2,%3}, [%4];" : "=r"(v[0]), "=r"(v[1]), "=r"(v[2]), "=r"(v[3]) : "l"(src + (i & 1) * 32 + (i >> 1) * 256) : "memory");
              while (__any_sync(0xffffffffu, v[0] == ~0u) && ++n < 64);
              sts128(a + (t2 & 31) * 16 + (i & 1) * 512 + (i >> 1) * 4096, v[0], v[1], v[2], v[3]);
            }
            fence_async_smem();
            __syncwarp();
          }
        }
      };
      #pragma unroll 1
      for (int j = 0; j < 2; j += P.one)
        ring_step<true, true>(c, B_FULL2 + 2 + j, 0, B_EMPTY2 + 1 + j, c.lead, [&]() {
          look(j);
          if ((t2 & 127) == 0 && j == 0) OSTAMP(11 + wg * 24);
          if ((t2 & 127) == 0) TSTAMP(9, wg * 16 + j);
          const uint64_t da = dofs(cdesc(2 * SLOT, 16, 512, 2), c.wofs + j * SLOT), db = dofs(cdesc(2 * SLOT + 16384, 8192, 1024, 1), j * SLOT);
          wg_fence();
          #pragma unroll
          for (int i = 0; i < 4; i++) ss128a<0, 1>(acc, dofs(da, (i & 1) * 32 + (i >> 1) * 4096), dofs(db, i * 2048));
          wg_commit();
        }, ab + 16 + j * 8, 0);
    }
    gemm2(acc, IC<1>(), IC<SK3>(), []() {});
    if (tid == 0) OSTAMP(13);
    if (tid == 128) OSTAMP(14);
    {
      const uint32_t id2 = job(); IDS(id2);
      const int t2 = fresh_tid();
      const int row = ((t2 >> 5) & 3) * 16 + (t2 & 15);
      const int cq = (t2 >> 4) & 1, sw = t2 & 7;
      const uint32_t stg = sb + (EHI ? T_OFF : 0) + wg * 8192;
      constexpr uint32_t HS = EHI ? 16384 : SLOT;
      if (EHI) mbar_wait(bars + B_CD * 8, 0);
      #pragma unroll 1
      for (int pass = 0;; pass++) {
      const bool bad = acc[0] != acc[0] || acc[2] != acc[2];
      #pragma unroll
      for (int hf = 0; hf < 2; hf++) {
        #pragma unroll
        for (int jj = 0; jj < 4; jj++) {
          const int o = hf * 32 + jj * 8;
          stsm4(stg + hf * HS + row * 128 + (((2 * jj + cq) ^ sw) << 4),
                pack_bf16(acc[o], acc[o + 1]), pack_bf16(acc[o + 2], acc[o + 3]),
                pack_bf16(acc[o + 4], acc[o + 5]), pack_bf16(acc[o + 6], acc[o + 7]));
        }
        fence_async_smem();
        __syncwarp();
        tma2d_store(&mOut, 1024 + n2 * 128 + hf * 64, m2 * 128 + warp * 16, sb + (EHI ? T_OFF : 0) + hf * HS + warp * 2048);
      }
      bulk_commit();
      uint32_t redo;
      asm volatile("{\n.reg .pred p, q;\nsetp.ne.b32 p, %1, 0;\nbar.red.or.pred q, %2, 128, p;\nselp.u32 %0, 1, 0, q;\n}" : "=r"(redo) : "r"((uint32_t)bad), "r"(1 + wg) : "memory");
      if (!uni(redo) || pass) break;
      if ((t2 & 127) == 0) OSTAMP(48 + wg);
      asm volatile("cp.async.bulk.wait_group 0;" ::: "memory");
      spin_until(&P.cnt[(16 + m2) * 32 + (t2 & 7)], lds32(sb + D_OFF + 40));
      fence_async_global();
      const uint32_t ab = bars + B_FA * 8 + wg * 32;
      #pragma unroll 1
      for (int k = 0; k < 16; k += P.one) {
        bar_sync(1 + wg, 128);
        if ((warp & 3) == 0) {
          mbar_expect_tx(ab, 24576);
          bulk_load(sb + c.wofs, P.o + (m2 * 16 + k) * 1024 + wg * 512, 8192, ab);
          tma2d(sb + SLOT + c.wofs, &mWo, n2 * 128, k * 64, ab);
          tma2d(sb + 2 * SLOT + c.wofs, &mWo, n2 * 128 + 64, k * 64, ab);
        }
        mbar_wait(ab, ~k & 1);
        const uint64_t da = dofs(cdesc(0, 16, 512, 2), c.wofs), db = dofs(cdesc(SLOT, SLOT, 1024, 1), c.wofs);
        wg_fence();
        ss128p<0, 1>(acc, da, db, k);
        ss128a<0, 1>(acc, dofs(da, 32), dofs(db, 2048));
        ss128a<0, 1>(acc, dofs(da, 4096), dofs(db, 4096));
        ss128a<0, 1>(acc, dofs(da, 4128), dofs(db, 6144));
        wg_commit();
        wg_wait<0>(); pinv<64>(acc);
      }
      }
      bulk_wait_read();
    }
  }
}

typedef CUresult (*EncodeFn)(CUtensorMap*, CUtensorMapDataType, cuuint32_t, void*, const cuuint64_t*, const cuuint64_t*,
                             const cuuint32_t*, const cuuint32_t*, CUtensorMapInterleave, CUtensorMapSwizzle,
                             CUtensorMapL2promotion, CUtensorMapFloatOOBfill);

void encode(EncodeFn fn, CUtensorMap* m, const void* ptr, int rank, const cuuint64_t* dims, const cuuint64_t* strides,
            const cuuint32_t* box, CUtensorMapSwizzle sw, CUtensorMapL2promotion pr) {
  const cuuint32_t es[5] = {1, 1, 1, 1, 1};
  fn(m, CU_TENSOR_MAP_DATA_TYPE_BFLOAT16, rank, const_cast<void*>(ptr), dims, strides, box, es,
     CU_TENSOR_MAP_INTERLEAVE_NONE, sw, pr, CU_TENSOR_MAP_FLOAT_OOB_FILL_NONE);
}

}

extern "C" void kernel_launch(void* const* d_in, const int* in_sizes, int n_in, void* d_out, int out_size) {
  (void)in_sizes; (void)n_in; (void)out_size;
  static EncodeFn fn = nullptr;
  static void *po, *pkv, *pcnt;
  if (!fn) {
    void* p = nullptr; cudaDriverEntryPointQueryResult qr;
    cudaGetDriverEntryPoint("cuTensorMapEncodeTiled", &p, cudaEnableDefault, &qr);
    fn = (EncodeFn)p;
    cudaGetSymbolAddress(&po, g_O); cudaGetSymbolAddress(&pkv, g_kv); cudaGetSymbolAddress(&pcnt, g_cnt);
    cudaFuncSetAttribute(fused_kernel, cudaFuncAttributeMaxDynamicSharedMemorySize, SMEM_BYTES);
  }
  const CUtensorMapL2promotion P128 = CU_TENSOR_MAP_L2_PROMOTION_L2_128B, P0 = CU_TENSOR_MAP_L2_PROMOTION_NONE;
  CUtensorMap mX, mW, mWq, mWo, mK, mV, mH, mQ, mOut, mOutA, mWp;
  { cuuint64_t d[2] = {1024, 2048}, s[1] = {2048}; cuuint32_t bx[2] = {64, 128}, bq[2] = {16, 128};
    encode(fn, &mX, d_in[6], 2, d, s, bx, CU_TENSOR_MAP_SWIZZLE_128B, P128);
    encode(fn, &mQ, d_in[0], 2, d, s, bq, CU_TENSOR_MAP_SWIZZLE_NONE, P128); }
  { cuuint64_t d[3] = {1024, 1024, 3}, s[2] = {6144, 2048}; cuuint32_t bx[3] = {64, 32, 2};
    encode(fn, &mW, d_in[7], 3, d, s, bx, CU_TENSOR_MAP_SWIZZLE_128B, P128); }
  { cuuint64_t d[2] = {1024, 1024}, s[1] = {6144}, so[1] = {2048}; cuuint32_t bx[2] = {64, 64};
    encode(fn, &mWq, d_in[7], 2, d, s, bx, CU_TENSOR_MAP_SWIZZLE_128B, P128);
    encode(fn, &mWo, d_in[8], 2, d, so, bx, CU_TENSOR_MAP_SWIZZLE_128B, P128); }
  { cuuint64_t d[5] = {1024, 2, 4, 4, 32}, s[4] = {2048, 16384, 4096, 65536}; cuuint32_t bx[5] = {64, 2, 4, 4, 4};
    encode(fn, &mWp, d_in[8], 5, d, s, bx, CU_TENSOR_MAP_SWIZZLE_128B, P128); }
  { cuuint64_t d[3] = {1024, 128, 16}, s[2] = {32768, 2048}; cuuint32_t bk[3] = {16, 17, 8}, bv[3] = {16, 16, 8};
    encode(fn, &mK, d_in[1], 3, d, s, bk, CU_TENSOR_MAP_SWIZZLE_32B, P128);
    encode(fn, &mV, d_in[2], 3, d, s, bv, CU_TENSOR_MAP_SWIZZLE_32B, P128); }
  { cuuint64_t d[2] = {16, 131072}, s[1] = {32}; cuuint32_t bx[2] = {16, 128};
    encode(fn, &mH, d_in[4], 2, d, s, bx, CU_TENSOR_MAP_SWIZZLE_32B, CU_TENSOR_MAP_L2_PROMOTION_L2_256B); }
  { cuuint64_t d[2] = {2048, 2048}, s[1] = {4096}; cuuint32_t bx[2] = {64, 16}, ba[2] = {16, 32};
    encode(fn, &mOut, d_out, 2, d, s, bx, CU_TENSOR_MAP_SWIZZLE_128B, P0);
    encode(fn, &mOutA, d_out, 2, d, s, ba, CU_TENSOR_MAP_SWIZZLE_NONE, P0); }
  Params P;
  P.shift = (const __nv_bfloat16*)d_in[3]; P.ssmD = (const __nv_bfloat16*)d_in[5];
  P.x = (const __nv_bfloat16*)d_in[6]; P.w = (const __nv_bfloat16*)d_in[7]; P.out = (__nv_bfloat16*)d_out; P.one = 1;
  P.o = (uint4*)po; P.kv = (float*)pkv; P.cnt = (unsigned*)pcnt;
  P.k = (const char*)d_in[1]; P.v = (const char*)d_in[2];
  P.pt[0] = {(const char*)d_in[6], 16 * 32768, 64 * 32768, 65536, 32768, 256, 4096, 2048};
  P.pt[1] = {(const char*)d_in[7] + 2048, 256, 1024, 16 * 6144, 8 * 6144, 128 * 6144, 6144, 2048};
  P.pt[2] = {(const char*)d_in[7], 512, 128 * 6144, 16 * 6144, 8 * 6144, 256 * 6144, 6144, 256};
  P.pt[3] = {(const char*)d_in[8], 512, 128 * 2048, 16 * 2048, 8 * 2048, 256 * 2048, 2048, 256};
  P.pt[4] = {(const char*)d_in[0], 256, 1024, 32768, 2097152, 262144, 4096, 2048};
  P.pt[5] = {(const char*)d_in[4], 16 * 32768, 64 * 32768, 65536, 32768, 4096, 512, 256};
  const uint8_t pf[32] = {PF_LIST};
  for (int i = 0; i < 32; i++) P.pf[i] = pf[i];
  const uint64_t cd[18] = {CONV_DESC};
  for (int i = 0; i < 18; i++) P.cd[i] = cd[i];
  fused_kernel<<<NCTA, NTHREADS, SMEM_BYTES, cudaStreamPerThread>>>(P, mX, mW, mWq, mWo, mK, mV, mH, mQ, mOut, mOutA, mWp);
}
```
